```python
import torch

def _softmax(x, axis=-1):
    return torch.softmax(x, dim=axis)

def _gelu(x):
    return torch.nn.functional.gelu(x, approximate='tanh')

def _silu(x):
    return torch.nn.functional.silu(x)

def _sigmoid(x):
    return torch.sigmoid(x)

def _layernorm(x, axis=-1, eps=1e-05):
    m = x.mean(dim=axis, keepdim=True)
    v = x.var(dim=axis, keepdim=True, unbiased=False)
    return (x - m) / torch.sqrt(v + eps)

def _scatter_add(tgt, idx, src, axis=0):
    return tgt.clone().index_add_(axis, idx, src)

def _segment_sum(src, seg, n):
    out = torch.zeros((n,) + src.shape[1:], dtype=src.dtype)
    return out.index_add_(0, seg, src)

def _pad(x, pw):
    flat = tuple((v for pair in reversed(pw) for v in pair))
    return torch.nn.functional.pad(x, flat)
kernel_name = 'standalone__kv_cache_quant_pre_rope_vs_post_rope__sampling'

def setup_inputs():

    _w = lambda a: (lambda t: t.to(torch.bfloat16) if t.is_floating_point() else t)(torch.as_tensor(a))
    B, Sq, Skv = (8, 1, 2048)
    H, Dh0 = (32, 192)
    G = -1 if -1 > 0 else Dh0
    G = max(2, G // 2 * 2)
    Dh = max(G, Dh0 // G * G)
    Skv = max(Skv, Sq)
    ng = Dh // G
    bits = 4 if 4 > 1 else 4
    bits = max(2, min(8, bits))
    qmax = (1 << bits) - 1
    half = Dh // 2
    inv = 1.0 / 10000.0 ** (torch.arange(half) / max(1, half))
    ang_k = torch.arange(Skv)[:, None] * inv[None, :]
    ang_q = torch.arange(Skv - Sq, Skv)[:, None] * inv[None, :]
    kc = torch.cat([torch.cos(ang_k), torch.cos(ang_k)], dim=-1)
    ks = torch.cat([torch.sin(ang_k), torch.sin(ang_k)], dim=-1)
    qc = torch.cat([torch.cos(ang_q), torch.cos(ang_q)], dim=-1)
    qs = torch.cat([torch.sin(ang_q), torch.sin(ang_q)], dim=-1)
    qk_i = torch.randint(0, qmax + 1, (B, H, Skv, Dh)).to(torch.int32)
    qv_i = torch.randint(0, qmax + 1, (B, H, Skv, Dh)).to(torch.int32)
    ksc = torch.abs((lambda *s: torch.randn(*s, dtype=torch.bfloat16) * 0.2)(B, H, Skv, ng)) * 0.1 + 0.01
    kzp = torch.full((B, H, Skv, ng), qmax / 2.0)
    vsc = torch.abs((lambda *s: torch.randn(*s, dtype=torch.bfloat16) * 0.2)(B, H, Skv, ng)) * 0.1 + 0.01
    vzp = torch.full((B, H, Skv, ng), qmax / 2.0)
    return {'q': _w((lambda *s: torch.randn(*s, dtype=torch.bfloat16) * 6.4)(B, H, Sq, Dh) * 0.5), 'qk': _w(qk_i), 'k_scales': _w(ksc), 'k_zeros': _w(kzp), 'qv': _w(qv_i), 'v_scales': _w(vsc), 'v_zeros': _w(vzp), 'q_cos': _w(qc), 'q_sin': _w(qs), 'k_cos': _w(kc), 'k_sin': _w(ks)}

def reference(q, qk, k_scales, k_zeros, qv, v_scales, v_zeros, q_cos, q_sin, k_cos, k_sin):
    B, H, Sq, Dh = q.shape
    ng = k_scales.shape[-1]
    G = Dh // ng
    half = Dh // 2
    ks = (lambda x, n, axis: torch.repeat_interleave(x, n, dim=axis))(k_scales, G, axis=-1)
    kz = (lambda x, n, axis: torch.repeat_interleave(x, n, dim=axis))(k_zeros, G, axis=-1)
    k = ((lambda x, dt: x.to(dt))(qk, q.dtype) - kz) * ks
    vs = (lambda x, n, axis: torch.repeat_interleave(x, n, dim=axis))(v_scales, G, axis=-1)
    vz = (lambda x, n, axis: torch.repeat_interleave(x, n, dim=axis))(v_zeros, G, axis=-1)
    v = ((lambda x, dt: x.to(dt))(qv, q.dtype) - vz) * vs
    k1 = k[..., :half].clone()
    k2 = k[..., half:].clone()
    krh = torch.concatenate([-k2, k1], axis=-1)
    kr = k * k_cos[None, None, :, :] + krh * k_sin[None, None, :, :]
    q1 = q[..., :half].clone()
    q2 = q[..., half:].clone()
    qrh = torch.concatenate([-q2, q1], axis=-1)
    qr = q * q_cos[None, None, :, :] + qrh * q_sin[None, None, :, :]
    logits = torch.einsum('bhqd,bhkd->bhqk', qr, kr) * float(Dh) ** (-0.5)
    attn = _softmax(logits, axis=-1)
    out = torch.einsum('bhqk,bhkd->bhqd', attn, v)
    return out
```

```cpp
#include <cuda_runtime.h>
#include <cuda_bf16.h>
#include <stdint.h>

namespace {

constexpr int D      = 192;
constexpr int SKV    = 2048;
constexpr int NHEAD  = 256;
constexpr int WARPS  = 8;
constexpr int TR     = 8;
constexpr int UNIT   = WARPS * TR;
constexpr int KBYTES = TR * D * 4;
constexpr int CBYTES = TR * D * 2;
constexpr int QBYTES = D * 2;
constexpr int NLEV   = 6;

constexpr int OFF_K = 0;
constexpr int OFF_C = OFF_K + KBYTES;
constexpr int OFF_S = OFF_C + CBYTES;
constexpr int OFF_V = OFF_S + CBYTES;
constexpr int OFF_Q = OFF_V + KBYTES;
constexpr int WARP_SMEM = OFF_Q + 512;
constexpr int OFF_PART  = WARPS * WARP_SMEM;
constexpr int OFF_ML    = OFF_PART + 2 * WARPS * D * 4;
constexpr int OFF_BAR   = OFF_ML + 2 * WARPS * 8;
constexpr int OFF_CLAIM = OFF_BAR + (2 * WARPS + 4) * 8;
constexpr int SMEM_BYTES = OFF_CLAIM + 16;

__device__ unsigned int g_queue;
__device__ unsigned long long g_part[NHEAD * (NLEV - 1) * D];

__device__ __forceinline__ uint32_t smem_u32(const void* p) { return (uint32_t)__cvta_generic_to_shared(p); }

__device__ __forceinline__ void mbar_init(uint32_t bar, uint32_t cnt) {
    asm volatile("mbarrier.init.shared::cta.b64 [%0], %1;" ::"r"(bar), "r"(cnt) : "memory");
}
__device__ __forceinline__ void mbar_expect(uint32_t bar, uint32_t bytes) {
    asm volatile("mbarrier.arrive.expect_tx.shared::cta.b64 _, [%0], %1;" ::"r"(bar), "r"(bytes) : "memory");
}
__device__ __forceinline__ void mbar_arrive(uint32_t bar) {
    asm volatile("mbarrier.arrive.shared::cta.b64 _, [%0];" ::"r"(bar) : "memory");
}
__device__ __forceinline__ void mbar_wait(uint32_t bar, uint32_t parity) {
    uint32_t ok;
    int it = 0;
    do {
        asm volatile("{\n.reg .pred p;\nmbarrier.try_wait.parity.shared::cta.b64 p, [%1], %2;\nselp.u32 %0, 1, 0, p;\n}"
                     : "=r"(ok) : "r"(bar), "r"(parity) : "memory");
        if (++it > (1 << 22)) __trap();
    } while (!ok);
}
__device__ __forceinline__ void bulk_stream(uint32_t dst, const void* src, uint32_t bytes, uint32_t bar, uint64_t pol) {
    asm volatile("cp.async.bulk.shared::cluster.global.mbarrier::complete_tx::bytes.L2::cache_hint [%0], [%1], %2, [%3], %4;"
                 ::"r"(dst), "l"(src), "r"(bytes), "r"(bar), "l"(pol) : "memory");
}
__device__ __forceinline__ void bulk_plain(uint32_t dst, const void* src, uint32_t bytes, uint32_t bar) {
    asm volatile("cp.async.bulk.shared::cluster.global.mbarrier::complete_tx::bytes [%0], [%1], %2, [%3];"
                 ::"r"(dst), "l"(src), "r"(bytes), "r"(bar) : "memory");
}
__device__ __forceinline__ int4 lds128(uint32_t a) {
    int4 v;
    asm volatile("ld.shared.v4.s32 {%0,%1,%2,%3}, [%4];" : "=r"(v.x), "=r"(v.y), "=r"(v.z), "=r"(v.w) : "r"(a));
    return v;
}
__device__ __forceinline__ uint2 lds64(uint32_t a) {
    uint2 v;
    asm volatile("ld.shared.v2.u32 {%0,%1}, [%2];" : "=r"(v.x), "=r"(v.y) : "r"(a));
    return v;
}
__device__ __forceinline__ uint32_t ldg32_stream(const void* p) {
    uint32_t v;
    asm volatile("ld.global.nc.L1::no_allocate.u32 %0, [%1];" : "=r"(v) : "l"(p));
    return v;
}
__device__ __forceinline__ float bf_lo(uint32_t v) { return __uint_as_float(v << 16); }
__device__ __forceinline__ float bf_hi(uint32_t v) { return __uint_as_float(v & 0xffff0000u); }
__device__ __forceinline__ float rbf(float x) { return __bfloat162float(__float2bfloat16_rn(x)); }
__device__ __forceinline__ float ex2(float x) {
    float y;
    asm("ex2.approx.ftz.f32 %0, %1;" : "=f"(y) : "f"(x));
    return y;
}

struct Claim { int head, row0, ntiles, level; };

__device__ __forceinline__ Claim decode_claim(int c, int P) {
    Claim cl;
    const int R = NHEAD - P;
    if (c >= NLEV * R) { cl.head = -1; cl.row0 = 0; cl.ntiles = 0; cl.level = 0; return cl; }
    const int lev = c / R;
    cl.head = P + (c - lev * R);
    cl.level = lev;
    cl.row0 = SKV - (SKV >> lev);
    cl.ntiles = lev == NLEV - 1 ? 1 : (16 >> lev);
    return cl;
}

struct Params {
    const __nv_bfloat16* q; const int* qk; const __nv_bfloat16* ks; const __nv_bfloat16* kz;
    const int* qv; const __nv_bfloat16* vs; const __nv_bfloat16* vz;
    const __nv_bfloat16* qcos; const __nv_bfloat16* qsin; const __nv_bfloat16* kcos; const __nv_bfloat16* ksin;
    __nv_bfloat16* out;
};

__global__ void __launch_bounds__(WARPS * 32, 1)
kv_rope_decode_kernel(const Params p) {
    extern __shared__ __align__(128) unsigned char smem[];
    const int tid = threadIdx.x, w = tid >> 5, lane = tid & 31;
    const int g = lane >> 3, l = lane & 7, godd = g & 1;
    const int P = gridDim.x;
    const uint32_t sbase = smem_u32(smem);
    const uint32_t wbase = sbase + w * WARP_SMEM;
    const uint32_t kbar = sbase + OFF_BAR + w * 8;
    const uint32_t vbar = sbase + OFF_BAR + (WARPS + w) * 8;
    const uint32_t cbar = sbase + OFF_BAR + 2 * WARPS * 8;
    volatile int* claims = reinterpret_cast<volatile int*>(smem + OFF_CLAIM);

    uint64_t pol;
    asm volatile("createpolicy.fractional.L2::evict_first.b64 %0, 1.0;" : "=l"(pol));

    auto issue_k = [&](int head, int row, bool first) {
        mbar_expect(kbar, KBYTES + 2 * CBYTES + (first ? QBYTES : 0));
        bulk_stream(wbase + OFF_K, p.qk + ((size_t)head * SKV + row) * D, KBYTES, kbar, pol);
        bulk_plain(wbase + OFF_C, p.kcos + row * D, CBYTES, kbar);
        bulk_plain(wbase + OFF_S, p.ksin + row * D, CBYTES, kbar);
        if (first) bulk_plain(wbase + OFF_Q, p.q + head * D, QBYTES, kbar);
    };
    auto issue_v = [&](int head, int row) {
        mbar_expect(vbar, KBYTES);
        bulk_stream(wbase + OFF_V, p.qv + ((size_t)head * SKV + row) * D, KBYTES, vbar, pol);
    };

    Claim cur;
    cur.head = blockIdx.x; cur.row0 = 0; cur.ntiles = SKV / UNIT; cur.level = -1;

    if (lane == 0) {
        mbar_init(kbar, 1);
        mbar_init(vbar, 1);
        if (w == 0) for (int i = 0; i < 4; i++) mbar_init(cbar + i * 8, 1);
        asm volatile("fence.mbarrier_init.release.cluster;" ::: "memory");
        asm volatile("fence.proxy.async.shared::cta;" ::: "memory");
        issue_k(cur.head, w * TR, true);
        issue_v(cur.head, w * TR);
    }
    uint32_t sks, skz, svs, svz;
    {
        const int r = cur.head * SKV + w * TR + 2 * g;
        sks = ldg32_stream(p.ks + r); skz = ldg32_stream(p.kz + r);
        svs = ldg32_stream(p.vs + r); svz = ldg32_stream(p.vz + r);
    }
    uint2 qc[6], qs[6];
#pragma unroll
    for (int j = 0; j < 6; j++) {
        const int blk = (j + 3 * godd) % 6;
        qc[j] = *reinterpret_cast<const uint2*>(p.qcos + blk * 32 + l * 4);
        qs[j] = *reinterpret_cast<const uint2*>(p.qsin + blk * 32 + l * 4);
    }
    __syncthreads();

    const uint32_t ka = wbase + OFF_K + g * (2 * D * 4) + l * 16;
    const uint32_t kA = ka + godd * 384, kB = ka - godd * 384;
    const uint32_t ca = wbase + OFF_C + g * (2 * D * 2) + l * 8;
    const uint32_t cA = ca + godd * 192, cB = ca - godd * 192;
    const uint32_t va = wbase + OFF_V + g * (2 * D * 4) + l * 16;
    const uint32_t qa = wbase + OFF_Q + l * 8;

    const float NEG = -3.0e38f;
    int n = 0;
    uint32_t ph = 0;
    Claim nxt = cur;

    while (true) {
        float qr[24], qx[24], acc[24];
        float m = NEG, lsum = 0.f, corr = 0.f;
#pragma unroll
        for (int i = 0; i < 24; i++) acc[i] = 0.f;

        for (int t = 0; t < cur.ntiles; t++) {
            mbar_wait(kbar, ph);
            if (t == 0) {
                float qv[24];
#pragma unroll
                for (int j = 0; j < 6; j++) {
                    const uint2 v = lds64(qa + j * 64 + (j < 3 ? godd * 192 : -godd * 192));
                    qv[j * 4 + 0] = bf_lo(v.x); qv[j * 4 + 1] = bf_hi(v.x);
                    qv[j * 4 + 2] = bf_lo(v.y); qv[j * 4 + 3] = bf_hi(v.y);
                }
                const float sc = 0.07216878364870322f * 1.4426950408889634f;
#pragma unroll
                for (int j = 0; j < 6; j++) {
                    const bool lowhalf = (j < 3) != (godd != 0);
                    const float c4[4] = {bf_lo(qc[j].x), bf_hi(qc[j].x), bf_lo(qc[j].y), bf_hi(qc[j].y)};
                    const float s4[4] = {bf_lo(qs[j].x), bf_hi(qs[j].x), bf_lo(qs[j].y), bf_hi(qs[j].y)};
#pragma unroll
                    for (int i = 0; i < 4; i++) {
                        const float o = qv[((j + 3) % 6) * 4 + i];
                        const float r = rbf(rbf(qv[j * 4 + i] * c4[i]) + rbf((lowhalf ? -o : o) * s4[i])) * sc;
                        qr[j * 4 + i] = r;
                        qx[j * 4 + i] = lowhalf ? -r : r;
                    }
                }
            }
            float dot[2];
#pragma unroll
            for (int ps = 0; ps < 2; ps++) {
                const float z = ps ? bf_hi(skz) : bf_lo(skz);
                float d0 = 0.f, d1 = 0.f;
#pragma unroll
                for (int j = 0; j < 3; j++) {
                    const int4 xa = lds128(kA + ps * 768 + j * 128);
                    const int4 xb = lds128(kB + ps * 768 + (j + 3) * 128);
                    const uint2 cva = lds64(cA + ps * 384 + j * 64);
                    const uint2 cvb = lds64(cB + ps * 384 + (j + 3) * 64);
                    const uint2 sva = lds64(cA + CBYTES + ps * 384 + j * 64);
                    const uint2 svb = lds64(cB + CBYTES + ps * 384 + (j + 3) * 64);
                    const float ta[4] = {(float)xa.x - z, (float)xa.y - z, (float)xa.z - z, (float)xa.w - z};
                    const float tb[4] = {(float)xb.x - z, (float)xb.y - z, (float)xb.z - z, (float)xb.w - z};
                    const float ca4[4] = {bf_lo(cva.x), bf_hi(cva.x), bf_lo(cva.y), bf_hi(cva.y)};
                    const float cb4[4] = {bf_lo(cvb.x), bf_hi(cvb.x), bf_lo(cvb.y), bf_hi(cvb.y)};
                    const float sa4[4] = {bf_lo(sva.x), bf_hi(sva.x), bf_lo(sva.y), bf_hi(sva.y)};
                    const float sb4[4] = {bf_lo(svb.x), bf_hi(svb.x), bf_lo(svb.y), bf_hi(svb.y)};
#pragma unroll
                    for (int i = 0; i < 4; i++) {
                        const float wa = fmaf(qx[(j + 3) * 4 + i], sb4[i], qr[j * 4 + i] * ca4[i]);
                        const float wb = fmaf(qx[j * 4 + i], sa4[i], qr[(j + 3) * 4 + i] * cb4[i]);
                        d0 = fmaf(ta[i], wa, d0);
                        d1 = fmaf(tb[i], wb, d1);
                    }
                }
                dot[ps] = d0 + d1;
            }
            __syncwarp();
            int nhead = cur.head, nrow = cur.row0 + (t + 1) * UNIT + w * TR;
            bool nfirst = false, nlast = (t + 2 == cur.ntiles);
            if (t + 1 == cur.ntiles) {
                mbar_wait(cbar + (n & 3) * 8, (n >> 2) & 1);
                nxt = decode_claim(claims[n & 3], P);
                nhead = nxt.head; nrow = nxt.row0 + w * TR; nfirst = true; nlast = (nxt.ntiles == 1);
            }
            uint32_t nks = 0, nkz = 0, nvs = 0, nvz = 0;
            if (nhead >= 0) {
                if (lane == 0) issue_k(nhead, nrow, nfirst);
                const int r = nhead * SKV + nrow + 2 * g;
                nks = ldg32_stream(p.ks + r); nkz = ldg32_stream(p.kz + r);
                nvs = ldg32_stream(p.vs + r); nvz = ldg32_stream(p.vz + r);
                if (nlast && tid == 0) {
                    const int seq = n + (nfirst ? 1 : 0);
                    claims[seq & 3] = (int)atomicInc(&g_queue, (unsigned)(NLEV * (NHEAD - P) + P - 1));
                    mbar_arrive(cbar + (seq & 3) * 8);
                }
            }
#pragma unroll
            for (int o = 1; o < 8; o <<= 1) {
                dot[0] += __shfl_xor_sync(0xffffffffu, dot[0], o);
                dot[1] += __shfl_xor_sync(0xffffffffu, dot[1], o);
            }
            const float s0 = dot[0] * bf_lo(sks), s1 = dot[1] * bf_hi(sks);
            const float mn = fmaxf(m, fmaxf(s0, s1));
            if (__any_sync(0xffffffffu, mn > m)) {
                const float a = ex2(m - mn);
                lsum *= a; corr *= a;
#pragma unroll
                for (int i = 0; i < 24; i++) acc[i] *= a;
                m = mn;
            }
            const float p0 = ex2(s0 - m), p1 = ex2(s1 - m);
            lsum += p0 + p1;
            const float pv0 = p0 * bf_lo(svs), pv1 = p1 * bf_hi(svs);
            corr = fmaf(pv0, bf_lo(svz), fmaf(pv1, bf_hi(svz), corr));
            mbar_wait(vbar, ph);
#pragma unroll
            for (int j = 0; j < 6; j++) {
                const int4 x0 = lds128(va + j * 128);
                const int4 x1 = lds128(va + 768 + j * 128);
                acc[j * 4 + 0] = fmaf(pv1, (float)x1.x, fmaf(pv0, (float)x0.x, acc[j * 4 + 0]));
                acc[j * 4 + 1] = fmaf(pv1, (float)x1.y, fmaf(pv0, (float)x0.y, acc[j * 4 + 1]));
                acc[j * 4 + 2] = fmaf(pv1, (float)x1.z, fmaf(pv0, (float)x0.z, acc[j * 4 + 2]));
                acc[j * 4 + 3] = fmaf(pv1, (float)x1.w, fmaf(pv0, (float)x0.w, acc[j * 4 + 3]));
            }
            __syncwarp();
            if (nhead >= 0 && lane == 0) issue_v(nhead, nrow);
            sks = nks; skz = nkz; svs = nvs; svz = nvz;
            ph ^= 1;
        }

        float mw = fmaxf(m, __shfl_xor_sync(0xffffffffu, m, 8));
        mw = fmaxf(mw, __shfl_xor_sync(0xffffffffu, mw, 16));
        const float a = ex2(m - mw);
        lsum *= a;
        lsum += __shfl_xor_sync(0xffffffffu, lsum, 8);
        lsum += __shfl_xor_sync(0xffffffffu, lsum, 16);
        float* part = reinterpret_cast<float*>(smem + OFF_PART) + (n & 1) * WARPS * D;
        float2* ml = reinterpret_cast<float2*>(smem + OFF_ML) + (n & 1) * WARPS;
        {
            float u[12];
            const bool up = lane & 16;
#pragma unroll
            for (int i = 0; i < 12; i++) {
                const float lo = (acc[i] - corr) * a, hi = (acc[12 + i] - corr) * a;
                u[i] = (up ? hi : lo) + __shfl_xor_sync(0xffffffffu, up ? lo : hi, 16);
            }
            const bool up2 = lane & 8;
#pragma unroll
            for (int j = 0; j < 3; j++) {
                float2 v;
                v.x = (up2 ? u[j * 4 + 2] : u[j * 4 + 0]) + __shfl_xor_sync(0xffffffffu, up2 ? u[j * 4 + 0] : u[j * 4 + 2], 8);
                v.y = (up2 ? u[j * 4 + 3] : u[j * 4 + 1]) + __shfl_xor_sync(0xffffffffu, up2 ? u[j * 4 + 1] : u[j * 4 + 3], 8);
                *reinterpret_cast<float2*>(part + w * D + (j + (up ? 3 : 0)) * 32 + l * 4 + (up2 ? 2 : 0)) = v;
            }
        }
        if (lane == 0) ml[w] = make_float2(mw, lsum);
        __syncthreads();
        if (tid < D) {
            float M = NEG;
#pragma unroll
            for (int i = 0; i < WARPS; i++) M = fmaxf(M, ml[i].x);
            float L = 0.f, o = 0.f;
#pragma unroll
            for (int i = 0; i < WARPS; i++) {
                const float2 v = ml[i];
                const float e = ex2(v.x - M);
                L = fmaf(e, v.y, L);
                o = fmaf(e, part[i * D + tid], o);
            }
            o = o / L;
            if (cur.level < 0) {
                p.out[cur.head * D + tid] = __float2bfloat16_rn(o);
            } else {
                const float lse = M + __log2f(L);
                unsigned long long* slot = g_part + (size_t)cur.head * (NLEV - 1) * D + tid;
                if (cur.level < NLEV - 1) {
                    unsigned long long pk = ((unsigned long long)__float_as_uint(lse) << 32) | __float_as_uint(o);
                    if (pk == 0ull) pk = 0x8000000000000000ull;
                    asm volatile("st.relaxed.gpu.global.u64 [%0], %1;" ::"l"(slot + cur.level * D), "l"(pk) : "memory");
                } else {
                    unsigned long long pk[NLEV - 1];
                    int it = 0;
                    bool ready;
                    do {
                        ready = true;
#pragma unroll
                        for (int i = 0; i < NLEV - 1; i++) {
                            asm volatile("ld.relaxed.gpu.global.u64 %0, [%1];" : "=l"(pk[i]) : "l"(slot + i * D) : "memory");
                            ready = ready && pk[i] != 0ull;
                        }
                        if (++it > (1 << 22)) __trap();
                    } while (!ready);
                    float MM = lse;
#pragma unroll
                    for (int i = 0; i < NLEV - 1; i++) MM = fmaxf(MM, __uint_as_float((uint32_t)(pk[i] >> 32)));
                    float W = ex2(lse - MM), O = W * o;
#pragma unroll
                    for (int i = 0; i < NLEV - 1; i++) {
                        const float e = ex2(__uint_as_float((uint32_t)(pk[i] >> 32)) - MM);
                        W += e;
                        O = fmaf(e, __uint_as_float((uint32_t)pk[i]), O);
                        slot[i * D] = 0ull;
                    }
                    p.out[cur.head * D + tid] = __float2bfloat16_rn(O / W);
                }
            }
        }
        if (nxt.head < 0) break;
        cur = nxt;
        n++;
    }
}

}

extern "C" void kernel_launch(void* const* d_in, const int* in_sizes, int n_in, void* d_out, int out_size) {
    (void)in_sizes; (void)n_in; (void)out_size;
    static int sms = 0;
    if (sms == 0) {
        int dev = 0;
        cudaGetDevice(&dev);
        cudaDeviceGetAttribute(&sms, cudaDevAttrMultiProcessorCount, dev);
        if (sms > NHEAD - 1) sms = NHEAD - 1;
        cudaFuncSetAttribute(kv_rope_decode_kernel, cudaFuncAttributeMaxDynamicSharedMemorySize, SMEM_BYTES);
    }
    Params p;
    p.q    = (const __nv_bfloat16*)d_in[0];
    p.qk   = (const int*)d_in[1];
    p.ks   = (const __nv_bfloat16*)d_in[2];
    p.kz   = (const __nv_bfloat16*)d_in[3];
    p.qv   = (const int*)d_in[4];
    p.vs   = (const __nv_bfloat16*)d_in[5];
    p.vz   = (const __nv_bfloat16*)d_in[6];
    p.qcos = (const __nv_bfloat16*)d_in[7];
    p.qsin = (const __nv_bfloat16*)d_in[8];
    p.kcos = (const __nv_bfloat16*)d_in[9];
    p.ksin = (const __nv_bfloat16*)d_in[10];
    p.out  = (__nv_bfloat16*)d_out;
    kv_rope_decode_kernel<<<sms, WARPS * 32, SMEM_BYTES>>>(p);
}
```

```cpp
#include <cuda_runtime.h>
#include <cuda_bf16.h>
#include <stdint.h>

namespace {

#define CFG_NCONS 4
#define CFG_NMERG 2
#define CFG_NSLOT 8
#define CFG_MAIN 64
#define CFG_MINP 4
#define CFG_LA 4
#define CFG_NTAILH 128

constexpr int D      = 192;
constexpr int SKV    = 2048;
constexpr int NHEAD  = 256;
constexpr int TR     = 8;
constexpr int TPH    = SKV / TR;
constexpr int NCONS  = CFG_NCONS;
constexpr int NMERG  = CFG_NMERG;
constexpr int NSLOT  = CFG_NSLOT;
constexpr int NSEG   = 8;
constexpr int SEGT   = 16;
constexpr int NTHREADS = (NCONS + 1 + NMERG) * 32;

constexpr int MAINP  = CFG_MAIN;
constexpr int MINP   = CFG_MINP;
constexpr int LA     = CFG_LA;
constexpr int NTAILH = CFG_NTAILH;
constexpr int ilog2(int x) { return x <= 1 ? 0 : 1 + ilog2(x / 2); }
constexpr int PH     = TPH / MAINP;
constexpr int NH0    = NHEAD - NTAILH;
constexpr int NTL    = ilog2(MAINP / MINP) + 1;
constexpr int NMAINC = NH0 * PH + NTAILH * (PH - 1);
constexpr int NCLAIM = NMAINC + NTL * NTAILH;
constexpr int MAXP   = PH - 1 + NTL;

constexpr int KBYTES = TR * D * 4;
constexpr int CBYTES = TR * D * 2;
constexpr int QBYTES = D * 2;
constexpr int T_K = 0, T_C = KBYTES, T_S = T_C + CBYTES, T_V = T_S + CBYTES, TILE_BYTES = T_V + KBYTES;
constexpr int SCB = SEGT * TR * 2;
constexpr int S_Q = 0, S_SC = QBYTES, S_DESC = S_SC + 4 * SCB, S_ML = S_DESC + 16;
constexpr int S_PART = (S_ML + NCONS * 8 + 127) / 128 * 128, SEG_BYTES = S_PART + NCONS * D * 4;
constexpr int OFF_SEG = NSLOT * TILE_BYTES;
constexpr int OFF_BAR = OFF_SEG + NSEG * SEG_BYTES;
constexpr int B_FK = 0, B_FV = NSLOT * 8, B_EM = 2 * NSLOT * 8, B_HDR = 3 * NSLOT * 8, B_PF = B_HDR + NSEG * 8,
              B_SE = B_PF + NSEG * 8;
constexpr int SMEM_BYTES = OFF_BAR + B_SE + NSEG * 8;
static_assert(SMEM_BYTES <= 232448, "smem");
static_assert(NSEG % NMERG == 0 && NCONS <= NSLOT && LA <= SEGT, "cfg");

__device__ unsigned int g_queue;
__device__ uint4 g_mail[NHEAD * MAXP * 64];

__device__ __forceinline__ uint32_t smem_u32(const void* p) { return (uint32_t)__cvta_generic_to_shared(p); }
__device__ __forceinline__ bool elect_one() {
    uint32_t pred;
    asm volatile("{\n.reg .pred p;\nelect.sync _|p, 0xffffffff;\nselp.u32 %0, 1, 0, p;\n}" : "=r"(pred));
    return pred;
}
__device__ __forceinline__ void mbar_init(uint32_t bar, uint32_t cnt) {
    asm volatile("mbarrier.init.shared::cta.b64 [%0], %1;" ::"r"(bar), "r"(cnt) : "memory");
}
__device__ __forceinline__ void mbar_expect(uint32_t bar, uint32_t bytes) {
    asm volatile("mbarrier.arrive.expect_tx.shared::cta.b64 _, [%0], %1;" ::"r"(bar), "r"(bytes) : "memory");
}
__device__ __forceinline__ void mbar_arrive(uint32_t bar) {
    asm volatile("mbarrier.arrive.shared::cta.b64 _, [%0];" ::"r"(bar) : "memory");
}
__device__ __forceinline__ void mbar_wait(uint32_t bar, uint32_t parity) {
    uint32_t ok;
    int it = 0;
    do {
        asm volatile("{\n.reg .pred p;\nmbarrier.try_wait.parity.shared::cta.b64 p, [%1], %2;\nselp.u32 %0, 1, 0, p;\n}"
                     : "=r"(ok) : "r"(bar), "r"(parity) : "memory");
        if (++it > (1 << 22)) __trap();
    } while (!ok);
}
__device__ __forceinline__ void bulk_stream(uint32_t dst, const void* src, uint32_t bytes, uint32_t bar, uint64_t pol) {
    asm volatile("cp.async.bulk.shared::cluster.global.mbarrier::complete_tx::bytes.L2::cache_hint [%0], [%1], %2, [%3], %4;"
                 ::"r"(dst), "l"(src), "r"(bytes), "r"(bar), "l"(pol) : "memory");
}
__device__ __forceinline__ void bulk_plain(uint32_t dst, const void* src, uint32_t bytes, uint32_t bar) {
    asm volatile("cp.async.bulk.shared::cluster.global.mbarrier::complete_tx::bytes [%0], [%1], %2, [%3];"
                 ::"r"(dst), "l"(src), "r"(bytes), "r"(bar) : "memory");
}
__device__ __forceinline__ int4 lds128(uint32_t a) {
    int4 v;
    asm volatile("ld.shared.v4.s32 {%0,%1,%2,%3}, [%4];" : "=r"(v.x), "=r"(v.y), "=r"(v.z), "=r"(v.w) : "r"(a));
    return v;
}
__device__ __forceinline__ uint2 lds64(uint32_t a) {
    uint2 v;
    asm volatile("ld.shared.v2.u32 {%0,%1}, [%2];" : "=r"(v.x), "=r"(v.y) : "r"(a));
    return v;
}
__device__ __forceinline__ uint32_t lds32(uint32_t a) {
    uint32_t v;
    asm volatile("ld.shared.u32 %0, [%1];" : "=r"(v) : "r"(a));
    return v;
}
__device__ __forceinline__ void sts64(uint32_t a, float x, float y) {
    asm volatile("st.shared.v2.f32 [%0], {%1,%2};" ::"r"(a), "f"(x), "f"(y) : "memory");
}
__device__ __forceinline__ float bf_lo(uint32_t v) { return __uint_as_float(v << 16); }
__device__ __forceinline__ float bf_hi(uint32_t v) { return __uint_as_float(v & 0xffff0000u); }
__device__ __forceinline__ float rbf(float x) { return __bfloat162float(__float2bfloat16_rn(x)); }
__device__ __forceinline__ float ex2(float x) {
    float y;
    asm("ex2.approx.ftz.f32 %0, %1;" : "=f"(y) : "f"(x));
    return y;
}
__device__ __forceinline__ uint32_t bmul(uint32_t a, uint32_t b) {
    uint32_t d; asm("mul.rn.bf16x2 %0, %1, %2;" : "=r"(d) : "r"(a), "r"(b)); return d;
}
__device__ __forceinline__ uint32_t bsub(uint32_t a, uint32_t b) {
    uint32_t d; asm("sub.rn.bf16x2 %0, %1, %2;" : "=r"(d) : "r"(a), "r"(b)); return d;
}
__device__ __forceinline__ uint32_t bfma(uint32_t a, uint32_t b, uint32_t c) {
    uint32_t d; asm("fma.rn.bf16x2 %0, %1, %2, %3;" : "=r"(d) : "r"(a), "r"(b), "r"(c)); return d;
}
__device__ __forceinline__ uint32_t i2bf2(int lo, int hi) {
    uint32_t d; asm("cvt.rn.bf16x2.f32 %0, %1, %2;" : "=r"(d) : "f"((float)hi), "f"((float)lo)); return d;
}
__device__ __forceinline__ uint32_t rope2(uint32_t x, uint32_t c, uint32_t y, uint32_t s, uint32_t sg) {
    return bfma(bmul(y, s), sg, bmul(x, c));
}
__device__ __forceinline__ void mma_bf16(float (&c)[4], uint32_t a0, uint32_t a1, uint32_t a2, uint32_t a3,
                                         uint32_t b0, uint32_t b1) {
    asm("mma.sync.aligned.m16n8k16.row.col.f32.bf16.bf16.f32 {%0,%1,%2,%3}, {%4,%5,%6,%7}, {%8,%9}, {%0,%1,%2,%3};"
        : "+f"(c[0]), "+f"(c[1]), "+f"(c[2]), "+f"(c[3])
        : "r"(a0), "r"(a1), "r"(a2), "r"(a3), "r"(b0), "r"(b1));
}
__device__ __forceinline__ uint32_t nz(float x) {
    const uint32_t u = __float_as_uint(x);
    return u == 0u ? 0x80000000u : u;
}

#define TS(i)
#define TILE_TS(cnt)

struct Claim { int head, tile0, ntiles, piece, npieces; };

__device__ __forceinline__ Claim decode_claim(int c) {
    Claim cl;
    if (c < NH0 * PH) {
        cl.head = c / PH; cl.piece = c % PH; cl.tile0 = cl.piece * MAINP; cl.ntiles = MAINP; cl.npieces = PH;
    } else if (PH > 1 && c < NMAINC) {
        constexpr int Q = PH > 1 ? PH - 1 : 1;
        const int k = c - NH0 * PH;
        cl.head = NH0 + k / Q; cl.piece = k % Q; cl.tile0 = cl.piece * MAINP; cl.ntiles = MAINP; cl.npieces = MAXP;
    } else {
        const int k = c - NMAINC, lev = k / NTAILH;
        cl.head = NH0 + k % NTAILH; cl.piece = PH - 1 + lev; cl.tile0 = TPH - (MAINP >> lev);
        cl.ntiles = lev == NTL - 1 ? MINP : (MAINP >> (lev + 1)); cl.npieces = MAXP;
    }
    return cl;
}

struct Params {
    const __nv_bfloat16* q; const int* qk; const __nv_bfloat16* ks; const __nv_bfloat16* kz;
    const int* qv; const __nv_bfloat16* vs; const __nv_bfloat16* vz;
    const __nv_bfloat16* qcos; const __nv_bfloat16* qsin; const __nv_bfloat16* kcos; const __nv_bfloat16* ksin;
    __nv_bfloat16* out;
};

constexpr float NEG = -3.0e38f;
constexpr float LOG2E = 1.4426950408889634f;

__global__ void __launch_bounds__(NTHREADS, 1)
kv_rope_decode_kernel(const Params p) {
    extern __shared__ __align__(128) unsigned char smem[];
    const int w = __shfl_sync(0xffffffffu, threadIdx.x >> 5, 0), lane = threadIdx.x & 31;
    const uint32_t sb = smem_u32(smem);
    const uint32_t bar = sb + OFF_BAR;

    if (w == NCONS) {
        TS(0);
        if (elect_one()) {
#pragma unroll
            for (int i = 0; i < NSLOT; i++) {
                mbar_init(bar + B_FK + i * 8, 1);
                mbar_init(bar + B_FV + i * 8, 1);
                mbar_init(bar + B_EM + i * 8, 1);
            }
#pragma unroll
            for (int i = 0; i < NSEG; i++) {
                mbar_init(bar + B_HDR + i * 8, 1);
                mbar_init(bar + B_PF + i * 8, NCONS);
                mbar_init(bar + B_SE + i * 8, 1);
            }
            asm volatile("fence.mbarrier_init.release.cluster;" ::: "memory");
        }
    }
    __syncthreads();

    if (w == NCONS) {
        if (elect_one()) {
            uint64_t pol;
            asm volatile("createpolicy.fractional.L2::evict_first.b64 %0, 1.0;" : "=l"(pol));
            int slot = 0, seg = 0;
            uint32_t sph = 1;
            int c = blockIdx.x;
            TS(16);
            while (c < NCLAIM) {
                const Claim cl = decode_claim(c);
                int row = cl.tile0 * TR;
                const int* kp = p.qk + ((size_t)cl.head * SKV + row) * D;
                const int* vp = p.qv + ((size_t)cl.head * SKV + row) * D;
                auto tiles = [&](int cnt) {
                    for (int j = 0; j < cnt; j++) {
                        const uint32_t t = sb + slot * TILE_BYTES, b = bar + slot * 8;
                        mbar_wait(b + B_EM, sph);
                        mbar_expect(b + B_FK, KBYTES + 2 * CBYTES);
                        bulk_stream(t + T_K, kp, KBYTES, b + B_FK, pol);
                        bulk_plain(t + T_C, p.kcos + row * D, CBYTES, b + B_FK);
                        bulk_plain(t + T_S, p.ksin + row * D, CBYTES, b + B_FK);
                        mbar_expect(b + B_FV, KBYTES);
                        bulk_stream(t + T_V, vp, KBYTES, b + B_FV, pol);
                        kp += TR * D; vp += TR * D; row += TR;
                        if (++slot == NSLOT) { slot = 0; sph ^= 1; }
                    }
                };
                for (int done = 0; done < cl.ntiles;) {
                    const int nt = min(SEGT, cl.ntiles - done);
                    const bool first = done == 0, last = done + nt == cl.ntiles;
                    const uint32_t s = sb + OFF_SEG + (seg % NSEG) * SEG_BYTES, b = bar + (seg % NSEG) * 8;
                    mbar_wait(b + B_SE, ((seg / NSEG) & 1) ^ 1);
                    asm volatile("st.shared.v4.s32 [%0], {%1,%2,%3,%4};" ::"r"(s + S_DESC), "r"(cl.head),
                                 "r"(nt | (first ? 256 : 0) | (last ? 512 : 0)), "r"(cl.piece), "r"(cl.npieces) : "memory");
                    const uint32_t scb = nt * TR * 2;
                    const int r = cl.head * SKV + row;
                    mbar_expect(b + B_HDR, 4 * scb + (first ? QBYTES : 0));
                    if (first) bulk_stream(s + S_Q, p.q + cl.head * D, QBYTES, b + B_HDR, pol);
                    bulk_stream(s + S_SC, p.ks + r, scb, b + B_HDR, pol);
                    bulk_stream(s + S_SC + SCB, p.kz + r, scb, b + B_HDR, pol);
                    bulk_stream(s + S_SC + 2 * SCB, p.vs + r, scb, b + B_HDR, pol);
                    bulk_stream(s + S_SC + 3 * SCB, p.vz + r, scb, b + B_HDR, pol);
                    seg++;
                    done += nt;
                    if (!last) {
                        tiles(nt);
                    } else {
                        const int pre = max(nt - LA, 0);
                        tiles(pre);
                        const unsigned nx = atomicInc(&g_queue, NCLAIM - 1);
                        tiles(nt - pre);
                        c = gridDim.x + nx;
                    }
                }
            }
            for (int i = 0; i < NMERG; i++, seg++) {
                const uint32_t s = sb + OFF_SEG + (seg % NSEG) * SEG_BYTES, b = bar + (seg % NSEG) * 8;
                mbar_wait(b + B_SE, ((seg / NSEG) & 1) ^ 1);
                asm volatile("st.shared.s32 [%0], %1;" ::"r"(s + S_DESC), "r"(-1) : "memory");
                mbar_arrive(b + B_HDR);
            }
        }
    } else if (w < NCONS) {
        const int g = lane >> 3, l = lane & 7, godd = g & 1;
        const uint32_t sgA = godd ? 0x3f803f80u : 0xbf80bf80u, sgB = sgA ^ 0x80008000u;
        uint2 qc[6], qs[6];
#pragma unroll
        for (int j = 0; j < 6; j++) {
            const int blk = (j + 3 * godd) % 6;
            qc[j] = *reinterpret_cast<const uint2*>(p.qcos + blk * 32 + l * 4);
            qs[j] = *reinterpret_cast<const uint2*>(p.qsin + blk * 32 + l * 4);
        }
        const uint32_t oV = g * (2 * D * 4) + l * 16;
        const uint32_t oKA = oV + godd * 384, oKB = oV - godd * 384 + 384;
        const uint32_t oCA = T_C + g * (2 * D * 2) + l * 8 + godd * 192, oCB = oCA - godd * 384 + 192;

        uint2 qr[6];
        float acc[24], m = NEG, lsum = 0.f, corr = 0.f;
        int slot = w, j0 = w;
        uint32_t tph = 0;
        for (int seg = 0;; seg++) {
            const uint32_t s = sb + OFF_SEG + (seg % NSEG) * SEG_BYTES, sbar = bar + (seg % NSEG) * 8;
            mbar_wait(sbar + B_HDR, (seg / NSEG) & 1);
            const uint2 desc = lds64(s + S_DESC);
            if ((int)desc.x < 0) break;
            const int nt = desc.y & 255;
            if (desc.y & 256) {
#pragma unroll
                for (int j = 0; j < 3; j++) {
                    const uint2 a = lds64(s + S_Q + l * 8 + godd * 192 + j * 64);
                    const uint2 b = lds64(s + S_Q + l * 8 - godd * 192 + 192 + j * 64);
                    qr[j].x = rope2(a.x, qc[j].x, b.x, qs[j].x, sgA);
                    qr[j].y = rope2(a.y, qc[j].y, b.y, qs[j].y, sgA);
                    qr[j + 3].x = rope2(b.x, qc[j + 3].x, a.x, qs[j + 3].x, sgB);
                    qr[j + 3].y = rope2(b.y, qc[j + 3].y, a.y, qs[j + 3].y, sgB);
                }
#pragma unroll
                for (int i = 0; i < 24; i++) acc[i] = 0.f;
                m = NEG; lsum = 0.f; corr = 0.f;
            }
            int j = j0;
            for (; j < nt; j += NCONS) {
                const uint32_t t = sb + slot * TILE_BYTES, b = bar + slot * 8;
                const uint32_t sc = s + S_SC + j * (TR * 2) + g * 4;
                const uint32_t sks = lds32(sc), skz = lds32(sc + SCB), svs = lds32(sc + 2 * SCB), svz = lds32(sc + 3 * SCB);
                const uint32_t ks2[2] = {__byte_perm(sks, 0, 0x1010), __byte_perm(sks, 0, 0x3232)};
                const uint32_t kz2[2] = {__byte_perm(skz, 0, 0x1010), __byte_perm(skz, 0, 0x3232)};
                mbar_wait(b + B_FK, tph);
                TILE_TS(tcnt);
                float cA[4] = {0.f, 0.f, 0.f, 0.f}, cB[4] = {0.f, 0.f, 0.f, 0.f};
#pragma unroll
                for (int jj = 0; jj < 3; jj++) {
                    uint2 ra[2], rb[2];
#pragma unroll
                    for (int ps = 0; ps < 2; ps++) {
                        const int4 xa = lds128(t + oKA + ps * 768 + jj * 128);
                        const int4 xb = lds128(t + oKB + ps * 768 + jj * 128);
                        const uint2 ca = lds64(t + oCA + ps * 384 + jj * 64);
                        const uint2 cb = lds64(t + oCB + ps * 384 + jj * 64);
                        const uint2 sa = lds64(t + oCA + CBYTES + ps * 384 + jj * 64);
                        const uint2 sbv = lds64(t + oCB + CBYTES + ps * 384 + jj * 64);
                        const uint32_t a0 = bmul(bsub(i2bf2(xa.x, xa.y), kz2[ps]), ks2[ps]);
                        const uint32_t a1 = bmul(bsub(i2bf2(xa.z, xa.w), kz2[ps]), ks2[ps]);
                        const uint32_t b0 = bmul(bsub(i2bf2(xb.x, xb.y), kz2[ps]), ks2[ps]);
                        const uint32_t b1 = bmul(bsub(i2bf2(xb.z, xb.w), kz2[ps]), ks2[ps]);
                        ra[ps].x = rope2(a0, ca.x, b0, sa.x, sgA);
                        ra[ps].y = rope2(a1, ca.y, b1, sa.y, sgA);
                        rb[ps].x = rope2(b0, cb.x, a0, sbv.x, sgB);
                        rb[ps].y = rope2(b1, cb.y, a1, sbv.y, sgB);
                    }
                    mma_bf16(cA, ra[0].x, ra[1].x, ra[0].y, ra[1].y, qr[jj].x, qr[jj].y);
                    mma_bf16(cB, rb[0].x, rb[1].x, rb[0].y, rb[1].y, qr[jj + 3].x, qr[jj + 3].y);
                }
                const float d0 = __shfl_sync(0xffffffffu, cA[0] + cB[0], 9 * g) + __shfl_sync(0xffffffffu, cA[1] + cB[1], 9 * g + 4);
                const float d1 = __shfl_sync(0xffffffffu, cA[2] + cB[2], 9 * g) + __shfl_sync(0xffffffffu, cA[3] + cB[3], 9 * g + 4);
                const float s0 = rbf(rbf(d0) * 0.07216878364870322f) * LOG2E;
                const float s1 = rbf(rbf(d1) * 0.07216878364870322f) * LOG2E;
                const float mn = fmaxf(m, fmaxf(s0, s1));
                if (__any_sync(0xffffffffu, mn > m)) {
                    const float a = ex2(m - mn);
                    lsum *= a; corr *= a;
#pragma unroll
                    for (int i = 0; i < 24; i++) acc[i] *= a;
                    m = mn;
                }
                const float p0 = ex2(s0 - m), p1 = ex2(s1 - m);
                lsum += p0 + p1;
                const float pv0 = p0 * bf_lo(svs), pv1 = p1 * bf_hi(svs);
                corr = fmaf(pv0, bf_lo(svz), fmaf(pv1, bf_hi(svz), corr));
                mbar_wait(b + B_FV, tph);
                TILE_TS(tcnt);
#pragma unroll
                for (int jj = 0; jj < 6; jj++) {
                    const int4 x0 = lds128(t + T_V + oV + jj * 128);
                    const int4 x1 = lds128(t + T_V + oV + 768 + jj * 128);
                    acc[jj * 4 + 0] = fmaf(pv1, (float)x1.x, fmaf(pv0, (float)x0.x, acc[jj * 4 + 0]));
                    acc[jj * 4 + 1] = fmaf(pv1, (float)x1.y, fmaf(pv0, (float)x0.y, acc[jj * 4 + 1]));
                    acc[jj * 4 + 2] = fmaf(pv1, (float)x1.z, fmaf(pv0, (float)x0.z, acc[jj * 4 + 2]));
                    acc[jj * 4 + 3] = fmaf(pv1, (float)x1.w, fmaf(pv0, (float)x0.w, acc[jj * 4 + 3]));
                }
                __syncwarp();
                if (lane == 0) mbar_arrive(b + B_EM);
                slot += NCONS;
                if (slot >= NSLOT) { slot -= NSLOT; tph ^= 1; }
            }
            if ((desc.y & 512) && j0 < nt) {
                float mw = fmaxf(m, __shfl_xor_sync(0xffffffffu, m, 8));
                mw = fmaxf(mw, __shfl_xor_sync(0xffffffffu, mw, 16));
                const float a = ex2(m - mw);
                float ls = lsum * a;
                ls += __shfl_xor_sync(0xffffffffu, ls, 8);
                ls += __shfl_xor_sync(0xffffffffu, ls, 16);
                float u[12];
                const bool up = lane & 16, up2 = lane & 8;
#pragma unroll
                for (int i = 0; i < 12; i++) {
                    const float lo = (acc[i] - corr) * a, hi = (acc[12 + i] - corr) * a;
                    u[i] = (up ? hi : lo) + __shfl_xor_sync(0xffffffffu, up ? lo : hi, 16);
                }
                const uint32_t pa = s + S_PART + j0 * (D * 4) + (up ? 384 : 0) + l * 16 + (up2 ? 8 : 0);
#pragma unroll
                for (int i = 0; i < 3; i++) {
                    const float x = (up2 ? u[i * 4 + 2] : u[i * 4 + 0]) + __shfl_xor_sync(0xffffffffu, up2 ? u[i * 4 + 0] : u[i * 4 + 2], 8);
                    const float y = (up2 ? u[i * 4 + 3] : u[i * 4 + 1]) + __shfl_xor_sync(0xffffffffu, up2 ? u[i * 4 + 1] : u[i * 4 + 3], 8);
                    sts64(pa + i * 128, x, y);
                }
                if (lane == 0) sts64(s + S_ML + j0 * 8, mw, ls);
            }
            __syncwarp();
            if (lane == 0) mbar_arrive(sbar + B_PF);
            j0 = j - nt;
        }
    } else {
        for (int seg = w - NCONS - 1;; seg += NMERG) {
            const uint32_t s = sb + OFF_SEG + (seg % NSEG) * SEG_BYTES, sbar = bar + (seg % NSEG) * 8;
            const uint32_t ph = (seg / NSEG) & 1;
            mbar_wait(sbar + B_HDR, ph);
            const int4 desc = lds128(s + S_DESC);
            if (desc.x < 0) break;
            const bool last = desc.y & 512, fin = last && desc.z == desc.w - 1;
            uint4* mail = g_mail + desc.x * (MAXP * 64) + lane;
            float M = NEG, W = 0.f, O[6] = {0.f, 0.f, 0.f, 0.f, 0.f, 0.f};
            if (fin) {
                for (int i0 = 0; i0 < desc.z; i0 += 4) {
                    uint4 pk[8];
                    bool ready;
                    int it = 0;
                    do {
                        ready = true;
#pragma unroll
                        for (int i = 0; i < 8; i++) {
                            pk[i] = make_uint4(1u, 1u, 1u, 0xff7fffffu);
                            if (i0 + (i >> 1) < desc.z)
                                asm volatile("ld.relaxed.gpu.global.v4.u32 {%0,%1,%2,%3}, [%4];"
                                             : "=r"(pk[i].x), "=r"(pk[i].y), "=r"(pk[i].z), "=r"(pk[i].w)
                                             : "l"(mail + i0 * 64 + i * 32) : "memory");
                        }
#pragma unroll
                        for (int i = 0; i < 8; i++) ready = ready && pk[i].x && pk[i].y && pk[i].z && pk[i].w;
                        if (++it > (1 << 22)) __trap();
                    } while (!ready);
#pragma unroll
                    for (int i = 0; i < 8; i++)
                        if (i0 + (i >> 1) < desc.z) mail[i0 * 64 + i * 32] = make_uint4(0u, 0u, 0u, 0u);
                    float Mn = M;
#pragma unroll
                    for (int i = 0; i < 8; i += 2) Mn = fmaxf(Mn, __uint_as_float(pk[i].w));
                    const float a = ex2(M - Mn);
                    W *= a;
#pragma unroll
                    for (int i = 0; i < 6; i++) O[i] *= a;
                    M = Mn;
#pragma unroll
                    for (int i = 0; i < 8; i += 2) {
                        const float e = ex2(__uint_as_float(pk[i].w) - M);
                        W += e;
                        O[0] = fmaf(e, __uint_as_float(pk[i].x), O[0]);
                        O[1] = fmaf(e, __uint_as_float(pk[i + 1].x), O[1]);
                        O[2] = fmaf(e, __uint_as_float(pk[i].y), O[2]);
                        O[3] = fmaf(e, __uint_as_float(pk[i + 1].y), O[3]);
                        O[4] = fmaf(e, __uint_as_float(pk[i].z), O[4]);
                        O[5] = fmaf(e, __uint_as_float(pk[i + 1].z), O[5]);
                    }
                }
            }
            mbar_wait(sbar + B_PF, ph);
            if (last) {
                const int np = min(desc.y & 255, NCONS);
                float mi[NCONS], li[NCONS], Mn = M;
#pragma unroll
                for (int i = 0; i < NCONS; i++) {
                    const uint2 v = lds64(s + S_ML + i * 8);
                    mi[i] = i < np ? __uint_as_float(v.x) : NEG;
                    li[i] = __uint_as_float(v.y);
                    Mn = fmaxf(Mn, mi[i]);
                }
                const float a = ex2(M - Mn);
                W *= a;
#pragma unroll
                for (int i = 0; i < 6; i++) O[i] *= a;
#pragma unroll
                for (int i = 0; i < NCONS; i++) {
                    if (i < np) {
                        const float e = ex2(mi[i] - Mn);
                        W = fmaf(e, li[i], W);
#pragma unroll
                        for (int k = 0; k < 6; k++)
                            O[k] = fmaf(e, __uint_as_float(lds32(s + S_PART + i * (D * 4) + k * 128 + lane * 4)), O[k]);
                    }
                }
                const float inv = 1.0f / W;
                if (fin) {
#pragma unroll
                    for (int k = 0; k < 6; k++) p.out[desc.x * D + k * 32 + lane] = __float2bfloat16_rn(O[k] * inv);
                } else {
                    const uint32_t lse = nz(Mn + __log2f(W));
#pragma unroll
                    for (int k = 0; k < 2; k++)
                        asm volatile("st.relaxed.gpu.global.v4.u32 [%0], {%1,%2,%3,%4};" ::"l"(mail + desc.z * 64 + k * 32),
                                     "r"(nz(O[k] * inv)), "r"(nz(O[k + 2] * inv)), "r"(nz(O[k + 4] * inv)), "r"(lse) : "memory");
                }
            }
            __syncwarp();
            if (lane == 0) mbar_arrive(sbar + B_SE);
        }
    }
    TS(2 + w);
}

}

extern "C" void kernel_launch(void* const* d_in, const int* in_sizes, int n_in, void* d_out, int out_size) {
    (void)in_sizes; (void)n_in; (void)out_size;
    static int sms = 0;
    if (sms == 0) {
        int dev = 0;
        cudaGetDevice(&dev);
        cudaDeviceGetAttribute(&sms, cudaDevAttrMultiProcessorCount, dev);
        cudaFuncSetAttribute(kv_rope_decode_kernel, cudaFuncAttributeMaxDynamicSharedMemorySize, SMEM_BYTES);
    }
    Params p;
    p.q    = (const __nv_bfloat16*)d_in[0];
    p.qk   = (const int*)d_in[1];
    p.ks   = (const __nv_bfloat16*)d_in[2];
    p.kz   = (const __nv_bfloat16*)d_in[3];
    p.qv   = (const int*)d_in[4];
    p.vs   = (const __nv_bfloat16*)d_in[5];
    p.vz   = (const __nv_bfloat16*)d_in[6];
    p.qcos = (const __nv_bfloat16*)d_in[7];
    p.qsin = (const __nv_bfloat16*)d_in[8];
    p.kcos = (const __nv_bfloat16*)d_in[9];
    p.ksin = (const __nv_bfloat16*)d_in[10];
    p.out  = (__nv_bfloat16*)d_out;
    kv_rope_decode_kernel<<<sms, NTHREADS, SMEM_BYTES>>>(p);
}
```

```cpp
#include <cuda_runtime.h>
#include <cuda_bf16.h>
#include <stdint.h>

namespace {

#define CFG_NKW 3
#define CFG_NK 9
#define CFG_NV 4
#define CFG_LEAD 4
#define CFG_MAIN 32
#define CFG_FINA 8
#define CFG_FINB 4
#define CFG_T0 16
#define CFG_T1 12
#define CFG_TAPER CFG_T0, CFG_T1
#define CFG_LA 4
#define CFG_PF0 4

constexpr int D      = 192;
constexpr int SKV    = 2048;
constexpr int NHEAD  = 256;
constexpr int TR     = 8;
constexpr int TPH    = SKV / TR;
constexpr int NKW    = CFG_NKW;
constexpr int NVW    = 2;
constexpr int NGW    = 2;
constexpr int NK     = CFG_NK;
constexpr int NV     = CFG_NV;
constexpr int LEAD   = CFG_LEAD;
constexpr int NSEG   = 8;
constexpr int SEGT   = 16;
constexpr int NLG    = 8;
constexpr int W_PROD = 0, W_V = 1, W_K = W_V + NVW, W_G = W_K + NKW, NWARPS = W_G + NGW;

constexpr int MAINP  = CFG_MAIN;
constexpr int FINA   = CFG_FINA;
constexpr int FINB   = CFG_FINB;
constexpr int TAPER[] = {CFG_TAPER};
constexpr int NTAP   = sizeof(TAPER) / sizeof(int);
constexpr int LA     = CFG_LA;
constexpr int PH     = TPH / MAINP;
constexpr int HH     = NHEAD / 2;
constexpr int C_B    = HH * PH;
constexpr int C_T    = C_B + HH * (PH - 1);
constexpr int C_F    = C_T + HH * NTAP;
constexpr int NCLAIM = C_F + NHEAD;
constexpr int MAXM   = PH - 1 + NTAP > PH ? PH - 1 + NTAP : PH;
constexpr int taper_sum(int n) { return n == 0 ? 0 : TAPER[n - 1] + taper_sum(n - 1); }
static_assert(taper_sum(NTAP) + FINB == MAINP && FINA <= SEGT && FINB <= SEGT, "taper");

constexpr int KBYTES = TR * D * 4;
constexpr int CBYTES = TR * D * 2;
constexpr int QBYTES = D * 2;
constexpr int T_C = KBYTES, T_S = T_C + CBYTES, KSLOT = T_S + CBYTES;
constexpr int SCB = SEGT * TR * 2;
constexpr int S_Q = 0, S_SC = QBYTES, S_DESC = S_SC + 4 * SCB, S_TM = S_DESC + 16, S_LG = S_TM + SEGT * 4,
              S_G = S_LG + SEGT * TR * 4, SEG_BYTES = (S_G + 64 * 16 + 127) / 128 * 128;
constexpr int OFF_V = NK * KSLOT, OFF_SEG = OFF_V + NV * KBYTES, OFF_BAR = OFF_SEG + NSEG * SEG_BYTES;
constexpr int B_FK = 0, B_EK = B_FK + NK * 8, B_FV = B_EK + NK * 8, B_EV = B_FV + NV * 8, B_LG = B_EV + NV * 8,
              B_HDR = B_LG + NLG * 8, B_GD = B_HDR + NSEG * 8, B_SE = B_GD + NSEG * 8;
constexpr int SMEM_BYTES = OFF_BAR + B_SE + NSEG * 8;
static_assert(SMEM_BYTES <= 232448, "smem");
static_assert(NSEG % NGW == 0 && NK % NKW == 0 && LA <= 4 && LEAD >= 1, "cfg");
static_assert(LEAD + NV >= 4 && LEAD + NV <= 4 * NLG - 4 && LEAD < 4 * (NSEG - 1), "cfg");

__device__ unsigned int g_queue;
__device__ uint4 g_mail[NHEAD * MAXM * 64];

__device__ __forceinline__ uint32_t smem_u32(const void* p) { return (uint32_t)__cvta_generic_to_shared(p); }
__device__ __forceinline__ bool elect_one() {
    uint32_t pred;
    asm volatile("{\n.reg .pred p;\nelect.sync _|p, 0xffffffff;\nselp.u32 %0, 1, 0, p;\n}" : "=r"(pred));
    return pred;
}
__device__ __forceinline__ void mbar_init(uint32_t bar, uint32_t cnt) {
    asm volatile("mbarrier.init.shared::cta.b64 [%0], %1;" ::"r"(bar), "r"(cnt) : "memory");
}
__device__ __forceinline__ void mbar_expect(uint32_t bar, uint32_t bytes) {
    asm volatile("mbarrier.arrive.expect_tx.shared::cta.b64 _, [%0], %1;" ::"r"(bar), "r"(bytes) : "memory");
}
__device__ __forceinline__ void mbar_arrive(uint32_t bar) {
    asm volatile("mbarrier.arrive.shared::cta.b64 _, [%0];" ::"r"(bar) : "memory");
}
__device__ __forceinline__ void mbar_wait(uint32_t bar, uint32_t parity) {
    uint32_t ok;
    int it = 0;
    do {
        asm volatile("{\n.reg .pred p;\nmbarrier.try_wait.parity.shared::cta.b64 p, [%1], %2;\nselp.u32 %0, 1, 0, p;\n}"
                     : "=r"(ok) : "r"(bar), "r"(parity) : "memory");
        if (++it > (1 << 22)) __trap();
    } while (!ok);
}
__device__ __forceinline__ void bulk_stream(uint32_t dst, const void* src, uint32_t bytes, uint32_t bar, uint64_t pol) {
    asm volatile("cp.async.bulk.shared::cluster.global.mbarrier::complete_tx::bytes.L2::cache_hint [%0], [%1], %2, [%3], %4;"
                 ::"r"(dst), "l"(src), "r"(bytes), "r"(bar), "l"(pol) : "memory");
}
__device__ __forceinline__ void bulk_plain(uint32_t dst, const void* src, uint32_t bytes, uint32_t bar) {
    asm volatile("cp.async.bulk.shared::cluster.global.mbarrier::complete_tx::bytes [%0], [%1], %2, [%3];"
                 ::"r"(dst), "l"(src), "r"(bytes), "r"(bar) : "memory");
}
__device__ __forceinline__ void l2_prefetch(const void* src, uint32_t bytes, uint64_t pol) {
    asm volatile("cp.async.bulk.prefetch.L2.global.L2::cache_hint [%0], %1, %2;" ::"l"(src), "r"(bytes), "l"(pol) : "memory");
}
__device__ __forceinline__ void l2_prefetch(const void* src, uint32_t bytes) {
    asm volatile("cp.async.bulk.prefetch.L2.global [%0], %1;" ::"l"(src), "r"(bytes) : "memory");
}
__device__ __forceinline__ int4 lds128(uint32_t a) {
    int4 v;
    asm volatile("ld.shared.v4.s32 {%0,%1,%2,%3}, [%4];" : "=r"(v.x), "=r"(v.y), "=r"(v.z), "=r"(v.w) : "r"(a));
    return v;
}
__device__ __forceinline__ uint2 lds64(uint32_t a) {
    uint2 v;
    asm volatile("ld.shared.v2.u32 {%0,%1}, [%2];" : "=r"(v.x), "=r"(v.y) : "r"(a));
    return v;
}
__device__ __forceinline__ uint32_t lds32(uint32_t a) {
    uint32_t v;
    asm volatile("ld.shared.u32 %0, [%1];" : "=r"(v) : "r"(a));
    return v;
}
__device__ __forceinline__ uint32_t lds16(uint32_t a) {
    uint16_t v;
    asm volatile("ld.shared.u16 %0, [%1];" : "=h"(v) : "r"(a));
    return v;
}
__device__ __forceinline__ void sts32(uint32_t a, float x) {
    asm volatile("st.shared.f32 [%0], %1;" ::"r"(a), "f"(x) : "memory");
}
__device__ __forceinline__ void sts64(uint32_t a, float x, float y) {
    asm volatile("st.shared.v2.f32 [%0], {%1,%2};" ::"r"(a), "f"(x), "f"(y) : "memory");
}
__device__ __forceinline__ float bf_lo(uint32_t v) { return __uint_as_float(v << 16); }
__device__ __forceinline__ float bf_hi(uint32_t v) { return __uint_as_float(v & 0xffff0000u); }
__device__ __forceinline__ float rbf(float x) { return __bfloat162float(__float2bfloat16_rn(x)); }
__device__ __forceinline__ float ex2(float x) {
    float y;
    asm("ex2.approx.ftz.f32 %0, %1;" : "=f"(y) : "f"(x));
    return y;
}
__device__ __forceinline__ uint32_t bmul(uint32_t a, uint32_t b) {
    uint32_t d; asm("mul.rn.bf16x2 %0, %1, %2;" : "=r"(d) : "r"(a), "r"(b)); return d;
}
__device__ __forceinline__ uint32_t bsub(uint32_t a, uint32_t b) {
    uint32_t d; asm("sub.rn.bf16x2 %0, %1, %2;" : "=r"(d) : "r"(a), "r"(b)); return d;
}
__device__ __forceinline__ uint32_t bfma(uint32_t a, uint32_t b, uint32_t c) {
    uint32_t d; asm("fma.rn.bf16x2 %0, %1, %2, %3;" : "=r"(d) : "r"(a), "r"(b), "r"(c)); return d;
}
__device__ __forceinline__ uint32_t i2bf2(int lo, int hi) {
    uint32_t d; asm("cvt.rn.bf16x2.f32 %0, %1, %2;" : "=r"(d) : "f"((float)hi), "f"((float)lo)); return d;
}
__device__ __forceinline__ uint32_t rope2(uint32_t x, uint32_t c, uint32_t y, uint32_t s, uint32_t sg) {
    return bfma(bmul(y, s), sg, bmul(x, c));
}
__device__ __forceinline__ void mma_bf16(float (&c)[4], uint32_t a0, uint32_t a1, uint32_t a2, uint32_t a3,
                                         uint32_t b0, uint32_t b1) {
    asm("mma.sync.aligned.m16n8k16.row.col.f32.bf16.bf16.f32 {%0,%1,%2,%3}, {%4,%5,%6,%7}, {%8,%9}, {%0,%1,%2,%3};"
        : "+f"(c[0]), "+f"(c[1]), "+f"(c[2]), "+f"(c[3])
        : "r"(a0), "r"(a1), "r"(a2), "r"(a3), "r"(b0), "r"(b1));
}
__device__ __forceinline__ uint32_t nz(float x) {
    const uint32_t u = __float_as_uint(x);
    return u == 0u ? 0x80000000u : u;
}

#define TS(i)
#define TS_ONCE(i)

#define NO_COMPUTE(x) x
struct Claim { int tile0, ntiles, piece; };

__device__ __forceinline__ Claim decode_claim(int c) {
    Claim cl;
    if (c < C_B) {
        cl.piece = c % PH; cl.tile0 = c * MAINP; cl.ntiles = cl.piece == PH - 1 ? MAINP - FINA : MAINP;
    } else if (c < C_T) {
        constexpr int Q = PH > 1 ? PH - 1 : 1;
        const int k = c - C_B;
        cl.piece = k % Q; cl.tile0 = (HH + k / Q) * TPH + cl.piece * MAINP; cl.ntiles = MAINP;
    } else if (c < C_F) {
        const int k = c - C_T, lev = k / HH;
        constexpr int tap[] = {CFG_TAPER};
        int off = 0, n = tap[0];
#pragma unroll
        for (int i = 1; i < NTAP; i++)
            if (lev >= i) { off += n; n = tap[i]; }
        cl.piece = PH - 1 + lev; cl.tile0 = (HH + k % HH + 1) * TPH - MAINP + off; cl.ntiles = n;
    } else {
        const int h = c - C_F;
        cl.piece = h < HH ? PH : PH - 1 + NTAP; cl.ntiles = h < HH ? FINA : FINB; cl.tile0 = (h + 1) * TPH - cl.ntiles;
    }
    return cl;
}

struct Params {
    const __nv_bfloat16* q; const int* qk; const __nv_bfloat16* ks; const __nv_bfloat16* kz;
    const int* qv; const __nv_bfloat16* vs; const __nv_bfloat16* vz;
    const __nv_bfloat16* qcos; const __nv_bfloat16* qsin; const __nv_bfloat16* kcos; const __nv_bfloat16* ksin;
    __nv_bfloat16* out;
};

constexpr float NEG = -3.0e38f;
constexpr float LOG2E = 1.4426950408889634f;
constexpr int F_FIRST = 256, F_LAST = 512, F_FIN = 1024;

__global__ void __launch_bounds__(NWARPS * 32, 1)
kv_rope_decode_kernel(const Params p) {
    extern __shared__ __align__(128) unsigned char smem[];
    const int w = __shfl_sync(0xffffffffu, threadIdx.x >> 5, 0), lane = threadIdx.x & 31;
    const uint32_t sb = smem_u32(smem);
    const uint32_t bar = sb + OFF_BAR;

    if (w == 0) {
        if (CFG_PF0 > 0 && blockIdx.x < C_B && elect_one()) {
            uint64_t pol;
            asm volatile("createpolicy.fractional.L2::evict_first.b64 %0, 1.0;" : "=l"(pol));
            l2_prefetch(p.qk + (size_t)blockIdx.x * (MAINP * TR * D), CFG_PF0 * KBYTES, pol);
        }
    } else if (w == 1) {
        if (elect_one()) {
#pragma unroll
            for (int i = 0; i < NSEG; i++) {
                mbar_init(bar + B_HDR + i * 8, 1);
                mbar_init(bar + B_GD + i * 8, 1);
                mbar_init(bar + B_SE + i * 8, NKW + NVW);
            }
            asm volatile("fence.mbarrier_init.release.cluster;" ::: "memory");
        }
    } else if (w == 2) {
        if (elect_one()) {
#pragma unroll
            for (int i = 0; i < NV; i++) {
                mbar_init(bar + B_FV + i * 8, 1);
                mbar_init(bar + B_EV + i * 8, NVW);
            }
#pragma unroll
            for (int i = 0; i < NLG; i++) mbar_init(bar + B_LG + i * 8, 4);
            asm volatile("fence.mbarrier_init.release.cluster;" ::: "memory");
        }
    } else if (w == 3) {
        if (elect_one()) {
#pragma unroll
            for (int i = 0; i < NK; i++) {
                mbar_init(bar + B_FK + i * 8, 1);
                mbar_init(bar + B_EK + i * 8, 1);
            }
            asm volatile("fence.mbarrier_init.release.cluster;" ::: "memory");
        }
    }
    __syncthreads();

    if (w == W_PROD) {
        if (elect_one()) {
            uint64_t pol;
            asm volatile("createpolicy.fractional.L2::evict_first.b64 %0, 1.0;" : "=l"(pol));
            int kslot = 0, vslot = 0, seg = 0;
            uint32_t kph = 1, vph = 1;
            int pend[LEAD];
#pragma unroll
            for (int i = 0; i < LEAD; i++) pend[i] = -1;
            auto push_v = [&](int tile) {
                if (pend[0] >= 0) {
                    const uint32_t b = bar + vslot * 8;
                    mbar_wait(b + B_EV, vph);
                    mbar_expect(b + B_FV, KBYTES);
                    bulk_stream(sb + OFF_V + vslot * KBYTES, p.qv + (size_t)pend[0] * (TR * D), KBYTES, b + B_FV, pol);
                    if (++vslot == NV) { vslot = 0; vph ^= 1; }
                }
#pragma unroll
                for (int i = 0; i + 1 < LEAD; i++) pend[i] = pend[i + 1];
                pend[LEAD - 1] = tile;
            };
            int c = blockIdx.x;
            TS(1);
            while (c < NCLAIM) {
                const Claim cl = decode_claim(c);
                int tile = cl.tile0;
                auto tiles = [&](int cnt) {
                    for (int j = 0; j < cnt; j++, tile++) {
                        push_v(tile);
                        const uint32_t t = sb + kslot * KSLOT, b = bar + kslot * 8;
                        const int ro = (tile % TPH) * (TR * D);
                        mbar_wait(b + B_EK, kph);
                        mbar_expect(b + B_FK, KSLOT);
                        bulk_stream(t, p.qk + (size_t)tile * (TR * D), KBYTES, b + B_FK, pol);
                        bulk_plain(t + T_C, p.kcos + ro, CBYTES, b + B_FK);
                        bulk_plain(t + T_S, p.ksin + ro, CBYTES, b + B_FK);
                        TS_ONCE(2); TS(3);
                        if (++kslot == NK) { kslot = 0; kph ^= 1; }
                    }
                };
                const int head = cl.tile0 / TPH;
                for (int left = cl.ntiles; left > 0;) {
                    const int nt = min(SEGT, left);
                    const bool first = left == cl.ntiles, last = left == nt;
                    const uint32_t s = sb + OFF_SEG + (seg % NSEG) * SEG_BYTES, b = bar + (seg % NSEG) * 8;
                    mbar_wait(b + B_SE, ((seg / NSEG) & 1) ^ 1);
                    asm volatile("st.shared.v4.s32 [%0], {%1,%2,%3,%3};" ::"r"(s + S_DESC), "r"(head),
                                 "r"(nt | (first ? F_FIRST : 0) | (last ? F_LAST : 0) | (c >= C_F ? F_FIN : 0)),
                                 "r"(cl.piece) : "memory");
                    const uint32_t scb = nt * TR * 2;
                    const int r = tile * TR;
                    mbar_expect(b + B_HDR, 4 * scb + (first ? QBYTES : 0));
                    if (first) bulk_stream(s + S_Q, p.q + head * D, QBYTES, b + B_HDR, pol);
                    bulk_stream(s + S_SC, p.ks + r, scb, b + B_HDR, pol);
                    bulk_stream(s + S_SC + SCB, p.kz + r, scb, b + B_HDR, pol);
                    bulk_stream(s + S_SC + 2 * SCB, p.vs + r, scb, b + B_HDR, pol);
                    bulk_stream(s + S_SC + 3 * SCB, p.vz + r, scb, b + B_HDR, pol);
                    seg++;
                    left -= nt;
                    if (!last) {
                        tiles(nt);
                    } else {
                        tiles(nt - LA);
                        const unsigned nx = atomicInc(&g_queue, NCLAIM - 1);
                        tiles(LA);
                        c = gridDim.x + nx;
                    }
                }
            }
            TS(4);
            for (int i = 0; i < LEAD; i++) push_v(-1);
            TS(5);
            for (int i = 0; i < NGW; i++, seg++) {
                const uint32_t s = sb + OFF_SEG + (seg % NSEG) * SEG_BYTES, b = bar + (seg % NSEG) * 8;
                mbar_wait(b + B_SE, ((seg / NSEG) & 1) ^ 1);
                asm volatile("st.shared.s32 [%0], %1;" ::"r"(s + S_DESC), "r"(-1) : "memory");
                mbar_arrive(b + B_HDR);
            }
        }
    } else if (w < W_K) {
        const int v = w - W_V, g = lane >> 3, l = lane & 7;
        const uint32_t oV = sb + OFF_V + g * (2 * D * 4) + v * 384 + l * 16;
        float acc[12], m = NEG, lsum = 0.f, corr = 0.f;
        int vslot = 0, batch = 0;
        uint32_t vph = 0;
        for (int seg = 0;; seg++) {
            const uint32_t s = sb + OFF_SEG + (seg % NSEG) * SEG_BYTES, sbar = bar + (seg % NSEG) * 8;
            const uint32_t sph = (seg / NSEG) & 1;
            mbar_wait(sbar + B_HDR, sph);
            const int4 desc = lds128(s + S_DESC);
            if (desc.x < 0) break;
            const int nb = (desc.y & 255) >> 2;
            if (desc.y & F_FIRST) {
#pragma unroll
                for (int i = 0; i < 12; i++) acc[i] = 0.f;
                m = NEG; lsum = 0.f; corr = 0.f;
            }
            float c1 = 0.f, c0[3] = {0.f, 0.f, 0.f}, lse = 0.f;
            for (int b = 0; b < nb; b++, batch++) {
                const float vs = bf_lo(lds16(s + S_SC + 2 * SCB + (b * 32 + lane) * 2));
                const float vz = bf_lo(lds16(s + S_SC + 3 * SCB + (b * 32 + lane) * 2));
                mbar_wait(bar + B_LG + (batch % NLG) * 8, (batch / NLG) & 1);
                TS(3);
                const float sv = __uint_as_float(lds32(s + S_LG + (b * 32 + lane) * 4));
                const int4 tm = lds128(s + S_TM + b * 16);
                const float mn = fmaxf(fmaxf(m, fmaxf(__int_as_float(tm.x), __int_as_float(tm.y))),
                                       fmaxf(__int_as_float(tm.z), __int_as_float(tm.w)));
                if (mn > m) {
                    const float a = ex2(m - mn);
                    lsum *= a; corr *= a;
#pragma unroll
                    for (int i = 0; i < 12; i++) acc[i] *= a;
                    m = mn;
                }
                const float pr = ex2(sv - m), pv = pr * vs;
                lsum += pr;
                corr = fmaf(pv, vz, corr);
#pragma unroll
                for (int i = 0; i < 4; i++) {
                    const float pv0 = __shfl_sync(0xffffffffu, pv, 8 * i + 2 * g);
                    const float pv1 = __shfl_sync(0xffffffffu, pv, 8 * i + 2 * g + 1);
                    if (i == 3 && b == nb - 1) {
                        mbar_wait(sbar + B_GD, sph);
                        if (desc.y & F_LAST) {
                            float L = lsum, C = corr;
#pragma unroll
                            for (int o = 16; o > 0; o >>= 1) {
                                L += __shfl_xor_sync(0xffffffffu, L, o);
                                C += __shfl_xor_sync(0xffffffffu, C, o);
                            }
                            int4 gt = make_int4(0, 0, 0, 0xff7fffff);
                            if (desc.y & F_FIN) gt = lds128(s + S_G + (v * 32 + lane) * 16);
                            const float M = fmaxf(m, __int_as_float(gt.w));
                            const float e = ex2(m - M), a = ex2(__int_as_float(gt.w) - M);
                            const float inv = 1.0f / fmaf(L, e, a);
                            c1 = e * inv;
                            c0[0] = fmaf(__int_as_float(gt.x), a * inv, -C * c1);
                            c0[1] = fmaf(__int_as_float(gt.y), a * inv, -C * c1);
                            c0[2] = fmaf(__int_as_float(gt.z), a * inv, -C * c1);
                            lse = m + __log2f(L);
                        }
                    }
                    const uint32_t t = oV + vslot * KBYTES;
                    TS(4);
                    mbar_wait(bar + B_FV + vslot * 8, vph);
                    TS_ONCE(1); TS(5);
#pragma unroll
                    for (int j = 0; j < NO_COMPUTE(3); j++) {
                        const int4 x0 = lds128(t + j * 128);
                        const int4 x1 = lds128(t + 768 + j * 128);
                        acc[j * 4 + 0] = fmaf(pv1, (float)x1.x, fmaf(pv0, (float)x0.x, acc[j * 4 + 0]));
                        acc[j * 4 + 1] = fmaf(pv1, (float)x1.y, fmaf(pv0, (float)x0.y, acc[j * 4 + 1]));
                        acc[j * 4 + 2] = fmaf(pv1, (float)x1.z, fmaf(pv0, (float)x0.z, acc[j * 4 + 2]));
                        acc[j * 4 + 3] = fmaf(pv1, (float)x1.w, fmaf(pv0, (float)x0.w, acc[j * 4 + 3]));
                    }
                    __syncwarp();
                    if (lane == 0) mbar_arrive(bar + B_EV + vslot * 8);
                    TS_ONCE(2);
                    if (++vslot == NV) { vslot = 0; vph ^= 1; }
                }
            }
            if (desc.y & F_LAST) {
                const bool up = lane & 16, up2 = lane & 8;
                float o[3];
#pragma unroll
                for (int j = 0; j < 3; j++) {
                    const float u0 = (up ? acc[j * 4 + 2] : acc[j * 4 + 0]) + __shfl_xor_sync(0xffffffffu, up ? acc[j * 4 + 0] : acc[j * 4 + 2], 16);
                    const float u1 = (up ? acc[j * 4 + 3] : acc[j * 4 + 1]) + __shfl_xor_sync(0xffffffffu, up ? acc[j * 4 + 1] : acc[j * 4 + 3], 16);
                    o[j] = fmaf((up2 ? u1 : u0) + __shfl_xor_sync(0xffffffffu, up2 ? u0 : u1, 8), c1, c0[j]);
                }
                if (desc.y & F_FIN) {
                    __nv_bfloat16* op = p.out + desc.x * D + v * 96 + l * 4 + (up ? 2 : 0) + (up2 ? 1 : 0);
#pragma unroll
                    for (int j = 0; j < 3; j++) op[j * 32] = __float2bfloat16_rn(o[j]);
                } else {
                    asm volatile("st.relaxed.gpu.global.v4.u32 [%0], {%1,%2,%3,%4};"
                                 ::"l"(g_mail + (desc.x * MAXM + desc.z) * 64 + v * 32 + lane),
                                   "r"(nz(o[0])), "r"(nz(o[1])), "r"(nz(o[2])), "r"(nz(lse)) : "memory");
                }
            }
            __syncwarp();
            if (lane == 0) mbar_arrive(sbar + B_SE);
            TS(6);
        }
    } else if (w < W_G) {
        const int g = lane >> 3, l = lane & 7, godd = g & 1;
        const uint32_t sgA = godd ? 0x3f803f80u : 0xbf80bf80u, sgB = sgA ^ 0x80008000u;
        uint2 qc[6], qs[6];
#pragma unroll
        for (int j = 0; j < 6; j++) {
            const int blk = (j + 3 * godd) % 6;
            qc[j] = *reinterpret_cast<const uint2*>(p.qcos + blk * 32 + l * 4);
            qs[j] = *reinterpret_cast<const uint2*>(p.qsin + blk * 32 + l * 4);
        }
        const uint32_t oKA = sb + g * (2 * D * 4) + l * 16 + godd * 384, oKB = oKA - godd * 768 + 384;
        const uint32_t oCA = sb + T_C + g * (2 * D * 2) + l * 8 + godd * 192, oCB = oCA - godd * 384 + 192;
        uint2 qr[6];
        int kslot = w - W_K, j = w - W_K, T = w - W_K;
        uint32_t kph = 0;
        for (int seg = 0;; seg++) {
            const uint32_t s = sb + OFF_SEG + (seg % NSEG) * SEG_BYTES, sbar = bar + (seg % NSEG) * 8;
            mbar_wait(sbar + B_HDR, (seg / NSEG) & 1);
            const uint2 desc = lds64(s + S_DESC);
            if ((int)desc.x < 0) break;
            const int nt = desc.y & 255;
            if (desc.y & F_FIRST) {
#pragma unroll
                for (int i = 0; i < 3; i++) {
                    const uint2 a = lds64(s + S_Q + l * 8 + godd * 192 + i * 64);
                    const uint2 b = lds64(s + S_Q + l * 8 - godd * 192 + 192 + i * 64);
                    qr[i].x = rope2(a.x, qc[i].x, b.x, qs[i].x, sgA);
                    qr[i].y = rope2(a.y, qc[i].y, b.y, qs[i].y, sgA);
                    qr[i + 3].x = rope2(b.x, qc[i + 3].x, a.x, qs[i + 3].x, sgB);
                    qr[i + 3].y = rope2(b.y, qc[i + 3].y, a.y, qs[i + 3].y, sgB);
                }
            }
            for (; j < nt; j += NKW, T += NKW) {
                const uint32_t t = kslot * KSLOT;
                const uint32_t sc = s + S_SC + j * (TR * 2) + g * 4;
                const uint32_t sks = lds32(sc), skz = lds32(sc + SCB);
                const uint32_t ks2[2] = {__byte_perm(sks, 0, 0x1010), __byte_perm(sks, 0, 0x3232)};
                const uint32_t kz2[2] = {__byte_perm(skz, 0, 0x1010), __byte_perm(skz, 0, 0x3232)};
                mbar_wait(bar + B_FK + kslot * 8, kph);
                TS_ONCE(1); TS(3);
                float cA[4] = {0.f, 0.f, 0.f, 0.f}, cB[4] = {0.f, 0.f, 0.f, 0.f};
#pragma unroll
                for (int jj = 0; jj < NO_COMPUTE(3); jj++) {
                    uint2 ra[2], rb[2];
#pragma unroll
                    for (int ps = 0; ps < 2; ps++) {
                        const int4 xa = lds128(t + oKA + ps * 768 + jj * 128);
                        const int4 xb = lds128(t + oKB + ps * 768 + jj * 128);
                        const uint2 ca = lds64(t + oCA + ps * 384 + jj * 64);
                        const uint2 cb = lds64(t + oCB + ps * 384 + jj * 64);
                        const uint2 sa = lds64(t + oCA + CBYTES + ps * 384 + jj * 64);
                        const uint2 sbv = lds64(t + oCB + CBYTES + ps * 384 + jj * 64);
                        const uint32_t a0 = bmul(bsub(i2bf2(xa.x, xa.y), kz2[ps]), ks2[ps]);
                        const uint32_t a1 = bmul(bsub(i2bf2(xa.z, xa.w), kz2[ps]), ks2[ps]);
                        const uint32_t b0 = bmul(bsub(i2bf2(xb.x, xb.y), kz2[ps]), ks2[ps]);
                        const uint32_t b1 = bmul(bsub(i2bf2(xb.z, xb.w), kz2[ps]), ks2[ps]);
                        ra[ps].x = rope2(a0, ca.x, b0, sa.x, sgA);
                        ra[ps].y = rope2(a1, ca.y, b1, sa.y, sgA);
                        rb[ps].x = rope2(b0, cb.x, a0, sbv.x, sgB);
                        rb[ps].y = rope2(b1, cb.y, a1, sbv.y, sgB);
                    }
                    mma_bf16(cA, ra[0].x, ra[1].x, ra[0].y, ra[1].y, qr[jj].x, qr[jj].y);
                    mma_bf16(cB, rb[0].x, rb[1].x, rb[0].y, rb[1].y, qr[jj + 3].x, qr[jj + 3].y);
                }
                __syncwarp();
                if (lane == 0) mbar_arrive(bar + B_EK + kslot * 8);
                TS_ONCE(2);
                const float d0 = __shfl_sync(0xffffffffu, cA[0] + cB[0], 9 * g) + __shfl_sync(0xffffffffu, cA[1] + cB[1], 9 * g + 4);
                const float d1 = __shfl_sync(0xffffffffu, cA[2] + cB[2], 9 * g) + __shfl_sync(0xffffffffu, cA[3] + cB[3], 9 * g + 4);
                const float s0 = rbf(rbf(d0) * 0.07216878364870322f) * LOG2E;
                const float s1 = rbf(rbf(d1) * 0.07216878364870322f) * LOG2E;
                if (l == 0) sts64(s + S_LG + (j * TR + 2 * g) * 4, s0, s1);
                float tm = fmaxf(s0, s1);
                tm = fmaxf(tm, __shfl_xor_sync(0xffffffffu, tm, 8));
                tm = fmaxf(tm, __shfl_xor_sync(0xffffffffu, tm, 16));
                if (lane == 0) sts32(s + S_TM + j * 4, tm);
                __syncwarp();
                if (lane == 0) mbar_arrive(bar + B_LG + ((T >> 2) % NLG) * 8);
                TS(4);
                kslot += NKW;
                if (kslot >= NK) { kslot -= NK; kph ^= 1; }
            }
            j -= nt;
            __syncwarp();
            if (lane == 0) mbar_arrive(sbar + B_SE);
        }
    } else {
        for (int seg = w - W_G;; seg += NGW) {
            const uint32_t s = sb + OFF_SEG + (seg % NSEG) * SEG_BYTES, sbar = bar + (seg % NSEG) * 8;
            mbar_wait(sbar + B_HDR, (seg / NSEG) & 1);
            const int4 desc = lds128(s + S_DESC);
            if (desc.x < 0) break;
            TS(1);
            if (desc.y & F_FIN) {
                uint4* mail = g_mail + desc.x * (MAXM * 64) + lane;
                uint4 pk[2 * MAXM];
                bool ready;
                int it = 0;
                do {
                    ready = true;
#pragma unroll
                    for (int i = 0; i < 2 * MAXM; i++) {
                        pk[i] = make_uint4(1u, 1u, 1u, 0xff7fffffu);
                        if ((i >> 1) < desc.z)
                            asm volatile("ld.relaxed.gpu.global.v4.u32 {%0,%1,%2,%3}, [%4];"
                                         : "=r"(pk[i].x), "=r"(pk[i].y), "=r"(pk[i].z), "=r"(pk[i].w)
                                         : "l"(mail + i * 32) : "memory");
                    }
#pragma unroll
                    for (int i = 0; i < 2 * MAXM; i++) ready = ready && pk[i].x && pk[i].y && pk[i].z && pk[i].w;
                    if (++it > (1 << 22)) __trap();
                } while (!ready);
                float M = NEG, W = 0.f, O[6] = {0.f, 0.f, 0.f, 0.f, 0.f, 0.f};
#pragma unroll
                for (int i = 0; i < 2 * MAXM; i += 2) M = fmaxf(M, __uint_as_float(pk[i].w));
#pragma unroll
                for (int i = 0; i < 2 * MAXM; i += 2) {
                    const float e = ex2(__uint_as_float(pk[i].w) - M);
                    W += e;
                    O[0] = fmaf(e, __uint_as_float(pk[i].x), O[0]);
                    O[1] = fmaf(e, __uint_as_float(pk[i].y), O[1]);
                    O[2] = fmaf(e, __uint_as_float(pk[i].z), O[2]);
                    O[3] = fmaf(e, __uint_as_float(pk[i + 1].x), O[3]);
                    O[4] = fmaf(e, __uint_as_float(pk[i + 1].y), O[4]);
                    O[5] = fmaf(e, __uint_as_float(pk[i + 1].z), O[5]);
                }
                const float inv = 1.0f / W, lse = M + __log2f(W);
#pragma unroll
                for (int k = 0; k < 2; k++)
                    asm volatile("st.shared.v4.f32 [%0], {%1,%2,%3,%4};" ::"r"(s + S_G + (k * 32 + lane) * 16),
                                 "f"(O[3 * k] * inv), "f"(O[3 * k + 1] * inv), "f"(O[3 * k + 2] * inv), "f"(lse) : "memory");
                __syncwarp();
                if (lane == 0) mbar_arrive(sbar + B_GD);
#pragma unroll
                for (int i = 0; i < 2 * MAXM; i++)
                    if ((i >> 1) < desc.z) mail[i * 32] = make_uint4(0u, 0u, 0u, 0u);
            } else
            {
                __syncwarp();
                if (lane == 0) mbar_arrive(sbar + B_GD);
            }
            TS(2);
        }
    }
}

}

extern "C" void kernel_launch(void* const* d_in, const int* in_sizes, int n_in, void* d_out, int out_size) {
    (void)in_sizes; (void)n_in; (void)out_size;
    static int sms = 0;
    if (sms == 0) {
        int dev = 0;
        cudaGetDevice(&dev);
        cudaDeviceGetAttribute(&sms, cudaDevAttrMultiProcessorCount, dev);
        cudaFuncSetAttribute(kv_rope_decode_kernel, cudaFuncAttributeMaxDynamicSharedMemorySize, SMEM_BYTES);
    }
    Params p;
    p.q    = (const __nv_bfloat16*)d_in[0];
    p.qk   = (const int*)d_in[1];
    p.ks   = (const __nv_bfloat16*)d_in[2];
    p.kz   = (const __nv_bfloat16*)d_in[3];
    p.qv   = (const int*)d_in[4];
    p.vs   = (const __nv_bfloat16*)d_in[5];
    p.vz   = (const __nv_bfloat16*)d_in[6];
    p.qcos = (const __nv_bfloat16*)d_in[7];
    p.qsin = (const __nv_bfloat16*)d_in[8];
    p.kcos = (const __nv_bfloat16*)d_in[9];
    p.ksin = (const __nv_bfloat16*)d_in[10];
    p.out  = (__nv_bfloat16*)d_out;
    kv_rope_decode_kernel<<<sms, NWARPS * 32, SMEM_BYTES>>>(p);
}
```

```cpp
#include <cuda_runtime.h>
#include <cuda_bf16.h>
#include <stdint.h>

namespace {

#define CFG_NKW 2
#define CFG_NK 8
#define CFG_NV 4
#define CFG_LEAD 4
#define CFG_MAIN 32
#define CFG_SEMI 0xfdb9
#define CFG_FIN 0x7531
#define CFG_LA 3
#define CFG_PF0 3

constexpr int D      = 192;
constexpr int SKV    = 2048;
constexpr int NHEAD  = 256;
constexpr int TR     = 8;
constexpr int TPH    = SKV / TR;
constexpr int NKW    = CFG_NKW;
constexpr int NVW    = 2;
constexpr int NGW    = 2;
constexpr int NK     = CFG_NK;
constexpr int NV     = CFG_NV;
constexpr int LEAD   = CFG_LEAD;
constexpr int NSEG   = 8;
constexpr int SEGT   = 16;
constexpr int NBAT   = 16;
constexpr int W_V = 2, W_PROD = 4, W_G0 = 5, W_S = 6, W_G1 = 7, NWARPS = 6 + NKW;

constexpr int MAINP  = CFG_MAIN;
constexpr int LA     = CFG_LA;
__host__ __device__ constexpr int semi_size(int h) { return ((CFG_SEMI >> (12 - 4 * (h >> 6))) & 15) + 1; }
__host__ __device__ constexpr int fin_size(int h) { return ((CFG_FIN >> (12 - 4 * (h >> 6))) & 15) + 1; }
constexpr int NM     = (TPH - semi_size(0) - fin_size(0) + MAINP - 1) / MAINP;
constexpr int C_S    = NHEAD * NM, C_F = C_S + NHEAD, NCLAIM = C_F + NHEAD;
constexpr bool sizes_ok(int h) { return h >= NHEAD || (semi_size(h) + fin_size(h) < TPH - (NM - 1) * MAINP && sizes_ok(h + 64)); }
static_assert(sizes_ok(0), "schedule");

constexpr int KBYTES = TR * D * 4;
constexpr int CBYTES = TR * D * 2;
constexpr int QBYTES = D * 2;
constexpr int T_C = KBYTES, T_S = T_C + CBYTES, KSLOT = T_S + CBYTES;
constexpr int SCB = SEGT * TR * 2;
constexpr int S_Q = 0, S_SC = QBYTES, S_DESC = S_SC + 4 * SCB, S_BD = S_DESC + 16, S_TM = S_BD + 4 * 16,
              S_LG = S_TM + SEGT * 4, S_G = S_LG + SEGT * TR * 4, S_LSE = S_G + 64 * 16,
              SEG_BYTES = (S_LSE + 16 + 127) / 128 * 128;
constexpr int OFF_V = NK * KSLOT, OFF_SEG = OFF_V + NV * KBYTES, OFF_BAR = OFF_SEG + NSEG * SEG_BYTES;
constexpr int B_FK = 0, B_EK = 128, B_PR = 256, B_HDR = 384, B_GD = 448, B_FC = 512, B_FV = 576, B_LG = 640,
              B_SE = 768, B_EV = 896;
constexpr int SMEM_BYTES = OFF_BAR + 1024;
static_assert(NK <= 16 && NV <= 8 && NSEG == 8 && NBAT == 16, "barrier layout");
static_assert(SMEM_BYTES <= 232448 && SMEM_BYTES > 232448 / 2, "smem");
static_assert(NSEG % NGW == 0 && NK % NKW == 0 && NKW >= 2 && NKW <= 4 && LEAD >= 1, "cfg");
static_assert(LEAD + NV >= 4 && LEAD + NV < NBAT && LEAD < NSEG, "cfg");

__device__ unsigned int g_queue;
__device__ uint4 g_mail[NHEAD * (NM + 1) * 64];

__device__ __forceinline__ uint32_t smem_u32(const void* p) { return (uint32_t)__cvta_generic_to_shared(p); }
__device__ __forceinline__ bool elect_one() {
    uint32_t pred;
    asm volatile("{\n.reg .pred p;\nelect.sync _|p, 0xffffffff;\nselp.u32 %0, 1, 0, p;\n}" : "=r"(pred));
    return pred;
}
__device__ __forceinline__ void mbar_init(uint32_t bar, uint32_t cnt) {
    asm volatile("mbarrier.init.shared::cta.b64 [%0], %1;" ::"r"(bar), "r"(cnt) : "memory");
}
__device__ __forceinline__ void mbar_expect(uint32_t bar, uint32_t bytes) {
    asm volatile("mbarrier.arrive.expect_tx.shared::cta.b64 _, [%0], %1;" ::"r"(bar), "r"(bytes) : "memory");
}
__device__ __forceinline__ void mbar_arrive(uint32_t bar) {
    asm volatile("mbarrier.arrive.shared::cta.b64 _, [%0];" ::"r"(bar) : "memory");
}
__device__ __forceinline__ void mbar_arrive(uint32_t bar, uint32_t cnt) {
    asm volatile("mbarrier.arrive.shared::cta.b64 _, [%0], %1;" ::"r"(bar), "r"(cnt) : "memory");
}
__device__ __forceinline__ void mbar_wait(uint32_t bar, uint32_t parity) {
    asm volatile("{\n.reg .pred p;\n.reg .u32 n;\n"
                 "mbarrier.try_wait.parity.shared::cta.b64 p, [%0], %1;\n"
                 "@p bra DONE;\n"
                 "mov.u32 n, 0;\n"
                 "LOOP:\n"
                 "mbarrier.try_wait.parity.shared::cta.b64 p, [%0], %1;\n"
                 "@p bra DONE;\n"
                 "add.u32 n, n, 1;\n"
                 "setp.lt.u32 p, n, 0x400000;\n"
                 "@p bra LOOP;\n"
                 "trap;\n"
                 "DONE:\n}" ::"r"(bar), "r"(parity) : "memory");
}
__device__ __forceinline__ void bulk_stream(uint32_t dst, const void* src, uint32_t bytes, uint32_t bar, uint64_t pol) {
    asm volatile("cp.async.bulk.shared::cluster.global.mbarrier::complete_tx::bytes.L2::cache_hint [%0], [%1], %2, [%3], %4;"
                 ::"r"(dst), "l"(src), "r"(bytes), "r"(bar), "l"(pol) : "memory");
}
__device__ __forceinline__ void bulk_plain(uint32_t dst, const void* src, uint32_t bytes, uint32_t bar) {
    asm volatile("cp.async.bulk.shared::cluster.global.mbarrier::complete_tx::bytes [%0], [%1], %2, [%3];"
                 ::"r"(dst), "l"(src), "r"(bytes), "r"(bar) : "memory");
}
__device__ __forceinline__ void l2_prefetch(const void* src, uint32_t bytes, uint64_t pol) {
    asm volatile("cp.async.bulk.prefetch.L2.global.L2::cache_hint [%0], %1, %2;" ::"l"(src), "r"(bytes), "l"(pol) : "memory");
}
__device__ __forceinline__ void l2_prefetch(const void* src, uint32_t bytes) {
    asm volatile("cp.async.bulk.prefetch.L2.global [%0], %1;" ::"l"(src), "r"(bytes) : "memory");
}
__device__ __forceinline__ int4 lds128(uint32_t a) {
    int4 v;
    asm volatile("ld.shared.v4.s32 {%0,%1,%2,%3}, [%4];" : "=r"(v.x), "=r"(v.y), "=r"(v.z), "=r"(v.w) : "r"(a));
    return v;
}
__device__ __forceinline__ uint2 lds64(uint32_t a) {
    uint2 v;
    asm volatile("ld.shared.v2.u32 {%0,%1}, [%2];" : "=r"(v.x), "=r"(v.y) : "r"(a));
    return v;
}
__device__ __forceinline__ uint32_t lds32(uint32_t a) {
    uint32_t v;
    asm volatile("ld.shared.u32 %0, [%1];" : "=r"(v) : "r"(a));
    return v;
}
__device__ __forceinline__ uint32_t lds16(uint32_t a) {
    uint16_t v;
    asm volatile("ld.shared.u16 %0, [%1];" : "=h"(v) : "r"(a));
    return v;
}
__device__ __forceinline__ void sts32(uint32_t a, float x) {
    asm volatile("st.shared.f32 [%0], %1;" ::"r"(a), "f"(x) : "memory");
}
__device__ __forceinline__ void sts128(uint32_t a, uint32_t x, uint32_t y, uint32_t z, uint32_t w) {
    asm volatile("st.shared.v4.u32 [%0], {%1,%2,%3,%4};" ::"r"(a), "r"(x), "r"(y), "r"(z), "r"(w) : "memory");
}
__device__ __forceinline__ void sts64(uint32_t a, float x, float y) {
    asm volatile("st.shared.v2.f32 [%0], {%1,%2};" ::"r"(a), "f"(x), "f"(y) : "memory");
}
__device__ __forceinline__ float bf_lo(uint32_t v) { return __uint_as_float(v << 16); }
__device__ __forceinline__ float bf_hi(uint32_t v) { return __uint_as_float(v & 0xffff0000u); }
__device__ __forceinline__ float rbf(float x) { return __bfloat162float(__float2bfloat16_rn(x)); }
__device__ __forceinline__ float ex2(float x) {
    float y;
    asm("ex2.approx.ftz.f32 %0, %1;" : "=f"(y) : "f"(x));
    return y;
}
__device__ __forceinline__ uint32_t bmul(uint32_t a, uint32_t b) {
    uint32_t d; asm("mul.rn.bf16x2 %0, %1, %2;" : "=r"(d) : "r"(a), "r"(b)); return d;
}
__device__ __forceinline__ uint32_t bsub(uint32_t a, uint32_t b) {
    uint32_t d; asm("sub.rn.bf16x2 %0, %1, %2;" : "=r"(d) : "r"(a), "r"(b)); return d;
}
__device__ __forceinline__ uint32_t bfma(uint32_t a, uint32_t b, uint32_t c) {
    uint32_t d; asm("fma.rn.bf16x2 %0, %1, %2, %3;" : "=r"(d) : "r"(a), "r"(b), "r"(c)); return d;
}
__device__ __forceinline__ uint32_t i2bf2(int lo, int hi) {
    uint32_t d; asm("cvt.rn.bf16x2.f32 %0, %1, %2;" : "=r"(d) : "f"((float)hi), "f"((float)lo)); return d;
}
__device__ __forceinline__ uint32_t rope2(uint32_t x, uint32_t c, uint32_t y, uint32_t s, uint32_t sg) {
    return bfma(bmul(y, s), sg, bmul(x, c));
}
__device__ __forceinline__ void mma_bf16(float (&c)[4], uint32_t a0, uint32_t a1, uint32_t a2, uint32_t a3,
                                         uint32_t b0, uint32_t b1) {
    asm("mma.sync.aligned.m16n8k16.row.col.f32.bf16.bf16.f32 {%0,%1,%2,%3}, {%4,%5,%6,%7}, {%8,%9}, {%0,%1,%2,%3};"
        : "+f"(c[0]), "+f"(c[1]), "+f"(c[2]), "+f"(c[3])
        : "r"(a0), "r"(a1), "r"(a2), "r"(a3), "r"(b0), "r"(b1));
}
__device__ __forceinline__ uint32_t nz(float x) {
    const uint32_t u = __float_as_uint(x);
    return u == 0u ? 0x80000000u : u;
}

#define TS(i)
#define TS_ONCE(i)

#define NO_COMPUTE(x) x
struct Claim { int head, tile0, ntiles, piece; };

__device__ __forceinline__ Claim decode_claim(int c) {
    Claim cl;
    if (c < C_S) {
        cl.head = c / NM; cl.piece = c - cl.head * NM; cl.tile0 = cl.head * TPH + cl.piece * MAINP;
        cl.ntiles = cl.piece < NM - 1 ? MAINP : TPH - (NM - 1) * MAINP - semi_size(cl.head) - fin_size(cl.head);
    } else {
        cl.head = (c - C_S) % NHEAD; cl.piece = NM;
        cl.ntiles = fin_size(cl.head); cl.tile0 = (cl.head + 1) * TPH - cl.ntiles;
        if (c < C_F) { cl.ntiles = semi_size(cl.head); cl.tile0 -= cl.ntiles; }
    }
    return cl;
}

struct Params {
    const __nv_bfloat16* q; const int* qk; const __nv_bfloat16* ks; const __nv_bfloat16* kz;
    const int* qv; const __nv_bfloat16* vs; const __nv_bfloat16* vz;
    const __nv_bfloat16* qcos; const __nv_bfloat16* qsin; const __nv_bfloat16* kcos; const __nv_bfloat16* ksin;
    __nv_bfloat16* out;
};

constexpr float NEG = -3.0e38f;
constexpr float LOG2E = 1.4426950408889634f;
constexpr int F_FIRST = 256, F_LAST = 512, F_SEMI = 1024, F_FIN = 2048, F_SEGEND = 4096, F_END = 8192;

__global__ void __launch_bounds__(NWARPS * 32, 1)
kv_rope_decode_kernel(const Params p) {
    extern __shared__ __align__(128) unsigned char smem[];
    if (threadIdx.x < 32 && elect_one()) {
        l2_prefetch(p.kcos + (blockIdx.x % (TPH / 2)) * (2 * TR * D), 2 * CBYTES);
        l2_prefetch(p.ksin + (blockIdx.x % (TPH / 2)) * (2 * TR * D), 2 * CBYTES);
        uint64_t pol;
        asm volatile("createpolicy.fractional.L2::evict_first.b64 %0, 1.0;" : "=l"(pol));
        const int h = blockIdx.x / NM;
        l2_prefetch(p.qk + (size_t)(h * TPH + (blockIdx.x - h * NM) * MAINP) * (TR * D), CFG_PF0 * KBYTES, pol);
        TS(5);
    }
    const int w = __shfl_sync(0xffffffffu, threadIdx.x >> 5, 0), lane = threadIdx.x & 31;
    const uint32_t sb = smem_u32(smem);
    const uint32_t bar = sb + OFF_BAR;

    if (w < 8 && elect_one()) {
        const uint32_t cnt = w == 5 ? 4 : w == 6 ? NKW + NVW + 1 : w == 7 ? NVW : 1;
#pragma unroll
        for (int i = 0; i < 16; i++) mbar_init(bar + w * 128 + i * 8, cnt);
        asm volatile("fence.mbarrier_init.release.cluster;" ::: "memory");
    }
    __syncthreads();

    if (w == W_V || w == W_V + 1) {
        const int v = w - W_V, g = lane >> 3, l = lane & 7;
        const uint32_t oV = sb + OFF_V + g * (2 * D * 4) + v * 384 + l * 16;
        const bool up = lane & 16, up2 = lane & 8;
        float acc[12];
#pragma unroll
        for (int i = 0; i < 12; i++) acc[i] = 0.f;
        int vslot = 0, seg = 0, b = 0;
        uint32_t vph = 0;
        for (int batch = 0;; batch++) {
            const uint32_t s = sb + OFF_SEG + (seg % NSEG) * SEG_BYTES, sbar = bar + (seg % NSEG) * 8;
            mbar_wait(bar + B_PR + (batch % NBAT) * 8, (batch / NBAT) & 1);
            const int4 bd = lds128(s + S_BD + b * 16);
            if (bd.y & F_END) break;
            TS(3);
            const float alpha = __int_as_float(bd.z);
            if (alpha != 1.0f) {
#pragma unroll
                for (int i = 0; i < 12; i++) acc[i] *= alpha;
            }
            const int n = bd.y & 255;
            int4 cf;
            uint32_t lse;
#pragma unroll 1
            for (int i = 0; i < n; i++) {
                const uint2 pv = lds64(s + S_LG + (b * 32 + i * TR + 2 * g) * 4);
                if (i == n - 1 && (bd.y & F_LAST)) {
                    mbar_wait(sbar + B_FC, (seg / NSEG) & 1);
                    cf = lds128(s + S_G + (v * 32 + lane) * 16);
                    lse = lds32(s + S_LSE);
                }
                const float pv0 = __uint_as_float(pv.x), pv1 = __uint_as_float(pv.y);
                const uint32_t t = oV + vslot * KBYTES;
                TS(4);
                mbar_wait(bar + B_FV + vslot * 8, vph);
                TS_ONCE(1); TS(5);
#pragma unroll
                for (int j = 0; j < NO_COMPUTE(3); j++) {
                    const int4 x0 = lds128(t + j * 128);
                    const int4 x1 = lds128(t + 768 + j * 128);
                    acc[j * 4 + 0] = fmaf(pv1, (float)x1.x, fmaf(pv0, (float)x0.x, acc[j * 4 + 0]));
                    acc[j * 4 + 1] = fmaf(pv1, (float)x1.y, fmaf(pv0, (float)x0.y, acc[j * 4 + 1]));
                    acc[j * 4 + 2] = fmaf(pv1, (float)x1.z, fmaf(pv0, (float)x0.z, acc[j * 4 + 2]));
                    acc[j * 4 + 3] = fmaf(pv1, (float)x1.w, fmaf(pv0, (float)x0.w, acc[j * 4 + 3]));
                }
                __syncwarp();
                if (lane == 0) mbar_arrive(bar + B_EV + vslot * 8);
                TS_ONCE(2);
                if (++vslot == NV) { vslot = 0; vph ^= 1; }
            }
            if (bd.y & F_LAST) {
                const float c0[3] = {__int_as_float(cf.x), __int_as_float(cf.y), __int_as_float(cf.z)};
                float o[3];
#pragma unroll
                for (int j = 0; j < 3; j++) {
                    const float u0 = (up ? acc[j * 4 + 2] : acc[j * 4 + 0]) + __shfl_xor_sync(0xffffffffu, up ? acc[j * 4 + 0] : acc[j * 4 + 2], 16);
                    const float u1 = (up ? acc[j * 4 + 3] : acc[j * 4 + 1]) + __shfl_xor_sync(0xffffffffu, up ? acc[j * 4 + 1] : acc[j * 4 + 3], 16);
                    o[j] = fmaf((up2 ? u1 : u0) + __shfl_xor_sync(0xffffffffu, up2 ? u0 : u1, 8), __int_as_float(cf.w), c0[j]);
                }
                if (bd.y & F_FIN) {
                    __nv_bfloat16* op = p.out + bd.x * D + (v * 96 + l * 4 + (up ? 2 : 0) + (up2 ? 1 : 0));
#pragma unroll
                    for (int j = 0; j < 3; j++) op[j * 32] = __float2bfloat16_rn(o[j]);
                } else {
                    asm volatile("st.relaxed.gpu.global.v4.u32 [%0], {%1,%2,%3,%4};"
                                 ::"l"(g_mail + bd.x * 64 + (v * 32 + lane)),
                                   "r"(nz(o[0])), "r"(nz(o[1])), "r"(nz(o[2])), "r"(lse) : "memory");
                }
#pragma unroll
                for (int i = 0; i < 12; i++) acc[i] = 0.f;
            }
            b++;
            if (bd.y & F_SEGEND) {
                __syncwarp();
                if (lane == 0) mbar_arrive(sbar + B_SE);
                seg++; b = 0;
            }
            TS(6);
        }
    } else if (w == W_S) {
        float m = NEG, lsum = 0.f, corr = 0.f;
        int batch = 0;
        for (int seg = 0;; seg++) {
            const uint32_t s = sb + OFF_SEG + (seg % NSEG) * SEG_BYTES, sbar = bar + (seg % NSEG) * 8;
            const uint32_t sph = (seg / NSEG) & 1;
            mbar_wait(sbar + B_HDR, sph);
            const int4 desc = lds128(s + S_DESC);
            if (desc.y & F_END) {
                if (lane == 0) {
                    sts128(s + S_BD, 0, F_END, 0, 0);
                    mbar_arrive(bar + B_PR + (batch % NBAT) * 8);
                }
                break;
            }
            if (desc.y & F_FIRST) { m = NEG; lsum = 0.f; corr = 0.f; }
            const int index = (desc.y & F_FIN) ? desc.x : desc.x * (NM + 1) + desc.z;
            int b = 0;
            for (int left = desc.y & 255; left > 0; left -= 4, b++, batch++) {
                const bool valid = lane < left * TR;
                const float vs = bf_lo(lds16(s + S_SC + 2 * SCB + (b * 32 + lane) * 2));
                const float vz = bf_lo(lds16(s + S_SC + 3 * SCB + (b * 32 + lane) * 2));
                mbar_wait(bar + B_LG + (batch % NBAT) * 8, (batch / NBAT) & 1);
                const float sv = __uint_as_float(lds32(s + S_LG + (b * 32 + lane) * 4));
                const int4 tm = lds128(s + S_TM + b * 16);
                float mn = fmaxf(m, __int_as_float(tm.x));
                if (left > 1) mn = fmaxf(mn, __int_as_float(tm.y));
                if (left > 2) mn = fmaxf(mn, __int_as_float(tm.z));
                if (left > 3) mn = fmaxf(mn, __int_as_float(tm.w));
                const float alpha = ex2(m - mn), pr = ex2(sv - mn), pv = pr * vs;
                m = mn;
                sts32(s + S_LG + (b * 32 + lane) * 4, pv);
                if (lane == 0)
                    sts128(s + S_BD + b * 16, index, left > 4 ? 4 : (left | F_SEGEND | (desc.y & (F_LAST | F_FIN))),
                           __float_as_uint(alpha), 0);
                __syncwarp();
                if (lane == 0) mbar_arrive(bar + B_PR + (batch % NBAT) * 8);
                lsum = fmaf(lsum, alpha, valid ? pr : 0.f);
                corr = fmaf(corr, alpha, valid ? pv * vz : 0.f);
                TS(3);
            }
            float L = lsum, C = corr;
            if (desc.y & F_LAST) {
#pragma unroll
                for (int o = 16; o > 0; o >>= 1) {
                    L += __shfl_xor_sync(0xffffffffu, L, o);
                    C += __shfl_xor_sync(0xffffffffu, C, o);
                }
            }
            mbar_wait(sbar + B_GD, sph);
            if (desc.y & F_LAST) {
                int4 g0 = make_int4(0, 0, 0, 0xff7fffff), g1 = g0;
                if (desc.y & (F_SEMI | F_FIN)) {
                    g0 = lds128(s + S_G + lane * 16);
                    g1 = lds128(s + S_G + (32 + lane) * 16);
                }
                const float M = fmaxf(m, __int_as_float(g0.w));
                const float e = ex2(m - M), a = ex2(__int_as_float(g0.w) - M);
                const float W = fmaf(L, e, a), inv = 1.0f / W;
                const float c1 = e * inv, ca = a * inv, cc = -C * c1;
                sts128(s + S_G + lane * 16, __float_as_uint(fmaf(__int_as_float(g0.x), ca, cc)),
                       __float_as_uint(fmaf(__int_as_float(g0.y), ca, cc)),
                       __float_as_uint(fmaf(__int_as_float(g0.z), ca, cc)), __float_as_uint(c1));
                sts128(s + S_G + (32 + lane) * 16, __float_as_uint(fmaf(__int_as_float(g1.x), ca, cc)),
                       __float_as_uint(fmaf(__int_as_float(g1.y), ca, cc)),
                       __float_as_uint(fmaf(__int_as_float(g1.z), ca, cc)), __float_as_uint(c1));
                if (lane == 0) sts32(s + S_LSE, __uint_as_float(nz(M + __log2f(W))));
            }
            __syncwarp();
            if (lane == 0) { mbar_arrive(sbar + B_FC); mbar_arrive(sbar + B_SE); }
            TS(4);
        }
    } else if (w == W_G0 || w == W_G1) {
        for (int seg = w == W_G1;; seg += NGW) {
            const uint32_t s = sb + OFF_SEG + (seg % NSEG) * SEG_BYTES, sbar = bar + (seg % NSEG) * 8;
            mbar_wait(sbar + B_HDR, (seg / NSEG) & 1);
            const int4 desc = lds128(s + S_DESC);
            if (desc.y & F_END) break;
            TS(1);
            if (desc.y & (F_SEMI | F_FIN)) {
                const int cnt = (desc.y & F_FIN) ? 1 : NM;
                uint4* mail = g_mail + (desc.x * (NM + 1) + ((desc.y & F_FIN) ? NM : 0)) * 64 + lane;
                float M = NEG, W = 0.f, O[6] = {0.f, 0.f, 0.f, 0.f, 0.f, 0.f};
#pragma unroll 1
                for (int i0 = 0; i0 < cnt; i0 += 4, mail += 4 * 64) {
                    uint4 pk[8];
                    bool ready;
                    int it = 0;
                    do {
                        ready = true;
#pragma unroll
                        for (int i = 0; i < 8; i++) {
                            pk[i] = make_uint4(1u, 1u, 1u, 0xff7fffffu);
                            if (i0 + (i >> 1) < cnt)
                                asm volatile("ld.relaxed.gpu.global.v4.u32 {%0,%1,%2,%3}, [%4];"
                                             : "=r"(pk[i].x), "=r"(pk[i].y), "=r"(pk[i].z), "=r"(pk[i].w)
                                             : "l"(mail + i * 32) : "memory");
                        }
#pragma unroll
                        for (int i = 0; i < 8; i++) ready = ready && pk[i].x && pk[i].y && pk[i].z && pk[i].w;
                        if (++it > (1 << 22)) __trap();
                    } while (!ready);
#pragma unroll
                    for (int i = 0; i < 8; i++)
                        if (i0 + (i >> 1) < cnt) mail[i * 32] = make_uint4(0u, 0u, 0u, 0u);
                    float Mn = M;
#pragma unroll
                    for (int i = 0; i < 8; i += 2) Mn = fmaxf(Mn, __uint_as_float(pk[i].w));
                    const float a = ex2(M - Mn);
                    M = Mn; W *= a;
#pragma unroll
                    for (int i = 0; i < 6; i++) O[i] *= a;
#pragma unroll
                    for (int i = 0; i < 8; i += 2) {
                        const float e = ex2(__uint_as_float(pk[i].w) - M);
                        W += e;
                        O[0] = fmaf(e, __uint_as_float(pk[i].x), O[0]);
                        O[1] = fmaf(e, __uint_as_float(pk[i].y), O[1]);
                        O[2] = fmaf(e, __uint_as_float(pk[i].z), O[2]);
                        O[3] = fmaf(e, __uint_as_float(pk[i + 1].x), O[3]);
                        O[4] = fmaf(e, __uint_as_float(pk[i + 1].y), O[4]);
                        O[5] = fmaf(e, __uint_as_float(pk[i + 1].z), O[5]);
                    }
                }
                const float inv = 1.0f / W, lse = M + __log2f(W);
#pragma unroll
                for (int k = 0; k < 2; k++)
                    sts128(s + S_G + (k * 32 + lane) * 16, __float_as_uint(O[3 * k] * inv), __float_as_uint(O[3 * k + 1] * inv),
                           __float_as_uint(O[3 * k + 2] * inv), __float_as_uint(lse));
            }
            __syncwarp();
            if (lane == 0) mbar_arrive(sbar + B_GD);
            TS(2);
        }
    } else if ((w & 6) == 0) {
        const int g = lane >> 3, l = lane & 7, godd = g & 1;
        const uint32_t sgA = godd ? 0x3f803f80u : 0xbf80bf80u, sgB = sgA ^ 0x80008000u;
        uint2 qc[6], qs[6];
#pragma unroll
        for (int j = 0; j < 6; j++) {
            const int blk = (j + 3 * godd) % 6;
            qc[j] = *reinterpret_cast<const uint2*>(p.qcos + blk * 32 + l * 4);
            qs[j] = *reinterpret_cast<const uint2*>(p.qsin + blk * 32 + l * 4);
        }
        const uint32_t oKA = sb + g * (2 * D * 4) + l * 16 + godd * 384, oKB = oKA - godd * 768 + 384;
        const uint32_t oCA = sb + T_C + g * (2 * D * 2) + l * 8 + godd * 192, oCB = oCA - godd * 384 + 192;
        uint2 qr[6];
        int kslot = w < 2 ? w : w - 6, j = kslot, batch0 = 0;
        uint32_t kph = 0;
        for (int seg = 0;; seg++) {
            const uint32_t s = sb + OFF_SEG + (seg % NSEG) * SEG_BYTES, sbar = bar + (seg % NSEG) * 8;
            mbar_wait(sbar + B_HDR, (seg / NSEG) & 1);
            const uint32_t desc = lds32(s + S_DESC + 4);
            if (desc & F_END) break;
            const int nt = desc & 255;
            if (desc & F_FIRST) {
#pragma unroll
                for (int i = 0; i < 3; i++) {
                    const uint2 a = lds64(s + S_Q + l * 8 + godd * 192 + i * 64);
                    const uint2 b = lds64(s + S_Q + l * 8 - godd * 192 + 192 + i * 64);
                    qr[i].x = rope2(a.x, qc[i].x, b.x, qs[i].x, sgA);
                    qr[i].y = rope2(a.y, qc[i].y, b.y, qs[i].y, sgA);
                    qr[i + 3].x = rope2(b.x, qc[i + 3].x, a.x, qs[i + 3].x, sgB);
                    qr[i + 3].y = rope2(b.y, qc[i + 3].y, a.y, qs[i + 3].y, sgB);
                }
            }
            for (; j < nt; j += NKW) {
                const uint32_t t = kslot * KSLOT;
                const uint32_t sc = s + S_SC + j * (TR * 2) + g * 4;
                const uint32_t sks = lds32(sc), skz = lds32(sc + SCB);
                const uint32_t ks2[2] = {__byte_perm(sks, 0, 0x1010), __byte_perm(sks, 0, 0x3232)};
                const uint32_t kz2[2] = {__byte_perm(skz, 0, 0x1010), __byte_perm(skz, 0, 0x3232)};
                mbar_wait(bar + B_FK + kslot * 8, kph);
                TS_ONCE(1); TS(3);
                float cA[4] = {0.f, 0.f, 0.f, 0.f}, cB[4] = {0.f, 0.f, 0.f, 0.f};
#pragma unroll
                for (int jj = 0; jj < NO_COMPUTE(3); jj++) {
                    uint2 ra[2], rb[2];
#pragma unroll
                    for (int ps = 0; ps < 2; ps++) {
                        const int4 xa = lds128(t + oKA + ps * 768 + jj * 128);
                        const int4 xb = lds128(t + oKB + ps * 768 + jj * 128);
                        const uint2 ca = lds64(t + oCA + ps * 384 + jj * 64);
                        const uint2 cb = lds64(t + oCB + ps * 384 + jj * 64);
                        const uint2 sa = lds64(t + oCA + CBYTES + ps * 384 + jj * 64);
                        const uint2 sbv = lds64(t + oCB + CBYTES + ps * 384 + jj * 64);
                        const uint32_t a0 = bmul(bsub(i2bf2(xa.x, xa.y), kz2[ps]), ks2[ps]);
                        const uint32_t a1 = bmul(bsub(i2bf2(xa.z, xa.w), kz2[ps]), ks2[ps]);
                        const uint32_t b0 = bmul(bsub(i2bf2(xb.x, xb.y), kz2[ps]), ks2[ps]);
                        const uint32_t b1 = bmul(bsub(i2bf2(xb.z, xb.w), kz2[ps]), ks2[ps]);
                        ra[ps].x = rope2(a0, ca.x, b0, sa.x, sgA);
                        ra[ps].y = rope2(a1, ca.y, b1, sa.y, sgA);
                        rb[ps].x = rope2(b0, cb.x, a0, sbv.x, sgB);
                        rb[ps].y = rope2(b1, cb.y, a1, sbv.y, sgB);
                    }
                    mma_bf16(cA, ra[0].x, ra[1].x, ra[0].y, ra[1].y, qr[jj].x, qr[jj].y);
                    mma_bf16(cB, rb[0].x, rb[1].x, rb[0].y, rb[1].y, qr[jj + 3].x, qr[jj + 3].y);
                }
                __syncwarp();
                if (lane == 0) mbar_arrive(bar + B_EK + kslot * 8);
                TS_ONCE(2);
                const float d0 = __shfl_sync(0xffffffffu, cA[0] + cB[0], 9 * g) + __shfl_sync(0xffffffffu, cA[1] + cB[1], 9 * g + 4);
                const float d1 = __shfl_sync(0xffffffffu, cA[2] + cB[2], 9 * g) + __shfl_sync(0xffffffffu, cA[3] + cB[3], 9 * g + 4);
                const float s0 = rbf(rbf(d0) * 0.07216878364870322f) * LOG2E;
                const float s1 = rbf(rbf(d1) * 0.07216878364870322f) * LOG2E;
                if (l == 0) sts64(s + S_LG + (j * TR + 2 * g) * 4, s0, s1);
                float tm = fmaxf(s0, s1);
                tm = fmaxf(tm, __shfl_xor_sync(0xffffffffu, tm, 8));
                tm = fmaxf(tm, __shfl_xor_sync(0xffffffffu, tm, 16));
                if (lane == 0) sts32(s + S_TM + j * 4, tm);
                __syncwarp();
                if (lane == 0) mbar_arrive(bar + B_LG + ((batch0 + (j >> 2)) % NBAT) * 8, j == nt - 1 ? 4 - (j & 3) : 1);
                TS(4);
                kslot += NKW;
                if (kslot >= NK) { kslot -= NK; kph ^= 1; }
            }
            j -= nt;
            batch0 += (nt + 3) >> 2;
            __syncwarp();
            if (lane == 0) mbar_arrive(sbar + B_SE);
        }
    } else {
        if (elect_one()) {
            uint64_t pol;
            asm volatile("createpolicy.fractional.L2::evict_first.b64 %0, 1.0;" : "=l"(pol));
            int kslot = 0, vslot = 0, seg = 0;
            uint32_t kph = 1, vph = 1;
            int pend[LEAD];
#pragma unroll
            for (int i = 0; i < LEAD; i++) pend[i] = -1;
            auto push_v = [&](int tile) {
                if (pend[0] >= 0) {
                    const uint32_t b = bar + vslot * 8;
                    mbar_wait(b + B_EV, vph);
                    mbar_expect(b + B_FV, KBYTES);
                    bulk_stream(sb + OFF_V + vslot * KBYTES, p.qv + (size_t)pend[0] * (TR * D), KBYTES, b + B_FV, pol);
                    if (++vslot == NV) { vslot = 0; vph ^= 1; }
                }
#pragma unroll
                for (int i = 0; i + 1 < LEAD; i++) pend[i] = pend[i + 1];
                pend[LEAD - 1] = tile;
            };
            int c = blockIdx.x;
            TS(1);
            while (c < NCLAIM) {
                const Claim cl = decode_claim(c);
                int tile = cl.tile0;
                auto tiles = [&](int cnt) {
#pragma unroll 1
                    for (int j = 0; j < cnt; j++, tile++) {
                        push_v(tile);
                        const uint32_t t = sb + kslot * KSLOT, b = bar + kslot * 8;
                        const int ro = (tile % TPH) * (TR * D);
                        mbar_wait(b + B_EK, kph);
                        mbar_expect(b + B_FK, KSLOT);
                        bulk_stream(t, p.qk + (size_t)tile * (TR * D), KBYTES, b + B_FK, pol);
                        bulk_plain(t + T_C, p.kcos + ro, CBYTES, b + B_FK);
                        bulk_plain(t + T_S, p.ksin + ro, CBYTES, b + B_FK);
                        TS_ONCE(2); TS(3);
                        if (++kslot == NK) { kslot = 0; kph ^= 1; }
                    }
                };
                int nt;
                for (int left = cl.ntiles;; left -= nt) {
                    nt = min(SEGT, left);
                    const bool first = left == cl.ntiles, last = left == nt;
                    const uint32_t s = sb + OFF_SEG + (seg % NSEG) * SEG_BYTES, b = bar + (seg % NSEG) * 8;
                    mbar_wait(b + B_SE, ((seg / NSEG) & 1) ^ 1);
                    sts128(s + S_DESC, cl.head,
                           nt | (first ? F_FIRST : 0) | (last ? F_LAST : 0) | (c >= C_F ? F_FIN : c >= C_S ? F_SEMI : 0),
                           cl.piece, 0);
                    const uint32_t scb = nt * TR * 2;
                    const int r = tile * TR;
                    mbar_expect(b + B_HDR, 4 * scb + (first ? QBYTES : 0));
                    if (first) bulk_stream(s + S_Q, p.q + cl.head * D, QBYTES, b + B_HDR, pol);
                    bulk_stream(s + S_SC, p.ks + r, scb, b + B_HDR, pol);
                    bulk_stream(s + S_SC + SCB, p.kz + r, scb, b + B_HDR, pol);
                    bulk_stream(s + S_SC + 2 * SCB, p.vs + r, scb, b + B_HDR, pol);
                    bulk_stream(s + S_SC + 3 * SCB, p.vz + r, scb, b + B_HDR, pol);
                    seg++;
                    tiles(last ? max(nt - LA, 0) : nt);
                    if (last) break;
                }
                const unsigned nx = atomicInc(&g_queue, NCLAIM - 1);
                tiles(min(nt, LA));
                c = gridDim.x + nx;
            }
            TS(4);
#pragma unroll 1
            for (int i = 0; i < LEAD; i++) push_v(-1);
            TS(5);
#pragma unroll 1
            for (int i = 0; i < NGW; i++, seg++) {
                const uint32_t s = sb + OFF_SEG + (seg % NSEG) * SEG_BYTES, b = bar + (seg % NSEG) * 8;
                mbar_wait(b + B_SE, ((seg / NSEG) & 1) ^ 1);
                sts128(s + S_DESC, 0, F_END, 0, 0);
                mbar_arrive(b + B_HDR);
            }
        }
    }
}

}

extern "C" void kernel_launch(void* const* d_in, const int* in_sizes, int n_in, void* d_out, int out_size) {
    (void)in_sizes; (void)n_in; (void)out_size;
    static int sms = 0;
    if (sms == 0) {
        int dev = 0;
        cudaGetDevice(&dev);
        cudaDeviceGetAttribute(&sms, cudaDevAttrMultiProcessorCount, dev);
        cudaFuncSetAttribute(kv_rope_decode_kernel, cudaFuncAttributeMaxDynamicSharedMemorySize, SMEM_BYTES);
    }
    Params p;
    p.q    = (const __nv_bfloat16*)d_in[0];
    p.qk   = (const int*)d_in[1];
    p.ks   = (const __nv_bfloat16*)d_in[2];
    p.kz   = (const __nv_bfloat16*)d_in[3];
    p.qv   = (const int*)d_in[4];
    p.vs   = (const __nv_bfloat16*)d_in[5];
    p.vz   = (const __nv_bfloat16*)d_in[6];
    p.qcos = (const __nv_bfloat16*)d_in[7];
    p.qsin = (const __nv_bfloat16*)d_in[8];
    p.kcos = (const __nv_bfloat16*)d_in[9];
    p.ksin = (const __nv_bfloat16*)d_in[10];
    p.out  = (__nv_bfloat16*)d_out;
    kv_rope_decode_kernel<<<sms, NWARPS * 32, SMEM_BYTES>>>(p);
}
```

```cpp
#include <cuda_runtime.h>
#include <cuda_bf16.h>
#include <stdint.h>

namespace {

#define PF_WARP
#define CFG_NKW 4
#define CFG_NK 8
#define CFG_NV 4
#define CFG_LEAD 5
#define CFG_MAIN 16
#define CFG_SEMI 0xfdb9
#define CFG_FIN 0x7531
#define CFG_FCMODE 2
#define CFG_LA 3
#define CFG_PF0 3

constexpr int D      = 192;
constexpr int SKV    = 2048;
constexpr int NHEAD  = 256;
constexpr int TR     = 8;
constexpr int TPH    = SKV / TR;
constexpr int NKW    = CFG_NKW;
constexpr int NVW    = 2;
constexpr int NGW    = 2;
constexpr int NK     = CFG_NK;
constexpr int NV     = CFG_NV;
constexpr int LEAD   = CFG_LEAD;
constexpr int NSEG   = 8;
constexpr int SEGT   = 16;
constexpr int NBAT   = 16;
constexpr int W_V = 6, W_PROD = 4, W_G0 = 8, W_S = 5, W_G1 = 9, NWARPS = 10;
#define IS_K(w) ((w >> 2) == 0)
#define K_IDX(w) w

constexpr int NTHREADS = NWARPS * 32 + 32;

constexpr int MAINP  = CFG_MAIN;
constexpr int LA     = CFG_LA;
__host__ __device__ constexpr int semi_size(int h) { return ((CFG_SEMI >> (12 - 4 * (h >> 6))) & 15) + 1; }
__host__ __device__ constexpr int fin_size(int h) { return ((CFG_FIN >> (12 - 4 * (h >> 6))) & 15) + 1; }
constexpr int NM     = (TPH - semi_size(0) - fin_size(0) + MAINP - 1) / MAINP;
constexpr int C_S    = NHEAD * NM, C_F = C_S + NHEAD, NCLAIM = C_F + NHEAD;
constexpr bool sizes_ok(int h) { return h >= NHEAD || (semi_size(h) + fin_size(h) < TPH - (NM - 1) * MAINP && sizes_ok(h + 64)); }
static_assert(sizes_ok(0), "schedule");

constexpr int KBYTES = TR * D * 4;
constexpr int CBYTES = TR * D * 2;
constexpr int QBYTES = D * 2;
constexpr int T_C = KBYTES, T_S = T_C + CBYTES, KSLOT = T_S + CBYTES;
constexpr int SCB = SEGT * TR * 2;
constexpr int S_Q = 0, S_SC = QBYTES, S_DESC = S_SC + 4 * SCB, S_BD = S_DESC + 16, S_TM = S_BD + 4 * 16,
              S_LG = S_TM + SEGT * 4, S_G = S_LG + 2 * SEGT * TR * 4, S_LSE = S_G + 64 * 16,
              SEG_BYTES = (S_LSE + 16 + 127) / 128 * 128;
constexpr int OFF_V = NK * KSLOT, OFF_SEG = OFF_V + NV * KBYTES, OFF_QT = OFF_SEG + NSEG * SEG_BYTES,
              OFF_BAR = OFF_QT + 2 * QBYTES;
constexpr int B_FK = 0, B_EK = 64, B_PR = 128, B_HDR = 256, B_GD = 320, B_FC = 384, B_FV = 448, B_LG = 640,
              B_SE = 768, B_EV = 896;
constexpr int SMEM_BYTES = OFF_BAR + 1024;
static_assert(NK <= 8 && NV <= 8 && NSEG == 8 && NBAT == 16, "barrier layout");
static_assert(SMEM_BYTES <= 232448 && SMEM_BYTES > 232448 / 2, "smem");
static_assert(NSEG % NGW == 0 && NK % NKW == 0 && NKW >= 2 && NKW <= 4 && LEAD >= 1, "cfg");
static_assert(LEAD + NV >= 4 && LEAD + NV < NBAT && LEAD < NSEG, "cfg");

__device__ unsigned int g_queue;
__device__ uint4 g_mail[NHEAD * (NM + 1) * 64];

__device__ __forceinline__ uint32_t smem_u32(const void* p) { return (uint32_t)__cvta_generic_to_shared(p); }
__device__ __forceinline__ bool elect_one() {
    uint32_t pred;
    asm volatile("{\n.reg .pred p;\nelect.sync _|p, 0xffffffff;\nselp.u32 %0, 1, 0, p;\n}" : "=r"(pred));
    return pred;
}
__device__ __forceinline__ void mbar_init(uint32_t bar, uint32_t cnt) {
    asm volatile("mbarrier.init.shared::cta.b64 [%0], %1;" ::"r"(bar), "r"(cnt) : "memory");
}
__device__ __forceinline__ void mbar_expect(uint32_t bar, uint32_t bytes) {
    asm volatile("mbarrier.arrive.expect_tx.shared::cta.b64 _, [%0], %1;" ::"r"(bar), "r"(bytes) : "memory");
}
__device__ __forceinline__ void mbar_arrive(uint32_t bar) {
    asm volatile("mbarrier.arrive.shared::cta.b64 _, [%0];" ::"r"(bar) : "memory");
}
__device__ __forceinline__ void mbar_arrive(uint32_t bar, uint32_t cnt) {
    asm volatile("mbarrier.arrive.shared::cta.b64 _, [%0], %1;" ::"r"(bar), "r"(cnt) : "memory");
}
__device__ __forceinline__ bool mbar_test(uint32_t bar, uint32_t parity) {
    uint32_t ok;
    asm volatile("{\n.reg .pred p;\nmbarrier.test_wait.parity.shared::cta.b64 p, [%1], %2;\nselp.u32 %0, 1, 0, p;\n}"
                 : "=r"(ok) : "r"(bar), "r"(parity) : "memory");
    return ok;
}
__device__ __forceinline__ void mbar_wait(uint32_t bar, uint32_t parity) {
    asm volatile("{\n.reg .pred p;\n.reg .u32 n;\n"
                 "mbarrier.try_wait.parity.shared::cta.b64 p, [%0], %1;\n"
                 "@p bra DONE;\n"
                 "mov.u32 n, 0;\n"
                 "LOOP:\n"
                 "mbarrier.try_wait.parity.shared::cta.b64 p, [%0], %1;\n"
                 "@p bra DONE;\n"
                 "add.u32 n, n, 1;\n"
                 "setp.lt.u32 p, n, 0x400000;\n"
                 "@p bra LOOP;\n"
                 "trap;\n"
                 "DONE:\n}" ::"r"(bar), "r"(parity) : "memory");
}
__device__ __forceinline__ void bulk_stream(uint32_t dst, const void* src, uint32_t bytes, uint32_t bar, uint64_t pol) {
    asm volatile("cp.async.bulk.shared::cluster.global.mbarrier::complete_tx::bytes.L2::cache_hint [%0], [%1], %2, [%3], %4;"
                 ::"r"(dst), "l"(src), "r"(bytes), "r"(bar), "l"(pol) : "memory");
}
__device__ __forceinline__ void bulk_plain(uint32_t dst, const void* src, uint32_t bytes, uint32_t bar) {
    asm volatile("cp.async.bulk.shared::cluster.global.mbarrier::complete_tx::bytes [%0], [%1], %2, [%3];"
                 ::"r"(dst), "l"(src), "r"(bytes), "r"(bar) : "memory");
}
__device__ __forceinline__ void l2_prefetch(const void* src, uint32_t bytes, uint64_t pol) {
    asm volatile("cp.async.bulk.prefetch.L2.global.L2::cache_hint [%0], %1, %2;" ::"l"(src), "r"(bytes), "l"(pol) : "memory");
}
__device__ __forceinline__ void l2_prefetch(const void* src, uint32_t bytes) {
    asm volatile("cp.async.bulk.prefetch.L2.global [%0], %1;" ::"l"(src), "r"(bytes) : "memory");
}
__device__ __forceinline__ int4 lds128(uint32_t a) {
    int4 v;
    asm volatile("ld.shared.v4.s32 {%0,%1,%2,%3}, [%4];" : "=r"(v.x), "=r"(v.y), "=r"(v.z), "=r"(v.w) : "r"(a));
    return v;
}
__device__ __forceinline__ uint2 lds64(uint32_t a) {
    uint2 v;
    asm volatile("ld.shared.v2.u32 {%0,%1}, [%2];" : "=r"(v.x), "=r"(v.y) : "r"(a));
    return v;
}
__device__ __forceinline__ uint32_t lds32(uint32_t a) {
    uint32_t v;
    asm volatile("ld.shared.u32 %0, [%1];" : "=r"(v) : "r"(a));
    return v;
}
__device__ __forceinline__ uint32_t lds16(uint32_t a) {
    uint16_t v;
    asm volatile("ld.shared.u16 %0, [%1];" : "=h"(v) : "r"(a));
    return v;
}
__device__ __forceinline__ void sts32(uint32_t a, float x) {
    asm volatile("st.shared.f32 [%0], %1;" ::"r"(a), "f"(x) : "memory");
}
__device__ __forceinline__ void sts128(uint32_t a, uint32_t x, uint32_t y, uint32_t z, uint32_t w) {
    asm volatile("st.shared.v4.u32 [%0], {%1,%2,%3,%4};" ::"r"(a), "r"(x), "r"(y), "r"(z), "r"(w) : "memory");
}
__device__ __forceinline__ void sts64(uint32_t a, float x, float y) {
    asm volatile("st.shared.v2.f32 [%0], {%1,%2};" ::"r"(a), "f"(x), "f"(y) : "memory");
}
__device__ __forceinline__ float bf_lo(uint32_t v) { return __uint_as_float(v << 16); }
__device__ __forceinline__ float bf_hi(uint32_t v) { return __uint_as_float(v & 0xffff0000u); }
__device__ __forceinline__ float rbf(float x) {
    uint32_t d; asm("cvt.rn.bf16x2.f32 %0, %1, %2;" : "=r"(d) : "f"(x), "f"(0.f)); return __uint_as_float(d);
}
__device__ __forceinline__ float rcp(float x) {
    float y;
    asm("rcp.approx.ftz.f32 %0, %1;" : "=f"(y) : "f"(x));
    return y;
}
__device__ __forceinline__ float lg2(float x) {
    float y;
    asm("lg2.approx.ftz.f32 %0, %1;" : "=f"(y) : "f"(x));
    return y;
}
__device__ __forceinline__ float ex2(float x) {
    float y;
    asm("ex2.approx.ftz.f32 %0, %1;" : "=f"(y) : "f"(x));
    return y;
}
__device__ __forceinline__ uint32_t bmul(uint32_t a, uint32_t b) {
    uint32_t d; asm("mul.rn.bf16x2 %0, %1, %2;" : "=r"(d) : "r"(a), "r"(b)); return d;
}
__device__ __forceinline__ uint32_t bsub(uint32_t a, uint32_t b) {
    uint32_t d; asm("sub.rn.bf16x2 %0, %1, %2;" : "=r"(d) : "r"(a), "r"(b)); return d;
}
__device__ __forceinline__ uint32_t bfma(uint32_t a, uint32_t b, uint32_t c) {
    uint32_t d; asm("fma.rn.bf16x2 %0, %1, %2, %3;" : "=r"(d) : "r"(a), "r"(b), "r"(c)); return d;
}
__device__ __forceinline__ uint32_t i2bf2(int lo, int hi) {
    uint32_t d; asm("cvt.rn.bf16x2.f32 %0, %1, %2;" : "=r"(d) : "f"((float)hi), "f"((float)lo)); return d;
}
__device__ __forceinline__ uint32_t rope2(uint32_t x, uint32_t c, uint32_t y, uint32_t s, uint32_t sg) {
    return bfma(bmul(y, s), sg, bmul(x, c));
}
__device__ __forceinline__ void mma_bf16(float (&c)[4], uint32_t a0, uint32_t a1, uint32_t a2, uint32_t a3,
                                         uint32_t b0, uint32_t b1) {
    asm("mma.sync.aligned.m16n8k16.row.col.f32.bf16.bf16.f32 {%0,%1,%2,%3}, {%4,%5,%6,%7}, {%8,%9}, {%0,%1,%2,%3};"
        : "+f"(c[0]), "+f"(c[1]), "+f"(c[2]), "+f"(c[3])
        : "r"(a0), "r"(a1), "r"(a2), "r"(a3), "r"(b0), "r"(b1));
}
__device__ __forceinline__ uint32_t nz(float x) {
    const uint32_t u = __float_as_uint(x);
    return u == 0u ? 0x80000000u : u;
}

#define TS(i)
#define TS_ONCE(i)

#define NO_COMPUTE(x) x
struct Claim { uint32_t head, tile0, piece; int ntiles; };

__device__ __forceinline__ Claim decode_claim(uint32_t c) {
    Claim cl;
    if (c < C_S) {
        cl.head = c / NM; cl.piece = c - cl.head * NM; cl.tile0 = cl.head * TPH + cl.piece * MAINP;
        cl.ntiles = cl.piece < NM - 1 ? MAINP : TPH - (NM - 1) * MAINP - semi_size(cl.head) - fin_size(cl.head);
    } else {
        cl.head = (c - C_S) % NHEAD; cl.piece = NM;
        cl.ntiles = fin_size(cl.head); cl.tile0 = (cl.head + 1) * TPH - cl.ntiles;
        if (c < C_F) { cl.ntiles = semi_size(cl.head); cl.tile0 -= cl.ntiles; }
    }
    return cl;
}

struct Params {
    const int* qk; const __nv_bfloat16* kcos; const __nv_bfloat16* ksin; const int* qv;
    const __nv_bfloat16* ks; const __nv_bfloat16* kz; const __nv_bfloat16* vs; const __nv_bfloat16* vz;
    const __nv_bfloat16* q; const __nv_bfloat16* qcos; const __nv_bfloat16* qsin;
    __nv_bfloat16* out;
};

constexpr float NEG = -3.0e38f;
constexpr float LOG2E = 1.4426950408889634f;
constexpr int F_FIRST = 256, F_LAST = 512, F_SEMI = 1024, F_FIN = 2048, F_SEGEND = 4096, F_END = 8192;

__global__ void __launch_bounds__(NTHREADS, 1)
kv_rope_decode_kernel(const Params p) {
    extern __shared__ __align__(128) unsigned char smem[];
    if (threadIdx.x >= NWARPS * 32 && elect_one()) {
        l2_prefetch(p.kcos + (blockIdx.x % (TPH / 2)) * (2 * TR * D), 2 * CBYTES);
        l2_prefetch(p.ksin + (blockIdx.x % (TPH / 2)) * (2 * TR * D), 2 * CBYTES);
        uint64_t pol;
        asm volatile("createpolicy.fractional.L2::evict_first.b64 %0, 1.0;" : "=l"(pol));
        const int h = blockIdx.x / NM;
        l2_prefetch(p.qk + (size_t)(h * TPH + (blockIdx.x - h * NM) * MAINP) * (TR * D), CFG_PF0 * KBYTES, pol);
    }
    const int w = __shfl_sync(0xffffffffu, threadIdx.x >> 5, 0), lane = threadIdx.x & 31;
    if (w == NWARPS) return;
    const uint32_t sb = smem_u32(smem);
    const uint32_t bar = sb + OFF_BAR;

    if (w < 8 && w != W_PROD && elect_one()) {
        const uint32_t cnt = w == 5 ? 4 : w == 6 ? NKW + NVW + 1 : w == 7 ? NVW : 1;
#pragma unroll
        for (int i = 0; i < 16; i++) mbar_init(bar + w * 128 + i * 8, cnt);
        asm volatile("fence.mbarrier_init.release.cluster;" ::: "memory");
    }
    asm volatile("bar.sync 0, %0;" ::"n"(NWARPS * 32) : "memory");

    if (w == W_V || w == W_V + 1) {
        const int v = w - W_V, g = lane >> 3, l = lane & 7;
        const uint32_t oV = sb + OFF_V + g * (2 * D * 4) + v * 384 + l * 16;
        const bool up = lane & 16, up2 = lane & 8;
        float acc[12];
#pragma unroll
        for (int i = 0; i < 12; i++) acc[i] = 0.f;
        uint32_t vslot = 0, seg = 0, b = 0, vph = 0;
        for (uint32_t batch = 0;; batch++) {
            const uint32_t s = sb + OFF_SEG + (seg % NSEG) * SEG_BYTES, sbar = bar + (seg % NSEG) * 8;
            mbar_wait(bar + B_PR + (batch % NBAT) * 8, (batch / NBAT) & 1);
            const int4 bd = lds128(s + S_BD + b * 16);
            if (bd.y & F_END) break;
            TS(3);
            const float alpha = __int_as_float(bd.z);
            if (alpha != 1.0f) {
#pragma unroll
                for (int i = 0; i < 12; i++) acc[i] *= alpha;
            }
            const int n = bd.y & 255;
            int4 cf;
            uint32_t lse;
            bool got = false;
#pragma unroll 1
            for (int i = 0; i < n; i++) {
                const uint2 pv = lds64(s + S_LG + (b * 32 + i * TR + 2 * g) * 4);
                const float pv0 = __uint_as_float(pv.x), pv1 = __uint_as_float(pv.y);
                const uint32_t t = oV + vslot * KBYTES;
                TS(4);
                mbar_wait(bar + B_FV + vslot * 8, vph);
                TS_ONCE(1); TS(5);
#pragma unroll
                for (int j = 0; j < NO_COMPUTE(3); j++) {
                    const int4 x0 = lds128(t + j * 128);
                    const int4 x1 = lds128(t + 768 + j * 128);
                    acc[j * 4 + 0] = fmaf(pv1, (float)x1.x, fmaf(pv0, (float)x0.x, acc[j * 4 + 0]));
                    acc[j * 4 + 1] = fmaf(pv1, (float)x1.y, fmaf(pv0, (float)x0.y, acc[j * 4 + 1]));
                    acc[j * 4 + 2] = fmaf(pv1, (float)x1.z, fmaf(pv0, (float)x0.z, acc[j * 4 + 2]));
                    acc[j * 4 + 3] = fmaf(pv1, (float)x1.w, fmaf(pv0, (float)x0.w, acc[j * 4 + 3]));
                }
                __syncwarp();
                if (lane == 0) mbar_arrive(bar + B_EV + vslot * 8);
                TS_ONCE(2);
                if (++vslot == NV) { vslot = 0; vph ^= 1; }
            }
            if (bd.y & F_LAST) {
                float o[3];
#pragma unroll
                for (int j = 0; j < 3; j++) {
                    const float u0 = (up ? acc[j * 4 + 2] : acc[j * 4 + 0]) + __shfl_xor_sync(0xffffffffu, up ? acc[j * 4 + 0] : acc[j * 4 + 2], 16);
                    const float u1 = (up ? acc[j * 4 + 3] : acc[j * 4 + 1]) + __shfl_xor_sync(0xffffffffu, up ? acc[j * 4 + 1] : acc[j * 4 + 3], 16);
                    o[j] = (up2 ? u1 : u0) + __shfl_xor_sync(0xffffffffu, up2 ? u0 : u1, 8);
                }
                if (CFG_FCMODE != 0 && !got) {
                    mbar_wait(sbar + B_FC, (seg / NSEG) & 1);
                    cf = lds128(s + S_G + (v * 32 + lane) * 16);
                    lse = lds32(s + S_LSE);
                }
                o[0] = fmaf(o[0], __int_as_float(cf.w), __int_as_float(cf.x));
                o[1] = fmaf(o[1], __int_as_float(cf.w), __int_as_float(cf.y));
                o[2] = fmaf(o[2], __int_as_float(cf.w), __int_as_float(cf.z));
                if (bd.y & F_FIN) {
                    __nv_bfloat16* op = p.out + bd.x * D + (v * 96 + l * 4 + (up ? 2 : 0) + (up2 ? 1 : 0));
#pragma unroll
                    for (int j = 0; j < 3; j++) op[j * 32] = __float2bfloat16_rn(o[j]);
                } else {
                    asm volatile("st.relaxed.gpu.global.v4.u32 [%0], {%1,%2,%3,%4};"
                                 ::"l"(g_mail + bd.x * 64 + (v * 32 + lane)),
                                   "r"(nz(o[0])), "r"(nz(o[1])), "r"(nz(o[2])), "r"(lse) : "memory");
                }
#pragma unroll
                for (int i = 0; i < 12; i++) acc[i] = 0.f;
            }
            b++;
            if (bd.y & F_SEGEND) {
                __syncwarp();
                if (lane == 0) mbar_arrive(sbar + B_SE);
                seg++; b = 0;
            }
            TS(6);
        }
    } else if (w == W_S) {
        float m = NEG, lsum = 0.f, corr = 0.f;
        uint32_t batch = 0;
        for (uint32_t seg = 0;; seg++) {
            const uint32_t s = sb + OFF_SEG + (seg % NSEG) * SEG_BYTES, sbar = bar + (seg % NSEG) * 8;
            const uint32_t sph = (seg / NSEG) & 1;
            mbar_wait(sbar + B_HDR, sph);
            const int4 desc = lds128(s + S_DESC);
            if (desc.y & F_END) {
                if (lane == 0) {
                    sts128(s + S_BD, 0, F_END, 0, 0);
                    mbar_arrive(bar + B_PR + (batch % NBAT) * 8);
                }
                break;
            }
            if (desc.y & F_FIRST) { m = NEG; lsum = 0.f; corr = 0.f; }
            const int index = (desc.y & F_FIN) ? desc.x : desc.x * (NM + 1) + desc.z;
            int b = 0;
            for (int left = desc.y & 255; left > 0; left -= 4, b++, batch++) {
                const bool valid = lane < left * TR;
                const float vs = bf_lo(lds16(s + S_SC + 2 * SCB + (b * 32 + lane) * 2));
                const float vz = bf_lo(lds16(s + S_SC + 3 * SCB + (b * 32 + lane) * 2));
                mbar_wait(bar + B_LG + (batch % NBAT) * 8, (batch / NBAT) & 1);
                const float dot = __uint_as_float(lds32(s + S_LG + (b * 32 + lane) * 4)) +
                                  __uint_as_float(lds32(s + S_LG + SEGT * TR * 4 + (b * 32 + lane) * 4));
                const float sv = rbf(rbf(dot) * 0.07216878364870322f) * LOG2E;
                int key = __float_as_int(fmaxf(m, valid ? sv : m));
                key ^= (key >> 31) & 0x7fffffff;
                key = __reduce_max_sync(0xffffffffu, key);
                const float mn = __int_as_float(key ^ ((key >> 31) & 0x7fffffff));
                const float alpha = ex2(m - mn), pr = ex2(sv - mn), pv = pr * vs;
                m = mn;
                sts32(s + S_LG + (b * 32 + lane) * 4, pv);
                if (lane == 0)
                    sts128(s + S_BD + b * 16, index, left > 4 ? 4 : (left | F_SEGEND | (desc.y & (F_LAST | F_FIN))),
                           __float_as_uint(alpha), 0);
                __syncwarp();
                if (lane == 0) mbar_arrive(bar + B_PR + (batch % NBAT) * 8);
                lsum = fmaf(lsum, alpha, valid ? pr : 0.f);
                corr = fmaf(corr, alpha, valid ? pv * vz : 0.f);
                TS(3);
            }
            float L = lsum, C = corr;
            if (desc.y & F_LAST) {
#pragma unroll
                for (int o = 16; o > 0; o >>= 1) {
                    L += __shfl_xor_sync(0xffffffffu, L, o);
                    C += __shfl_xor_sync(0xffffffffu, C, o);
                }
            }
            mbar_wait(sbar + B_GD, sph);
            if (desc.y & F_LAST) {
                int4 g0 = make_int4(0, 0, 0, 0xff7fffff), g1 = g0;
                if (desc.y & (F_SEMI | F_FIN)) {
                    g0 = lds128(s + S_G + lane * 16);
                    g1 = lds128(s + S_G + (32 + lane) * 16);
                }
                const float M = fmaxf(m, __int_as_float(g0.w));
                const float e = ex2(m - M), a = ex2(__int_as_float(g0.w) - M);
                const float W = fmaf(L, e, a), inv = rcp(W);
                const float c1 = e * inv, ca = a * inv, cc = -C * c1;
                sts128(s + S_G + lane * 16, __float_as_uint(fmaf(__int_as_float(g0.x), ca, cc)),
                       __float_as_uint(fmaf(__int_as_float(g0.y), ca, cc)),
                       __float_as_uint(fmaf(__int_as_float(g0.z), ca, cc)), __float_as_uint(c1));
                sts128(s + S_G + (32 + lane) * 16, __float_as_uint(fmaf(__int_as_float(g1.x), ca, cc)),
                       __float_as_uint(fmaf(__int_as_float(g1.y), ca, cc)),
                       __float_as_uint(fmaf(__int_as_float(g1.z), ca, cc)), __float_as_uint(c1));
                if (lane == 0) sts32(s + S_LSE, __uint_as_float(nz(M + lg2(W))));
            }
            __syncwarp();
            if (lane == 0) { mbar_arrive(sbar + B_FC); mbar_arrive(sbar + B_SE); }
            TS(4);
        }
    } else if (w == W_G0 || w == W_G1) {
        for (uint32_t seg = w == W_G1;; seg += NGW) {
            const uint32_t s = sb + OFF_SEG + (seg % NSEG) * SEG_BYTES, sbar = bar + (seg % NSEG) * 8;
            mbar_wait(sbar + B_HDR, (seg / NSEG) & 1);
            const int4 desc = lds128(s + S_DESC);
            if (desc.y & F_END) break;
            TS(1);
            if (desc.y & (F_SEMI | F_FIN)) {
                const int cnt = (desc.y & F_FIN) ? 1 : NM;
                uint4* mail = g_mail + (desc.x * (NM + 1) + ((desc.y & F_FIN) ? NM : 0)) * 64 + lane;
                float M = NEG, W = 0.f, O[6] = {0.f, 0.f, 0.f, 0.f, 0.f, 0.f};
#pragma unroll 1
                for (int i0 = 0; i0 < cnt; i0 += 4, mail += 4 * 64) {
                    uint4 pk[8];
                    bool ready;
                    int it = 0;
                    do {
                        ready = true;
#pragma unroll
                        for (int i = 0; i < 8; i++) {
                            pk[i] = make_uint4(1u, 1u, 1u, 0xff7fffffu);
                            if (i0 + (i >> 1) < cnt)
                                asm volatile("ld.relaxed.gpu.global.v4.u32 {%0,%1,%2,%3}, [%4];"
                                             : "=r"(pk[i].x), "=r"(pk[i].y), "=r"(pk[i].z), "=r"(pk[i].w)
                                             : "l"(mail + i * 32) : "memory");
                        }
#pragma unroll
                        for (int i = 0; i < 8; i++) ready = ready && pk[i].x && pk[i].y && pk[i].z && pk[i].w;
                        if (++it > (1 << 22)) __trap();
                    } while (!ready);
#pragma unroll
                    for (int i = 0; i < 8; i++)
                        if (i0 + (i >> 1) < cnt) mail[i * 32] = make_uint4(0u, 0u, 0u, 0u);
                    float Mn = M;
#pragma unroll
                    for (int i = 0; i < 8; i += 2) Mn = fmaxf(Mn, __uint_as_float(pk[i].w));
                    const float a = ex2(M - Mn);
                    M = Mn; W *= a;
#pragma unroll
                    for (int i = 0; i < 6; i++) O[i] *= a;
#pragma unroll
                    for (int i = 0; i < 8; i += 2) {
                        const float e = ex2(__uint_as_float(pk[i].w) - M);
                        W += e;
                        O[0] = fmaf(e, __uint_as_float(pk[i].x), O[0]);
                        O[1] = fmaf(e, __uint_as_float(pk[i].y), O[1]);
                        O[2] = fmaf(e, __uint_as_float(pk[i].z), O[2]);
                        O[3] = fmaf(e, __uint_as_float(pk[i + 1].x), O[3]);
                        O[4] = fmaf(e, __uint_as_float(pk[i + 1].y), O[4]);
                        O[5] = fmaf(e, __uint_as_float(pk[i + 1].z), O[5]);
                    }
                }
                const float inv = rcp(W), lse = M + lg2(W);
#pragma unroll
                for (int k = 0; k < 2; k++)
                    sts128(s + S_G + (k * 32 + lane) * 16, __float_as_uint(O[3 * k] * inv), __float_as_uint(O[3 * k + 1] * inv),
                           __float_as_uint(O[3 * k + 2] * inv), __float_as_uint(lse));
            }
            __syncwarp();
            if (lane == 0) mbar_arrive(sbar + B_GD);
            TS(2);
        }
    } else if (IS_K(w)) {
        const int g = lane >> 3, l = lane & 7, godd = g & 1;
        const uint32_t sgA = godd ? 0x3f803f80u : 0xbf80bf80u, sgB = sgA ^ 0x80008000u;
        const uint32_t oKA = sb + g * (2 * D * 4) + l * 16 + godd * 384, oKB = oKA - godd * 768 + 384;
        const uint32_t oCA = sb + T_C + g * (2 * D * 2) + l * 8 + godd * 192, oCB = oCA - godd * 384 + 192;
        uint2 qr[6];
        uint32_t kslot = K_IDX(w), j = kslot, batch0 = 0, kph = 0;
        for (uint32_t seg = 0;; seg++) {
            const uint32_t s = sb + OFF_SEG + (seg % NSEG) * SEG_BYTES, sbar = bar + (seg % NSEG) * 8;
            mbar_wait(sbar + B_HDR, (seg / NSEG) & 1);
            const uint32_t desc = lds32(s + S_DESC + 4);
            if (desc & F_END) break;
            const uint32_t nt = desc & 255;
            if (desc & F_FIRST) {
#pragma unroll
                for (int i = 0; i < 3; i++) {
                    const uint32_t oa = l * 8 + godd * 192 + i * 64, ob = oa + 192 - godd * 384;
                    const uint2 a = lds64(s + S_Q + oa), b = lds64(s + S_Q + ob);
                    const uint2 ca = lds64(sb + OFF_QT + oa), cb = lds64(sb + OFF_QT + ob);
                    const uint2 sa = lds64(sb + OFF_QT + QBYTES + oa), sbv = lds64(sb + OFF_QT + QBYTES + ob);
                    qr[i].x = rope2(a.x, ca.x, b.x, sa.x, sgA);
                    qr[i].y = rope2(a.y, ca.y, b.y, sa.y, sgA);
                    qr[i + 3].x = rope2(b.x, cb.x, a.x, sbv.x, sgB);
                    qr[i + 3].y = rope2(b.y, cb.y, a.y, sbv.y, sgB);
                }
            }
            for (; j < nt; j += NKW) {
                const uint32_t t = kslot * KSLOT;
                const uint32_t sc = s + S_SC + j * (TR * 2) + g * 4;
                const uint32_t sks = lds32(sc), skz = lds32(sc + SCB);
                const uint32_t ks2[2] = {__byte_perm(sks, 0, 0x1010), __byte_perm(sks, 0, 0x3232)};
                const uint32_t kz2[2] = {__byte_perm(skz, 0, 0x1010), __byte_perm(skz, 0, 0x3232)};
                mbar_wait(bar + B_FK + kslot * 8, kph);
                TS_ONCE(1); TS(3);
                float cA[4] = {0.f, 0.f, 0.f, 0.f}, cB[4] = {0.f, 0.f, 0.f, 0.f};
#pragma unroll
                for (int jj = 0; jj < NO_COMPUTE(3); jj++) {
                    uint2 ra[2], rb[2];
#pragma unroll
                    for (int ps = 0; ps < 2; ps++) {
                        const int4 xa = lds128(t + oKA + ps * 768 + jj * 128);
                        const int4 xb = lds128(t + oKB + ps * 768 + jj * 128);
                        const uint2 ca = lds64(t + oCA + ps * 384 + jj * 64);
                        const uint2 cb = lds64(t + oCB + ps * 384 + jj * 64);
                        const uint2 sa = lds64(t + oCA + CBYTES + ps * 384 + jj * 64);
                        const uint2 sbv = lds64(t + oCB + CBYTES + ps * 384 + jj * 64);
                        const uint32_t a0 = bmul(bsub(i2bf2(xa.x, xa.y), kz2[ps]), ks2[ps]);
                        const uint32_t a1 = bmul(bsub(i2bf2(xa.z, xa.w), kz2[ps]), ks2[ps]);
                        const uint32_t b0 = bmul(bsub(i2bf2(xb.x, xb.y), kz2[ps]), ks2[ps]);
                        const uint32_t b1 = bmul(bsub(i2bf2(xb.z, xb.w), kz2[ps]), ks2[ps]);
                        ra[ps].x = rope2(a0, ca.x, b0, sa.x, sgA);
                        ra[ps].y = rope2(a1, ca.y, b1, sa.y, sgA);
                        rb[ps].x = rope2(b0, cb.x, a0, sbv.x, sgB);
                        rb[ps].y = rope2(b1, cb.y, a1, sbv.y, sgB);
                    }
                    mma_bf16(cA, ra[0].x, ra[1].x, ra[0].y, ra[1].y, qr[jj].x, qr[jj].y);
                    mma_bf16(cB, rb[0].x, rb[1].x, rb[0].y, rb[1].y, qr[jj + 3].x, qr[jj + 3].y);
                }
                __syncwarp();
                if (lane == 0) mbar_arrive(bar + B_EK + kslot * 8);
                TS_ONCE(2);
                if ((lane & 3) == g)
                    sts64(s + S_LG + (l >> 2) * (SEGT * TR * 4) + (j * TR + 2 * g) * 4,
                          l < 4 ? cA[0] + cB[0] : cA[1] + cB[1], l < 4 ? cA[2] + cB[2] : cA[3] + cB[3]);
                __syncwarp();
                if (lane == 0) mbar_arrive(bar + B_LG + ((batch0 + (j >> 2)) % NBAT) * 8, j == nt - 1 ? 4 - (j & 3) : 1);
                TS(4);
                kslot += NKW;
                if (kslot >= NK) { kslot -= NK; kph ^= 1; }
            }
            j -= nt;
            batch0 += (nt + 3) >> 2;
            __syncwarp();
            if (lane == 0) mbar_arrive(sbar + B_SE);
        }
    } else {
        if (elect_one()) {
            uint64_t pol;
            asm volatile("createpolicy.fractional.L2::evict_first.b64 %0, 1.0;" : "=l"(pol));
            uint32_t kslot = 0, vslot = 0, seg = 0, kph = 1, vph = 1;
            uint32_t win = NV;
            int pend[LEAD];
#pragma unroll
            for (int i = 0; i < LEAD; i++) pend[i] = -1;
            auto push_v = [&](int tile) {
                if (pend[0] >= 0) {
                    const uint32_t b = bar + vslot * 8;
                    mbar_wait(b + B_EV, vph);
                    mbar_expect(b + B_FV, KBYTES);
                    bulk_stream(sb + OFF_V + vslot * KBYTES, p.qv + (size_t)pend[0] * (TR * D), KBYTES, b + B_FV, pol);
                    if (++vslot == NV) { vslot = 0; vph ^= 1; }
                }
#pragma unroll
                for (int i = 0; i + 1 < LEAD; i++) pend[i] = pend[i + 1];
                pend[LEAD - 1] = tile;
            };
            asm volatile("mbarrier.expect_tx.shared::cta.b64 [%0], %1;" ::"r"(bar + B_HDR), "r"(2 * QBYTES) : "memory");
            bulk_plain(sb + OFF_QT, p.qcos, QBYTES, bar + B_HDR);
            bulk_plain(sb + OFF_QT + QBYTES, p.qsin, QBYTES, bar + B_HDR);
            uint32_t c = blockIdx.x;
            TS(1);
            while (c < NCLAIM) {
                const Claim cl = decode_claim(c);
                uint32_t tile = cl.tile0;
                auto tiles = [&](int cnt) {
#pragma unroll 1
                    for (int j = 0; j < cnt; j++, tile++) {
                        push_v(tile);
                        const uint32_t t = sb + kslot * KSLOT, b = bar + kslot * 8;
                        const uint32_t ro = (tile % TPH) * (TR * D);
                        mbar_wait(b + B_EK, kph);
                        mbar_expect(b + B_FK, KSLOT);
                        bulk_stream(t, p.qk + (size_t)tile * (TR * D), KBYTES, b + B_FK, pol);
                        bulk_plain(t + T_C, p.kcos + ro, CBYTES, b + B_FK);
                        bulk_plain(t + T_S, p.ksin + ro, CBYTES, b + B_FK);
                        TS_ONCE(2); TS(3);
                        if (++kslot == NK) { kslot = 0; kph ^= 1; }
                    }
                };
                int nt;
                for (int left = cl.ntiles;; left -= nt) {
                    nt = min(SEGT, left);
                    const bool first = left == cl.ntiles, last = left == nt;
                    const uint32_t s = sb + OFF_SEG + (seg % NSEG) * SEG_BYTES, b = bar + (seg % NSEG) * 8;
                    mbar_wait(b + B_SE, ((seg / NSEG) & 1) ^ 1);
                    sts128(s + S_DESC, cl.head,
                           nt | (first ? F_FIRST : 0) | (last ? F_LAST : 0) | (c >= C_F ? F_FIN : c >= C_S ? F_SEMI : 0),
                           cl.piece, 0);
                    const uint32_t scb = nt * TR * 2;
                    const uint32_t r = tile * TR;
                    mbar_expect(b + B_HDR, 4 * scb + (first ? QBYTES : 0));
                    if (first) bulk_stream(s + S_Q, p.q + cl.head * D, QBYTES, b + B_HDR, pol);
                    bulk_stream(s + S_SC, p.ks + r, scb, b + B_HDR, pol);
                    bulk_stream(s + S_SC + SCB, p.kz + r, scb, b + B_HDR, pol);
                    bulk_stream(s + S_SC + 2 * SCB, p.vs + r, scb, b + B_HDR, pol);
                    bulk_stream(s + S_SC + 3 * SCB, p.vz + r, scb, b + B_HDR, pol);
                    seg++;
                    tiles(last ? max(nt - LA, 0) : nt);
                    if (last) break;
                }
                const unsigned nx = atomicInc(&g_queue, NCLAIM - 1);
                tiles(min(nt, LA));
                c = gridDim.x + nx;
            }
            TS(4);
#pragma unroll 1
            for (int i = 0; i < LEAD; i++) push_v(-1);
            TS(5);
#pragma unroll 1
            for (int i = 0; i < NGW; i++, seg++) {
                const uint32_t s = sb + OFF_SEG + (seg % NSEG) * SEG_BYTES, b = bar + (seg % NSEG) * 8;
                mbar_wait(b + B_SE, ((seg / NSEG) & 1) ^ 1);
                sts128(s + S_DESC, 0, F_END, 0, 0);
                mbar_arrive(b + B_HDR);
            }
        }
    }
}

}

extern "C" void kernel_launch(void* const* d_in, const int* in_sizes, int n_in, void* d_out, int out_size) {
    (void)in_sizes; (void)n_in; (void)out_size;
    static int sms = 0;
    if (sms == 0) {
        int dev = 0;
        cudaGetDevice(&dev);
        cudaDeviceGetAttribute(&sms, cudaDevAttrMultiProcessorCount, dev);
        cudaFuncSetAttribute(kv_rope_decode_kernel, cudaFuncAttributeMaxDynamicSharedMemorySize, SMEM_BYTES);
    }
    Params p;
    p.q    = (const __nv_bfloat16*)d_in[0];
    p.qk   = (const int*)d_in[1];
    p.ks   = (const __nv_bfloat16*)d_in[2];
    p.kz   = (const __nv_bfloat16*)d_in[3];
    p.qv   = (const int*)d_in[4];
    p.vs   = (const __nv_bfloat16*)d_in[5];
    p.vz   = (const __nv_bfloat16*)d_in[6];
    p.qcos = (const __nv_bfloat16*)d_in[7];
    p.qsin = (const __nv_bfloat16*)d_in[8];
    p.kcos = (const __nv_bfloat16*)d_in[9];
    p.ksin = (const __nv_bfloat16*)d_in[10];
    p.out  = (__nv_bfloat16*)d_out;
    kv_rope_decode_kernel<<<sms, NTHREADS, SMEM_BYTES>>>(p);
}
```

```cpp
#include <cuda_runtime.h>
#include <cuda_bf16.h>
#include <stdint.h>

namespace {

#define CFG_NKW 4
#define CFG_NK 8
#define CFG_NV 4
#define CFG_LEAD 5
#define CFG_MAIN 16
#define CFG_SEMI 0xfdb9
#define CFG_FIN 0x7531
#define CFG_GSH 1
#define CFG_LA 3
#define CFG_PF0 3

constexpr int D      = 192;
constexpr int SKV    = 2048;
constexpr int NHEAD  = 256;
constexpr int TR     = 8;
constexpr int TPH    = SKV / TR;
constexpr int NKW    = CFG_NKW;
constexpr int NVW    = 2;
constexpr int NGW    = 2;
constexpr int NK     = CFG_NK;
constexpr int NV     = CFG_NV;
constexpr int LEAD   = CFG_LEAD;
constexpr int NSEG   = 8;
constexpr int SEGT   = 16;
constexpr int NBAT   = 16;
constexpr int W_V = 6, W_PROD = 4, W_G0 = 8, W_S = 5, W_G1 = 9, NWARPS = 10;
#define IS_K(w) ((w >> 2) == 0)
#define K_IDX(w) w

constexpr int NTHREADS = NWARPS * 32 + 32;

constexpr int MAINP  = CFG_MAIN;
constexpr int GSH    = CFG_GSH;
constexpr int LA     = CFG_LA;
__host__ __device__ constexpr int semi_size(int h) { return ((CFG_SEMI >> (12 - 4 * (h >> 6))) & 15) + 1; }
__host__ __device__ constexpr int fin_size(int h) { return ((CFG_FIN >> (12 - 4 * (h >> 6))) & 15) + 1; }
constexpr int NM     = (TPH - semi_size(0) - fin_size(0) + MAINP - 1) / MAINP;
constexpr int C_S    = NHEAD * NM, C_F = C_S + NHEAD, NCLAIM = C_F + NHEAD;
constexpr bool sizes_ok(int h) { return h >= NHEAD || (semi_size(h) + fin_size(h) < TPH - (NM - 1) * MAINP && sizes_ok(h + 64)); }
static_assert(sizes_ok(0), "schedule");

constexpr int KBYTES = TR * D * 4;
constexpr int CBYTES = TR * D * 2;
constexpr int QBYTES = D * 2;
constexpr int T_C = KBYTES, T_S = T_C + CBYTES, KSLOT = T_S + CBYTES;
constexpr int SCB = SEGT * TR * 2 << GSH;
static_assert(GSH == 0 || MAINP == SEGT, "interleaved pieces are single segments");
constexpr int S_Q = 0, S_SC = QBYTES, S_DESC = S_SC + 4 * SCB, S_BD = S_DESC + 16,
              S_LG = S_BD + 4 * 16, S_G = S_LG + 2 * SEGT * TR * 4, S_LSE = S_G + 64 * 16,
              SEG_BYTES = (S_LSE + 16 + 127) / 128 * 128;
constexpr int OFF_V = NK * KSLOT, OFF_SEG = OFF_V + NV * KBYTES, OFF_QT = OFF_SEG + NSEG * SEG_BYTES,
              OFF_BAR = OFF_QT + 2 * QBYTES;
constexpr int B_FK = 0, B_EK = 64, B_PR = 128, B_HDR = 256, B_GD = 320, B_FC = 384, B_FV = 448, B_LG = 640,
              B_SE = 768, B_EV = 896;
constexpr int SMEM_BYTES = OFF_BAR + 1024;
static_assert(NK <= 8 && NV <= 8 && NSEG == 8 && NBAT == 16, "barrier layout");
static_assert(SMEM_BYTES <= 232448 && SMEM_BYTES > 232448 / 2, "smem");
static_assert(NSEG % NGW == 0 && NK % NKW == 0 && NKW >= 2 && NKW <= 4 && LEAD >= 1, "cfg");
static_assert(LEAD + NV >= 4 && LEAD + NV < NBAT && LEAD < NSEG, "cfg");

__device__ unsigned int g_queue;
__device__ uint4 g_mail[NHEAD * (NM + 1) * 64];

__device__ __forceinline__ uint32_t smem_u32(const void* p) { return (uint32_t)__cvta_generic_to_shared(p); }
__device__ __forceinline__ bool elect_one() {
    uint32_t pred;
    asm volatile("{\n.reg .pred p;\nelect.sync _|p, 0xffffffff;\nselp.u32 %0, 1, 0, p;\n}" : "=r"(pred));
    return pred;
}
__device__ __forceinline__ void mbar_init(uint32_t bar, uint32_t cnt) {
    asm volatile("mbarrier.init.shared::cta.b64 [%0], %1;" ::"r"(bar), "r"(cnt) : "memory");
}
__device__ __forceinline__ void mbar_expect(uint32_t bar, uint32_t bytes) {
    asm volatile("mbarrier.arrive.expect_tx.shared::cta.b64 _, [%0], %1;" ::"r"(bar), "r"(bytes) : "memory");
}
__device__ __forceinline__ void mbar_arrive(uint32_t bar) {
    asm volatile("mbarrier.arrive.shared::cta.b64 _, [%0];" ::"r"(bar) : "memory");
}
__device__ __forceinline__ void mbar_arrive(uint32_t bar, uint32_t cnt) {
    asm volatile("mbarrier.arrive.shared::cta.b64 _, [%0], %1;" ::"r"(bar), "r"(cnt) : "memory");
}
__device__ __forceinline__ void mbar_wait(uint32_t bar, uint32_t parity) {
    asm volatile("{\n.reg .pred p;\n.reg .u32 n;\n"
                 "mbarrier.try_wait.parity.shared::cta.b64 p, [%0], %1;\n"
                 "@p bra DONE;\n"
                 "mov.u32 n, 0;\n"
                 "LOOP:\n"
                 "mbarrier.try_wait.parity.shared::cta.b64 p, [%0], %1;\n"
                 "@p bra DONE;\n"
                 "add.u32 n, n, 1;\n"
                 "setp.lt.u32 p, n, 0x400000;\n"
                 "@p bra LOOP;\n"
                 "trap;\n"
                 "DONE:\n}" ::"r"(bar), "r"(parity) : "memory");
}
__device__ __forceinline__ void bulk_stream(uint32_t dst, const void* src, uint32_t bytes, uint32_t bar, uint64_t pol) {
    asm volatile("cp.async.bulk.shared::cluster.global.mbarrier::complete_tx::bytes.L2::cache_hint [%0], [%1], %2, [%3], %4;"
                 ::"r"(dst), "l"(src), "r"(bytes), "r"(bar), "l"(pol) : "memory");
}
__device__ __forceinline__ void bulk_plain(uint32_t dst, const void* src, uint32_t bytes, uint32_t bar) {
    asm volatile("cp.async.bulk.shared::cluster.global.mbarrier::complete_tx::bytes [%0], [%1], %2, [%3];"
                 ::"r"(dst), "l"(src), "r"(bytes), "r"(bar) : "memory");
}
__device__ __forceinline__ void l2_prefetch(const void* src, uint32_t bytes, uint64_t pol) {
    asm volatile("cp.async.bulk.prefetch.L2.global.L2::cache_hint [%0], %1, %2;" ::"l"(src), "r"(bytes), "l"(pol) : "memory");
}
__device__ __forceinline__ void l2_prefetch(const void* src, uint32_t bytes) {
    asm volatile("cp.async.bulk.prefetch.L2.global [%0], %1;" ::"l"(src), "r"(bytes) : "memory");
}
__device__ __forceinline__ int4 lds128(uint32_t a) {
    int4 v;
    asm volatile("ld.shared.v4.s32 {%0,%1,%2,%3}, [%4];" : "=r"(v.x), "=r"(v.y), "=r"(v.z), "=r"(v.w) : "r"(a));
    return v;
}
__device__ __forceinline__ uint2 lds64(uint32_t a) {
    uint2 v;
    asm volatile("ld.shared.v2.u32 {%0,%1}, [%2];" : "=r"(v.x), "=r"(v.y) : "r"(a));
    return v;
}
__device__ __forceinline__ uint32_t lds32(uint32_t a) {
    uint32_t v;
    asm volatile("ld.shared.u32 %0, [%1];" : "=r"(v) : "r"(a));
    return v;
}
__device__ __forceinline__ uint32_t lds16(uint32_t a) {
    uint16_t v;
    asm volatile("ld.shared.u16 %0, [%1];" : "=h"(v) : "r"(a));
    return v;
}
__device__ __forceinline__ void sts32(uint32_t a, float x) {
    asm volatile("st.shared.f32 [%0], %1;" ::"r"(a), "f"(x) : "memory");
}
__device__ __forceinline__ void sts128(uint32_t a, uint32_t x, uint32_t y, uint32_t z, uint32_t w) {
    asm volatile("st.shared.v4.u32 [%0], {%1,%2,%3,%4};" ::"r"(a), "r"(x), "r"(y), "r"(z), "r"(w) : "memory");
}
__device__ __forceinline__ void sts64(uint32_t a, float x, float y) {
    asm volatile("st.shared.v2.f32 [%0], {%1,%2};" ::"r"(a), "f"(x), "f"(y) : "memory");
}
__device__ __forceinline__ float bf_lo(uint32_t v) { return __uint_as_float(v << 16); }
__device__ __forceinline__ float bf_hi(uint32_t v) { return __uint_as_float(v & 0xffff0000u); }
__device__ __forceinline__ float rbf(float x) {
    uint32_t d; asm("cvt.rn.bf16x2.f32 %0, %1, %2;" : "=r"(d) : "f"(x), "f"(0.f)); return __uint_as_float(d);
}
__device__ __forceinline__ float rcp(float x) {
    float y;
    asm("rcp.approx.ftz.f32 %0, %1;" : "=f"(y) : "f"(x));
    return y;
}
__device__ __forceinline__ float lg2(float x) {
    float y;
    asm("lg2.approx.ftz.f32 %0, %1;" : "=f"(y) : "f"(x));
    return y;
}
__device__ __forceinline__ float ex2(float x) {
    float y;
    asm("ex2.approx.ftz.f32 %0, %1;" : "=f"(y) : "f"(x));
    return y;
}
__device__ __forceinline__ uint32_t bmul(uint32_t a, uint32_t b) {
    uint32_t d; asm("mul.rn.bf16x2 %0, %1, %2;" : "=r"(d) : "r"(a), "r"(b)); return d;
}
__device__ __forceinline__ uint32_t bsub(uint32_t a, uint32_t b) {
    uint32_t d; asm("sub.rn.bf16x2 %0, %1, %2;" : "=r"(d) : "r"(a), "r"(b)); return d;
}
__device__ __forceinline__ uint32_t bfma(uint32_t a, uint32_t b, uint32_t c) {
    uint32_t d; asm("fma.rn.bf16x2 %0, %1, %2, %3;" : "=r"(d) : "r"(a), "r"(b), "r"(c)); return d;
}
__device__ __forceinline__ uint32_t i2bf2(int lo, int hi) {
    uint32_t d; asm("cvt.rn.bf16x2.f32 %0, %1, %2;" : "=r"(d) : "f"((float)hi), "f"((float)lo)); return d;
}
__device__ __forceinline__ uint32_t rope2(uint32_t x, uint32_t c, uint32_t y, uint32_t s, uint32_t sg) {
    return bfma(bmul(y, s), sg, bmul(x, c));
}
__device__ __forceinline__ void mma_bf16(float (&c)[4], uint32_t a0, uint32_t a1, uint32_t a2, uint32_t a3,
                                         uint32_t b0, uint32_t b1) {
    asm("mma.sync.aligned.m16n8k16.row.col.f32.bf16.bf16.f32 {%0,%1,%2,%3}, {%4,%5,%6,%7}, {%8,%9}, {%0,%1,%2,%3};"
        : "+f"(c[0]), "+f"(c[1]), "+f"(c[2]), "+f"(c[3])
        : "r"(a0), "r"(a1), "r"(a2), "r"(a3), "r"(b0), "r"(b1));
}
__device__ __forceinline__ uint32_t nz(float x) {
    const uint32_t u = __float_as_uint(x);
    return u == 0u ? 0x80000000u : u;
}

#define TS(i)
#define TS_ONCE(i)

#define NO_COMPUTE(x) x
struct Claim { uint32_t head, tile0, piece, sh, off; int ntiles; };

__device__ __forceinline__ Claim decode_claim(uint32_t c) {
    Claim cl;
    cl.sh = cl.off = 0;
    if (c < C_S) {
        cl.head = c / NM; cl.piece = c - cl.head * NM; cl.tile0 = cl.head * TPH + cl.piece * MAINP;
        cl.ntiles = cl.piece < NM - 1 ? MAINP : TPH - (NM - 1) * MAINP - semi_size(cl.head) - fin_size(cl.head);
        if (cl.piece < ((NM - 1) >> GSH << GSH)) {
            cl.sh = GSH; cl.off = cl.piece & ((1 << GSH) - 1); cl.tile0 -= cl.off * MAINP;
        }
    } else {
        cl.head = (c - C_S) % NHEAD; cl.piece = NM;
        cl.ntiles = fin_size(cl.head); cl.tile0 = (cl.head + 1) * TPH - cl.ntiles;
        if (c < C_F) { cl.ntiles = semi_size(cl.head); cl.tile0 -= cl.ntiles; }
    }
    return cl;
}

struct Params {
    const int* qk; const __nv_bfloat16* kcos; const __nv_bfloat16* ksin; const int* qv;
    const __nv_bfloat16* ks; const __nv_bfloat16* kz; const __nv_bfloat16* vs; const __nv_bfloat16* vz;
    const __nv_bfloat16* q; const __nv_bfloat16* qcos; const __nv_bfloat16* qsin;
    __nv_bfloat16* out;
};

constexpr float NEG = -3.0e38f;
constexpr float LOG2E = 1.4426950408889634f;
constexpr int F_FIRST = 256, F_LAST = 512, F_SEMI = 1024, F_FIN = 2048, F_SEGEND = 4096, F_END = 8192;

__global__ void __launch_bounds__(NTHREADS, 1)
kv_rope_decode_kernel(const Params p) {
    extern __shared__ __align__(128) unsigned char smem[];
        if (threadIdx.x >= NWARPS * 32 && elect_one()) {
        l2_prefetch(p.kcos + (blockIdx.x % (TPH / 2)) * (2 * TR * D), 2 * CBYTES);
        l2_prefetch(p.ksin + (blockIdx.x % (TPH / 2)) * (2 * TR * D), 2 * CBYTES);
        uint64_t pol;
        asm volatile("createpolicy.fractional.L2::evict_first.b64 %0, 1.0;" : "=l"(pol));
        const uint32_t h = blockIdx.x / NM, pc = blockIdx.x - h * NM, off = pc & ((1 << GSH) - 1);
        l2_prefetch(p.qk + (size_t)(h * TPH + (pc - off) * MAINP + off * CFG_PF0) * (TR * D), CFG_PF0 * KBYTES, pol);
    }
    const int w = __shfl_sync(0xffffffffu, threadIdx.x >> 5, 0), lane = threadIdx.x & 31;
    if (w == NWARPS) return;
    const uint32_t sb = smem_u32(smem);
    const uint32_t bar = sb + OFF_BAR;

    if (w < 8 && w != W_PROD && elect_one()) {
        const uint32_t cnt = w == 5 ? 4 : w == 6 ? NKW + NVW : w == 7 ? NVW : 1;
#pragma unroll
        for (int i = 0; i < 16; i++) mbar_init(bar + w * 128 + i * 8, cnt);
        asm volatile("fence.mbarrier_init.release.cluster;" ::: "memory");
    }
    asm volatile("bar.sync 0, %0;" ::"n"(NWARPS * 32) : "memory");

    if (w == W_V || w == W_V + 1) {
        const int v = w - W_V, g = lane >> 3, l = lane & 7;
        const uint32_t oV = sb + OFF_V + g * (2 * D * 4) + v * 384 + l * 16;
        const bool up = lane & 16, up2 = lane & 8;
        float acc[12];
#pragma unroll
        for (int i = 0; i < 12; i++) acc[i] = 0.f;
        uint32_t vslot = 0, seg = 0, b = 0, vph = 0;
        for (uint32_t batch = 0;; batch++) {
            const uint32_t s = sb + OFF_SEG + (seg % NSEG) * SEG_BYTES, sbar = bar + (seg % NSEG) * 8;
            mbar_wait(bar + B_PR + (batch % NBAT) * 8, (batch / NBAT) & 1);
            const int4 bd = lds128(s + S_BD + b * 16);
            if (bd.y & F_END) break;
            TS(3);
            const float alpha = __int_as_float(bd.z);
            if (alpha != 1.0f) {
#pragma unroll
                for (int i = 0; i < 12; i++) acc[i] *= alpha;
            }
            const int n = bd.y & 255;
#pragma unroll 1
            for (int i = 0; i < n; i++) {
                const uint2 pv = lds64(s + S_LG + (b * 32 + i * TR + 2 * g) * 4);
                const float pv0 = __uint_as_float(pv.x), pv1 = __uint_as_float(pv.y);
                const uint32_t t = oV + vslot * KBYTES;
                TS(4);
                mbar_wait(bar + B_FV + vslot * 8, vph);
                TS_ONCE(1); TS(5);
#pragma unroll
                for (int j = 0; j < NO_COMPUTE(3); j++) {
                    const int4 x0 = lds128(t + j * 128);
                    const int4 x1 = lds128(t + 768 + j * 128);
                    acc[j * 4 + 0] = fmaf(pv1, (float)x1.x, fmaf(pv0, (float)x0.x, acc[j * 4 + 0]));
                    acc[j * 4 + 1] = fmaf(pv1, (float)x1.y, fmaf(pv0, (float)x0.y, acc[j * 4 + 1]));
                    acc[j * 4 + 2] = fmaf(pv1, (float)x1.z, fmaf(pv0, (float)x0.z, acc[j * 4 + 2]));
                    acc[j * 4 + 3] = fmaf(pv1, (float)x1.w, fmaf(pv0, (float)x0.w, acc[j * 4 + 3]));
                }
                __syncwarp();
                if (lane == 0) mbar_arrive(bar + B_EV + vslot * 8);
                TS_ONCE(2);
                if (++vslot == NV) { vslot = 0; vph ^= 1; }
            }
            if (bd.y & F_LAST) {
                float o[3];
#pragma unroll
                for (int j = 0; j < 3; j++) {
                    const float u0 = (up ? acc[j * 4 + 2] : acc[j * 4 + 0]) + __shfl_xor_sync(0xffffffffu, up ? acc[j * 4 + 0] : acc[j * 4 + 2], 16);
                    const float u1 = (up ? acc[j * 4 + 3] : acc[j * 4 + 1]) + __shfl_xor_sync(0xffffffffu, up ? acc[j * 4 + 1] : acc[j * 4 + 3], 16);
                    o[j] = (up2 ? u1 : u0) + __shfl_xor_sync(0xffffffffu, up2 ? u0 : u1, 8);
                }
                mbar_wait(sbar + B_FC, (seg / NSEG) & 1);
                const int4 cf = lds128(s + S_G + (v * 32 + lane) * 16);
                const uint32_t lse = lds32(s + S_LSE);
                o[0] = fmaf(o[0], __int_as_float(cf.w), __int_as_float(cf.x));
                o[1] = fmaf(o[1], __int_as_float(cf.w), __int_as_float(cf.y));
                o[2] = fmaf(o[2], __int_as_float(cf.w), __int_as_float(cf.z));
                if (bd.y & F_FIN) {
                    __nv_bfloat16* op = p.out + bd.x * D + (v * 96 + l * 4 + (up ? 2 : 0) + (up2 ? 1 : 0));
#pragma unroll
                    for (int j = 0; j < 3; j++) op[j * 32] = __float2bfloat16_rn(o[j]);
                } else {
                    asm volatile("st.relaxed.gpu.global.v4.u32 [%0], {%1,%2,%3,%4};"
                                 ::"l"(g_mail + bd.x * 64 + (v * 32 + lane)),
                                   "r"(nz(o[0])), "r"(nz(o[1])), "r"(nz(o[2])), "r"(lse) : "memory");
                }
#pragma unroll
                for (int i = 0; i < 12; i++) acc[i] = 0.f;
            }
            b++;
            if (bd.y & F_SEGEND) {
                if (!(bd.y & F_LAST)) mbar_wait(sbar + B_FC, (seg / NSEG) & 1);
                __syncwarp();
                if (lane == 0) mbar_arrive(sbar + B_SE);
                seg++; b = 0;
            }
            TS(6);
        }
    } else if (w == W_S) {
        float m = NEG, lsum = 0.f, corr = 0.f;
        uint32_t batch = 0;
        for (uint32_t seg = 0;; seg++) {
            const uint32_t s = sb + OFF_SEG + (seg % NSEG) * SEG_BYTES, sbar = bar + (seg % NSEG) * 8;
            const uint32_t sph = (seg / NSEG) & 1;
            mbar_wait(sbar + B_HDR, sph);
            const int4 desc = lds128(s + S_DESC);
            if (desc.y & F_END) {
                if (lane == 0) {
                    sts128(s + S_BD, 0, F_END, 0, 0);
                    mbar_arrive(bar + B_PR + (batch % NBAT) * 8);
                }
                break;
            }
            if (desc.y & F_FIRST) { m = NEG; lsum = 0.f; corr = 0.f; }
            const int index = (desc.y & F_FIN) ? desc.x : desc.x * (NM + 1) + desc.z;
            int b = 0;
            for (int left = desc.y & 255; left > 0; left -= 4, b++, batch++) {
                const bool valid = lane < left * TR;
                const uint32_t sc = s + S_SC + ((((b * 4 + (lane >> 3)) << (desc.w & 255)) + (desc.w >> 8)) * TR + (lane & 7)) * 2;
                const float vs = bf_lo(lds16(sc + 2 * SCB)), vz = bf_lo(lds16(sc + 3 * SCB));
                mbar_wait(bar + B_LG + (batch % NBAT) * 8, (batch / NBAT) & 1);
                const float dot = __uint_as_float(lds32(s + S_LG + (b * 32 + lane) * 4)) +
                                  __uint_as_float(lds32(s + S_LG + SEGT * TR * 4 + (b * 32 + lane) * 4));
                const float sv = rbf(rbf(dot) * 0.07216878364870322f) * LOG2E;
                int key = __float_as_int(fmaxf(m, valid ? sv : m));
                key ^= (key >> 31) & 0x7fffffff;
                key = __reduce_max_sync(0xffffffffu, key);
                const float mn = __int_as_float(key ^ ((key >> 31) & 0x7fffffff));
                const float alpha = ex2(m - mn), pr = ex2(sv - mn), pv = pr * vs;
                m = mn;
                sts32(s + S_LG + (b * 32 + lane) * 4, pv);
                if (lane == 0)
                    sts128(s + S_BD + b * 16, index, left > 4 ? 4 : (left | F_SEGEND | (desc.y & (F_LAST | F_FIN))),
                           __float_as_uint(alpha), 0);
                __syncwarp();
                if (lane == 0) mbar_arrive(bar + B_PR + (batch % NBAT) * 8);
                lsum = fmaf(lsum, alpha, valid ? pr : 0.f);
                corr = fmaf(corr, alpha, valid ? pv * vz : 0.f);
                TS(3);
            }
            float L = lsum, C = corr;
            if (desc.y & F_LAST) {
#pragma unroll
                for (int o = 16; o > 0; o >>= 1) {
                    L += __shfl_xor_sync(0xffffffffu, L, o);
                    C += __shfl_xor_sync(0xffffffffu, C, o);
                }
            }
            mbar_wait(sbar + B_GD, sph);
            if (desc.y & F_LAST) {
                int4 g0 = make_int4(0, 0, 0, 0xff7fffff), g1 = g0;
                if (desc.y & (F_SEMI | F_FIN)) {
                    g0 = lds128(s + S_G + lane * 16);
                    g1 = lds128(s + S_G + (32 + lane) * 16);
                }
                const float M = fmaxf(m, __int_as_float(g0.w));
                const float e = ex2(m - M), a = ex2(__int_as_float(g0.w) - M);
                const float W = fmaf(L, e, a), inv = rcp(W);
                const float c1 = e * inv, ca = a * inv, cc = -C * c1;
                sts128(s + S_G + lane * 16, __float_as_uint(fmaf(__int_as_float(g0.x), ca, cc)),
                       __float_as_uint(fmaf(__int_as_float(g0.y), ca, cc)),
                       __float_as_uint(fmaf(__int_as_float(g0.z), ca, cc)), __float_as_uint(c1));
                sts128(s + S_G + (32 + lane) * 16, __float_as_uint(fmaf(__int_as_float(g1.x), ca, cc)),
                       __float_as_uint(fmaf(__int_as_float(g1.y), ca, cc)),
                       __float_as_uint(fmaf(__int_as_float(g1.z), ca, cc)), __float_as_uint(c1));
                if (lane == 0) sts32(s + S_LSE, __uint_as_float(nz(M + lg2(W))));
            }
            __syncwarp();
            if (lane == 0) mbar_arrive(sbar + B_FC);
            TS(4);
        }
    } else if (w == W_G0 || w == W_G1) {
        for (uint32_t seg = w == W_G1;; seg += NGW) {
            const uint32_t s = sb + OFF_SEG + (seg % NSEG) * SEG_BYTES, sbar = bar + (seg % NSEG) * 8;
            mbar_wait(sbar + B_HDR, (seg / NSEG) & 1);
            const int4 desc = lds128(s + S_DESC);
            if (desc.y & F_END) break;
            TS(1);
            if (desc.y & (F_SEMI | F_FIN)) {
                const int cnt = (desc.y & F_FIN) ? 1 : NM;
                uint4* mail = g_mail + (desc.x * (NM + 1) + ((desc.y & F_FIN) ? NM : 0)) * 64 + lane;
                float M = NEG, W = 0.f, O[6] = {0.f, 0.f, 0.f, 0.f, 0.f, 0.f};
#pragma unroll 1
                for (int i0 = 0; i0 < cnt; i0 += 4, mail += 4 * 64) {
                    uint4 pk[8];
                    bool ready;
                    int it = 0;
                    do {
                        ready = true;
#pragma unroll
                        for (int i = 0; i < 8; i++) {
                            pk[i] = make_uint4(1u, 1u, 1u, 0xff7fffffu);
                            if (i0 + (i >> 1) < cnt)
                                asm volatile("ld.relaxed.gpu.global.v4.u32 {%0,%1,%2,%3}, [%4];"
                                             : "=r"(pk[i].x), "=r"(pk[i].y), "=r"(pk[i].z), "=r"(pk[i].w)
                                             : "l"(mail + i * 32) : "memory");
                        }
#pragma unroll
                        for (int i = 0; i < 8; i++) ready = ready && pk[i].x && pk[i].y && pk[i].z && pk[i].w;
                        if (++it > (1 << 22)) __trap();
                    } while (!ready);
#pragma unroll
                    for (int i = 0; i < 8; i++)
                        if (i0 + (i >> 1) < cnt) mail[i * 32] = make_uint4(0u, 0u, 0u, 0u);
                    float Mn = M;
#pragma unroll
                    for (int i = 0; i < 8; i += 2) Mn = fmaxf(Mn, __uint_as_float(pk[i].w));
                    const float a = ex2(M - Mn);
                    M = Mn; W *= a;
#pragma unroll
                    for (int i = 0; i < 6; i++) O[i] *= a;
#pragma unroll
                    for (int i = 0; i < 8; i += 2) {
                        const float e = ex2(__uint_as_float(pk[i].w) - M);
                        W += e;
                        O[0] = fmaf(e, __uint_as_float(pk[i].x), O[0]);
                        O[1] = fmaf(e, __uint_as_float(pk[i].y), O[1]);
                        O[2] = fmaf(e, __uint_as_float(pk[i].z), O[2]);
                        O[3] = fmaf(e, __uint_as_float(pk[i + 1].x), O[3]);
                        O[4] = fmaf(e, __uint_as_float(pk[i + 1].y), O[4]);
                        O[5] = fmaf(e, __uint_as_float(pk[i + 1].z), O[5]);
                    }
                }
                const float inv = rcp(W), lse = M + lg2(W);
#pragma unroll
                for (int k = 0; k < 2; k++)
                    sts128(s + S_G + (k * 32 + lane) * 16, __float_as_uint(O[3 * k] * inv), __float_as_uint(O[3 * k + 1] * inv),
                           __float_as_uint(O[3 * k + 2] * inv), __float_as_uint(lse));
            }
            __syncwarp();
            if (lane == 0) mbar_arrive(sbar + B_GD);
            TS(2);
        }
    } else if (IS_K(w)) {
        const int g = lane >> 3, l = lane & 7, godd = g & 1;
        const uint32_t sgA = godd ? 0x3f803f80u : 0xbf80bf80u, sgB = sgA ^ 0x80008000u;
        const uint32_t oKA = sb + g * (2 * D * 4) + l * 16 + godd * 384, oKB = oKA - godd * 768 + 384;
        const uint32_t oCA = sb + T_C + g * (2 * D * 2) + l * 8 + godd * 192, oCB = oCA - godd * 384 + 192;
        uint2 qr[6];
        uint32_t kslot = K_IDX(w), j = kslot, batch0 = 0, kph = 0;
        for (uint32_t seg = 0;; seg++) {
            const uint32_t s = sb + OFF_SEG + (seg % NSEG) * SEG_BYTES, sbar = bar + (seg % NSEG) * 8;
            mbar_wait(sbar + B_HDR, (seg / NSEG) & 1);
            const uint32_t desc = lds32(s + S_DESC + 4), geo = lds32(s + S_DESC + 12);
            if (desc & F_END) break;
            const uint32_t nt = desc & 255;
            if (desc & F_FIRST) {
#pragma unroll
                for (int i = 0; i < 3; i++) {
                    const uint32_t oa = l * 8 + godd * 192 + i * 64, ob = oa + 192 - godd * 384;
                    const uint2 a = lds64(s + S_Q + oa), b = lds64(s + S_Q + ob);
                    const uint2 ca = lds64(sb + OFF_QT + oa), cb = lds64(sb + OFF_QT + ob);
                    const uint2 sa = lds64(sb + OFF_QT + QBYTES + oa), sbv = lds64(sb + OFF_QT + QBYTES + ob);
                    qr[i].x = rope2(a.x, ca.x, b.x, sa.x, sgA);
                    qr[i].y = rope2(a.y, ca.y, b.y, sa.y, sgA);
                    qr[i + 3].x = rope2(b.x, cb.x, a.x, sbv.x, sgB);
                    qr[i + 3].y = rope2(b.y, cb.y, a.y, sbv.y, sgB);
                }
            }
            for (; j < nt; j += NKW) {
                const uint32_t t = kslot * KSLOT;
                const uint32_t sc = s + S_SC + ((j << (geo & 255)) + (geo >> 8)) * (TR * 2) + g * 4;
                const uint32_t sks = lds32(sc), skz = lds32(sc + SCB);
                const uint32_t ks2[2] = {__byte_perm(sks, 0, 0x1010), __byte_perm(sks, 0, 0x3232)};
                const uint32_t kz2[2] = {__byte_perm(skz, 0, 0x1010), __byte_perm(skz, 0, 0x3232)};
                mbar_wait(bar + B_FK + kslot * 8, kph);
                TS_ONCE(1); TS(3);
                float cA[4] = {0.f, 0.f, 0.f, 0.f}, cB[4] = {0.f, 0.f, 0.f, 0.f};
#pragma unroll
                for (int jj = 0; jj < NO_COMPUTE(3); jj++) {
                    uint2 ra[2], rb[2];
#pragma unroll
                    for (int ps = 0; ps < 2; ps++) {
                        const int4 xa = lds128(t + oKA + ps * 768 + jj * 128);
                        const int4 xb = lds128(t + oKB + ps * 768 + jj * 128);
                        const uint2 ca = lds64(t + oCA + ps * 384 + jj * 64);
                        const uint2 cb = lds64(t + oCB + ps * 384 + jj * 64);
                        const uint2 sa = lds64(t + oCA + CBYTES + ps * 384 + jj * 64);
                        const uint2 sbv = lds64(t + oCB + CBYTES + ps * 384 + jj * 64);
                        const uint32_t a0 = bmul(bsub(i2bf2(xa.x, xa.y), kz2[ps]), ks2[ps]);
                        const uint32_t a1 = bmul(bsub(i2bf2(xa.z, xa.w), kz2[ps]), ks2[ps]);
                        const uint32_t b0 = bmul(bsub(i2bf2(xb.x, xb.y), kz2[ps]), ks2[ps]);
                        const uint32_t b1 = bmul(bsub(i2bf2(xb.z, xb.w), kz2[ps]), ks2[ps]);
                        ra[ps].x = rope2(a0, ca.x, b0, sa.x, sgA);
                        ra[ps].y = rope2(a1, ca.y, b1, sa.y, sgA);
                        rb[ps].x = rope2(b0, cb.x, a0, sbv.x, sgB);
                        rb[ps].y = rope2(b1, cb.y, a1, sbv.y, sgB);
                    }
                    mma_bf16(cA, ra[0].x, ra[1].x, ra[0].y, ra[1].y, qr[jj].x, qr[jj].y);
                    mma_bf16(cB, rb[0].x, rb[1].x, rb[0].y, rb[1].y, qr[jj + 3].x, qr[jj + 3].y);
                }
                __syncwarp();
                if (lane == 0) mbar_arrive(bar + B_EK + kslot * 8);
                TS_ONCE(2);
                if ((lane & 3) == g)
                    sts64(s + S_LG + (l >> 2) * (SEGT * TR * 4) + (j * TR + 2 * g) * 4,
                          l < 4 ? cA[0] + cB[0] : cA[1] + cB[1], l < 4 ? cA[2] + cB[2] : cA[3] + cB[3]);
                __syncwarp();
                if (lane == 0) mbar_arrive(bar + B_LG + ((batch0 + (j >> 2)) % NBAT) * 8, j == nt - 1 ? 4 - (j & 3) : 1);
                TS(4);
                kslot += NKW;
                if (kslot >= NK) { kslot -= NK; kph ^= 1; }
            }
            j -= nt;
            batch0 += (nt + 3) >> 2;
            __syncwarp();
            if (lane == 0) mbar_arrive(sbar + B_SE);
        }
    } else {
        if (elect_one()) {
            uint64_t pol;
            asm volatile("createpolicy.fractional.L2::evict_first.b64 %0, 1.0;" : "=l"(pol));
            uint32_t kslot = 0, vslot = 0, seg = 0, kph = 1, vph = 1;
            uint32_t win = NV;
            int pend[LEAD];
#pragma unroll
            for (int i = 0; i < LEAD; i++) pend[i] = -1;
            auto push_v = [&](int tile) {
                if (pend[0] >= 0) {
                    const uint32_t b = bar + vslot * 8;
                    mbar_wait(b + B_EV, vph);
                    mbar_expect(b + B_FV, KBYTES);
                    bulk_stream(sb + OFF_V + vslot * KBYTES, p.qv + (size_t)pend[0] * (TR * D), KBYTES, b + B_FV, pol);
                    if (++vslot == NV) { vslot = 0; vph ^= 1; }
                }
#pragma unroll
                for (int i = 0; i + 1 < LEAD; i++) pend[i] = pend[i + 1];
                pend[LEAD - 1] = tile;
            };
            asm volatile("mbarrier.expect_tx.shared::cta.b64 [%0], %1;" ::"r"(bar + B_HDR), "r"(2 * QBYTES) : "memory");
            bulk_plain(sb + OFF_QT, p.qcos, QBYTES, bar + B_HDR);
            bulk_plain(sb + OFF_QT + QBYTES, p.qsin, QBYTES, bar + B_HDR);
            uint32_t c = blockIdx.x;
            TS(1);
            while (c < NCLAIM) {
                const Claim cl = decode_claim(c);
                uint32_t tile = cl.tile0 + cl.off;
                auto tiles = [&](int cnt) {
#pragma unroll 1
                    for (int j = 0; j < cnt; j++, tile += 1u << cl.sh) {
                        push_v(tile);
                        const uint32_t t = sb + kslot * KSLOT, b = bar + kslot * 8;
                        const uint32_t ro = (tile % TPH) * (TR * D);
                        mbar_wait(b + B_EK, kph);
                        mbar_expect(b + B_FK, KSLOT);
                        bulk_stream(t, p.qk + (size_t)tile * (TR * D), KBYTES, b + B_FK, pol);
                        bulk_plain(t + T_C, p.kcos + ro, CBYTES, b + B_FK);
                        bulk_plain(t + T_S, p.ksin + ro, CBYTES, b + B_FK);
                        TS_ONCE(2); TS(3);
                        if (++kslot == NK) { kslot = 0; kph ^= 1; }
                    }
                };
                int nt;
                for (int left = cl.ntiles;; left -= nt) {
                    nt = min(SEGT, left);
                    const bool first = left == cl.ntiles, last = left == nt;
                    const uint32_t s = sb + OFF_SEG + (seg % NSEG) * SEG_BYTES, b = bar + (seg % NSEG) * 8;
                    mbar_wait(b + B_SE, ((seg / NSEG) & 1) ^ 1);
                    sts128(s + S_DESC, cl.head,
                           nt | (first ? F_FIRST : 0) | (last ? F_LAST : 0) | (c >= C_F ? F_FIN : c >= C_S ? F_SEMI : 0),
                           cl.piece, cl.sh | cl.off << 8);
                    const uint32_t scb = nt * TR * 2 << cl.sh;
                    const uint32_t r = (tile - cl.off) * TR;
                    mbar_expect(b + B_HDR, 4 * scb + (first ? QBYTES : 0));
                    if (first) bulk_stream(s + S_Q, p.q + cl.head * D, QBYTES, b + B_HDR, pol);
                    bulk_stream(s + S_SC, p.ks + r, scb, b + B_HDR, pol);
                    bulk_stream(s + S_SC + SCB, p.kz + r, scb, b + B_HDR, pol);
                    bulk_stream(s + S_SC + 2 * SCB, p.vs + r, scb, b + B_HDR, pol);
                    bulk_stream(s + S_SC + 3 * SCB, p.vz + r, scb, b + B_HDR, pol);
                    seg++;
                    tiles(last ? max(nt - LA, 0) : nt);
                    if (last) break;
                }
                const unsigned nx = atomicInc(&g_queue, NCLAIM - 1);
                tiles(min(nt, LA));
                c = gridDim.x + nx;
            }
            TS(4);
#pragma unroll 1
            for (int i = 0; i < LEAD; i++) push_v(-1);
            TS(5);
#pragma unroll 1
            for (int i = 0; i < NGW; i++, seg++) {
                const uint32_t s = sb + OFF_SEG + (seg % NSEG) * SEG_BYTES, b = bar + (seg % NSEG) * 8;
                mbar_wait(b + B_SE, ((seg / NSEG) & 1) ^ 1);
                sts128(s + S_DESC, 0, F_END, 0, 0);
                mbar_arrive(b + B_HDR);
            }
        }
    }
}

}

extern "C" void kernel_launch(void* const* d_in, const int* in_sizes, int n_in, void* d_out, int out_size) {
    (void)in_sizes; (void)n_in; (void)out_size;
    static int sms = 0;
    if (sms == 0) {
        int dev = 0;
        cudaGetDevice(&dev);
        cudaDeviceGetAttribute(&sms, cudaDevAttrMultiProcessorCount, dev);
        cudaFuncSetAttribute(kv_rope_decode_kernel, cudaFuncAttributeMaxDynamicSharedMemorySize, SMEM_BYTES);
    }
    Params p;
    p.q    = (const __nv_bfloat16*)d_in[0];
    p.qk   = (const int*)d_in[1];
    p.ks   = (const __nv_bfloat16*)d_in[2];
    p.kz   = (const __nv_bfloat16*)d_in[3];
    p.qv   = (const int*)d_in[4];
    p.vs   = (const __nv_bfloat16*)d_in[5];
    p.vz   = (const __nv_bfloat16*)d_in[6];
    p.qcos = (const __nv_bfloat16*)d_in[7];
    p.qsin = (const __nv_bfloat16*)d_in[8];
    p.kcos = (const __nv_bfloat16*)d_in[9];
    p.ksin = (const __nv_bfloat16*)d_in[10];
    p.out  = (__nv_bfloat16*)d_out;
    kv_rope_decode_kernel<<<sms, NTHREADS, SMEM_BYTES>>>(p);
}
```

```cpp
#include <cuda_runtime.h>
#include <cuda_bf16.h>
#include <stdint.h>

namespace {

#define CFG_NKW 4
#define CFG_NK 8
#define CFG_NV 4
#define CFG_LEAD 5
#define CFG_MAIN 16
#define CFG_SEMI 0xfdb9
#define CFG_FIN 0x7531
#define CFG_GSH 2
#define CFG_LA 3
#define CFG_PF0 3

constexpr int D      = 192;
constexpr int SKV    = 2048;
constexpr int NHEAD  = 256;
constexpr int TR     = 8;
constexpr int TPH    = SKV / TR;
constexpr int NKW    = CFG_NKW;
constexpr int NVW    = 2;
constexpr int NGW    = 2;
constexpr int NK     = CFG_NK;
constexpr int NV     = CFG_NV;
constexpr int LEAD   = CFG_LEAD;
constexpr int NSEG   = 8;
constexpr int SEGT   = 16;
constexpr int NBAT   = 16;
constexpr int W_V = 6, W_PROD = 4, W_G0 = 8, W_S = 5, W_G1 = 9, NWARPS = 10;
#define IS_K(w) ((w >> 2) == 0)
#define K_IDX(w) w

constexpr int NTHREADS = NWARPS * 32 + 32;

constexpr int MAINP  = CFG_MAIN;
constexpr int GSH    = CFG_GSH;
constexpr int LA     = CFG_LA;
__host__ __device__ constexpr int semi_size(int h) { return ((CFG_SEMI >> (12 - 4 * (h >> 6))) & 15) + 1; }
__host__ __device__ constexpr int fin_size(int h) { return ((CFG_FIN >> (12 - 4 * (h >> 6))) & 15) + 1; }
constexpr int NM     = (TPH - semi_size(0) - fin_size(0) + MAINP - 1) / MAINP;
constexpr int C_S    = NHEAD * NM, C_F = C_S + NHEAD, NCLAIM = C_F + NHEAD;
constexpr bool sizes_ok(int h) { return h >= NHEAD || (semi_size(h) + fin_size(h) < TPH - (NM - 1) * MAINP && sizes_ok(h + 64)); }
static_assert(sizes_ok(0), "schedule");

constexpr int KBYTES = TR * D * 4;
constexpr int CBYTES = TR * D * 2;
constexpr int QBYTES = D * 2;
constexpr int T_C = KBYTES, T_S = T_C + CBYTES, KSLOT = T_S + CBYTES;
constexpr int SCB = SEGT * TR * 2 << GSH;
static_assert(GSH == 0 || MAINP == SEGT, "interleaved pieces are single segments");
constexpr int S_Q = 0, S_SC = QBYTES, S_DESC = S_SC + 4 * SCB, S_BD = S_DESC + 16,
              S_LG = S_BD + 4 * 16, S_G = S_LG + 2 * SEGT * TR * 4, S_LSE = S_G + 64 * 16,
              SEG_BYTES = (S_LSE + 16 + 127) / 128 * 128;
constexpr int OFF_V = NK * KSLOT, OFF_SEG = OFF_V + NV * KBYTES, OFF_QT = OFF_SEG + NSEG * SEG_BYTES,
              OFF_BAR = OFF_QT + 2 * QBYTES;
constexpr int B_FK = 0, B_EK = 64, B_PR = 128, B_HDR = 256, B_GD = 320, B_FC = 384, B_FV = 448, B_LG = 640,
              B_SE = 768, B_EV = 896;
constexpr int SMEM_BYTES = OFF_BAR + 1024;
static_assert(NK <= 8 && NV <= 8 && NSEG == 8 && NBAT == 16, "barrier layout");
static_assert(SMEM_BYTES <= 232448 && SMEM_BYTES > 232448 / 2, "smem");
static_assert(NSEG % NGW == 0 && NK % NKW == 0 && NKW >= 2 && NKW <= 4 && LEAD >= 1, "cfg");
static_assert(LEAD + NV >= 4 && LEAD + NV < NBAT && LEAD < NSEG, "cfg");

__device__ unsigned int g_queue;
__device__ uint4 g_mail[NHEAD * (NM + 1) * 64];

__device__ __forceinline__ uint32_t smem_u32(const void* p) { return (uint32_t)__cvta_generic_to_shared(p); }
__device__ __forceinline__ uint32_t pin(uint32_t x) {
    return __shfl_sync(0xffffffffu, x, threadIdx.x & 31);
}
__device__ __forceinline__ bool elect_one() {
    uint32_t pred;
    asm volatile("{\n.reg .pred p;\nelect.sync _|p, 0xffffffff;\nselp.u32 %0, 1, 0, p;\n}" : "=r"(pred));
    return pred;
}
__device__ __forceinline__ void mbar_init(uint32_t bar, uint32_t cnt) {
    asm volatile("mbarrier.init.shared::cta.b64 [%0], %1;" ::"r"(bar), "r"(cnt) : "memory");
}
__device__ __forceinline__ void mbar_expect(uint32_t bar, uint32_t bytes) {
    asm volatile("mbarrier.arrive.expect_tx.shared::cta.b64 _, [%0], %1;" ::"r"(bar), "r"(bytes) : "memory");
}
__device__ __forceinline__ void mbar_arrive(uint32_t bar) {
    asm volatile("mbarrier.arrive.shared::cta.b64 _, [%0];" ::"r"(bar) : "memory");
}
__device__ __forceinline__ void mbar_arrive(uint32_t bar, uint32_t cnt) {
    asm volatile("mbarrier.arrive.shared::cta.b64 _, [%0], %1;" ::"r"(bar), "r"(cnt) : "memory");
}
__device__ __forceinline__ bool mbar_test(uint32_t bar, uint32_t parity) {
    uint32_t ok;
    asm volatile("{\n.reg .pred p;\nmbarrier.test_wait.parity.shared::cta.b64 p, [%1], %2;\nselp.u32 %0, 1, 0, p;\n}"
                 : "=r"(ok) : "r"(bar), "r"(parity) : "memory");
    return ok;
}
__device__ __forceinline__ void mbar_wait(uint32_t bar, uint32_t parity) {
    asm volatile("{\n.reg .pred p;\n.reg .u32 n;\n"
                 "mbarrier.try_wait.parity.shared::cta.b64 p, [%0], %1;\n"
                 "@p bra DONE;\n"
                 "mov.u32 n, 0;\n"
                 "LOOP:\n"
                 "mbarrier.try_wait.parity.shared::cta.b64 p, [%0], %1;\n"
                 "@p bra DONE;\n"
                 "add.u32 n, n, 1;\n"
                 "setp.lt.u32 p, n, 0x400000;\n"
                 "@p bra LOOP;\n"
                 "trap;\n"
                 "DONE:\n}" ::"r"(bar), "r"(parity) : "memory");
}
__device__ __forceinline__ void bulk_stream(uint32_t dst, const void* src, uint32_t bytes, uint32_t bar, uint64_t pol) {
    asm volatile("cp.async.bulk.shared::cluster.global.mbarrier::complete_tx::bytes.L2::cache_hint [%0], [%1], %2, [%3], %4;"
                 ::"r"(dst), "l"(src), "r"(bytes), "r"(bar), "l"(pol) : "memory");
}
__device__ __forceinline__ void bulk_plain(uint32_t dst, const void* src, uint32_t bytes, uint32_t bar) {
    asm volatile("cp.async.bulk.shared::cluster.global.mbarrier::complete_tx::bytes [%0], [%1], %2, [%3];"
                 ::"r"(dst), "l"(src), "r"(bytes), "r"(bar) : "memory");
}
__device__ __forceinline__ void l2_prefetch(const void* src, uint32_t bytes, uint64_t pol) {
    asm volatile("cp.async.bulk.prefetch.L2.global.L2::cache_hint [%0], %1, %2;" ::"l"(src), "r"(bytes), "l"(pol) : "memory");
}
__device__ __forceinline__ void l2_prefetch(const void* src, uint32_t bytes) {
    asm volatile("cp.async.bulk.prefetch.L2.global [%0], %1;" ::"l"(src), "r"(bytes) : "memory");
}
__device__ __forceinline__ int4 lds128(uint32_t a) {
    int4 v;
    asm volatile("ld.shared.v4.s32 {%0,%1,%2,%3}, [%4];" : "=r"(v.x), "=r"(v.y), "=r"(v.z), "=r"(v.w) : "r"(a));
    return v;
}
__device__ __forceinline__ uint2 lds64(uint32_t a) {
    uint2 v;
    asm volatile("ld.shared.v2.u32 {%0,%1}, [%2];" : "=r"(v.x), "=r"(v.y) : "r"(a));
    return v;
}
__device__ __forceinline__ uint32_t lds32(uint32_t a) {
    uint32_t v;
    asm volatile("ld.shared.u32 %0, [%1];" : "=r"(v) : "r"(a));
    return v;
}
__device__ __forceinline__ uint32_t lds16(uint32_t a) {
    uint16_t v;
    asm volatile("ld.shared.u16 %0, [%1];" : "=h"(v) : "r"(a));
    return v;
}
__device__ __forceinline__ void sts32(uint32_t a, float x) {
    asm volatile("st.shared.f32 [%0], %1;" ::"r"(a), "f"(x) : "memory");
}
__device__ __forceinline__ void sts128(uint32_t a, uint32_t x, uint32_t y, uint32_t z, uint32_t w) {
    asm volatile("st.shared.v4.u32 [%0], {%1,%2,%3,%4};" ::"r"(a), "r"(x), "r"(y), "r"(z), "r"(w) : "memory");
}
__device__ __forceinline__ void sts64(uint32_t a, float x, float y) {
    asm volatile("st.shared.v2.f32 [%0], {%1,%2};" ::"r"(a), "f"(x), "f"(y) : "memory");
}
__device__ __forceinline__ float bf_lo(uint32_t v) { return __uint_as_float(v << 16); }
__device__ __forceinline__ float bf_hi(uint32_t v) { return __uint_as_float(v & 0xffff0000u); }
__device__ __forceinline__ float rbf(float x) {
    uint32_t d; asm("cvt.rn.bf16x2.f32 %0, %1, %2;" : "=r"(d) : "f"(x), "f"(0.f)); return __uint_as_float(d);
}
__device__ __forceinline__ float rcp(float x) {
    float y;
    asm("rcp.approx.ftz.f32 %0, %1;" : "=f"(y) : "f"(x));
    return y;
}
__device__ __forceinline__ float lg2(float x) {
    float y;
    asm("lg2.approx.ftz.f32 %0, %1;" : "=f"(y) : "f"(x));
    return y;
}
__device__ __forceinline__ float ex2(float x) {
    float y;
    asm("ex2.approx.ftz.f32 %0, %1;" : "=f"(y) : "f"(x));
    return y;
}
__device__ __forceinline__ uint32_t bmul(uint32_t a, uint32_t b) {
    uint32_t d; asm("mul.rn.bf16x2 %0, %1, %2;" : "=r"(d) : "r"(a), "r"(b)); return d;
}
__device__ __forceinline__ uint32_t bsub(uint32_t a, uint32_t b) {
    uint32_t d; asm("sub.rn.bf16x2 %0, %1, %2;" : "=r"(d) : "r"(a), "r"(b)); return d;
}
__device__ __forceinline__ uint32_t bfma(uint32_t a, uint32_t b, uint32_t c) {
    uint32_t d; asm("fma.rn.bf16x2 %0, %1, %2, %3;" : "=r"(d) : "r"(a), "r"(b), "r"(c)); return d;
}
__device__ __forceinline__ uint32_t i2bf2(int lo, int hi) {
    uint32_t d; asm("cvt.rn.bf16x2.f32 %0, %1, %2;" : "=r"(d) : "f"((float)hi), "f"((float)lo)); return d;
}
__device__ __forceinline__ uint32_t rope2(uint32_t x, uint32_t c, uint32_t y, uint32_t s, uint32_t sg) {
    return bfma(bmul(y, s), sg, bmul(x, c));
}
__device__ __forceinline__ void mma_bf16(float (&c)[4], uint32_t a0, uint32_t a1, uint32_t a2, uint32_t a3,
                                         uint32_t b0, uint32_t b1) {
    asm("mma.sync.aligned.m16n8k16.row.col.f32.bf16.bf16.f32 {%0,%1,%2,%3}, {%4,%5,%6,%7}, {%8,%9}, {%0,%1,%2,%3};"
        : "+f"(c[0]), "+f"(c[1]), "+f"(c[2]), "+f"(c[3])
        : "r"(a0), "r"(a1), "r"(a2), "r"(a3), "r"(b0), "r"(b1));
}
__device__ __forceinline__ uint32_t nz(float x) {
    const uint32_t u = __float_as_uint(x);
    return u == 0u ? 0x80000000u : u;
}

#define TS(i)
#define TS_ONCE(i)

#define NO_COMPUTE(x) x
struct Claim { uint32_t head, tile0, piece, sh, off; int ntiles; };

__device__ __forceinline__ Claim decode_claim(uint32_t c) {
    Claim cl;
    cl.sh = cl.off = 0;
    if (c < C_S) {
        cl.head = c / NM; cl.piece = c - cl.head * NM; cl.tile0 = cl.head * TPH + cl.piece * MAINP;
        cl.ntiles = cl.piece < NM - 1 ? MAINP : TPH - (NM - 1) * MAINP - semi_size(cl.head) - fin_size(cl.head);
        if (cl.piece < ((NM - 1) >> GSH << GSH)) {
            cl.sh = GSH; cl.off = cl.piece & ((1 << GSH) - 1); cl.tile0 -= cl.off * MAINP;
        }
    } else {
        cl.head = (c - C_S) % NHEAD; cl.piece = NM;
        cl.ntiles = fin_size(cl.head); cl.tile0 = (cl.head + 1) * TPH - cl.ntiles;
        if (c < C_F) { cl.ntiles = semi_size(cl.head); cl.tile0 -= cl.ntiles; }
    }
    return cl;
}

struct Params {
    const int* qk; const __nv_bfloat16* kcos; const __nv_bfloat16* ksin; const int* qv;
    const __nv_bfloat16* ks; const __nv_bfloat16* kz; const __nv_bfloat16* vs; const __nv_bfloat16* vz;
    const __nv_bfloat16* q; const __nv_bfloat16* qcos; const __nv_bfloat16* qsin;
    __nv_bfloat16* out;
};

constexpr float NEG = -3.0e38f;
constexpr float LOG2E = 1.4426950408889634f;
constexpr int F_FIRST = 256, F_LAST = 512, F_SEMI = 1024, F_FIN = 2048, F_SEGEND = 4096, F_END = 8192;

__global__ void __launch_bounds__(NTHREADS, 1)
kv_rope_decode_kernel(const Params p) {
    extern __shared__ __align__(128) unsigned char smem[];
        if (threadIdx.x >= NWARPS * 32 && elect_one()) {
        l2_prefetch(p.kcos + (blockIdx.x % (TPH / 2)) * (2 * TR * D), 2 * CBYTES);
        l2_prefetch(p.ksin + (blockIdx.x % (TPH / 2)) * (2 * TR * D), 2 * CBYTES);
        uint64_t pol;
        asm volatile("createpolicy.fractional.L2::evict_first.b64 %0, 1.0;" : "=l"(pol));
        const uint32_t h = blockIdx.x / NM, pc = blockIdx.x - h * NM;
        const uint32_t off = pc < ((NM - 1) >> GSH << GSH) ? pc & ((1 << GSH) - 1) : 0;
        l2_prefetch(p.qk + (size_t)(h * TPH + (pc - off) * MAINP + off * CFG_PF0) * (TR * D), CFG_PF0 * KBYTES, pol);
    }
    const int w = __shfl_sync(0xffffffffu, threadIdx.x >> 5, 0), lane = threadIdx.x & 31;
    if (w == NWARPS) return;
    const uint32_t sb = __shfl_sync(0xffffffffu, smem_u32(smem), 0);
    const uint32_t bar = sb + OFF_BAR;

    if (w < 8 && w != W_PROD && elect_one()) {
        const uint32_t cnt = w == 5 ? 4 : w == 6 ? NKW + NVW : w == 7 ? NVW : 1;
#pragma unroll
        for (int i = 0; i < 16; i++) mbar_init(bar + w * 128 + i * 8, cnt);
        asm volatile("fence.mbarrier_init.release.cluster;" ::: "memory");
    }
    asm volatile("bar.sync 0, %0;" ::"n"(NWARPS * 32) : "memory");

    if (w == W_V || w == W_V + 1) {
        const int v = w - W_V, g = lane >> 3, l = lane & 7;
        const bool up = lane & 16, up2 = lane & 8;
        const uint32_t oV = pin(sb + OFF_V + g * (2 * D * 4) + v * 384 + l * 16);
        const uint32_t oP = pin(S_LG + g * 8), oG = pin(S_G + (v * 32 + lane) * 16);
        const uint32_t oM = pin(v * 32 + lane), oO = pin(v * 96 + l * 4 + (up ? 2 : 0) + (up2 ? 1 : 0));
        float acc[12];
#pragma unroll
        for (int i = 0; i < 12; i++) acc[i] = 0.f;
        uint32_t vslot = 0, seg = 0, b = 0, vph = 0;
        for (uint32_t batch = 0;; batch++) {
            const uint32_t s = sb + OFF_SEG + (seg % NSEG) * SEG_BYTES, sbar = bar + (seg % NSEG) * 8;
            mbar_wait(bar + B_PR + (batch % NBAT) * 8, (batch / NBAT) & 1);
            const int4 bd = lds128(s + S_BD + b * 16);
            const bool early = mbar_test(sbar + B_FC, (seg / NSEG) & 1);
            bool ready = mbar_test(bar + B_FV + vslot * 8, vph);
            uint32_t pa = s + oP + b * 128;
            uint2 pv = lds64(pa);
            int4 cf = lds128(s + oG);
            uint32_t lse = lds32(s + S_LSE);
            if (bd.y & F_END) break;
            TS(3);
            const float alpha = __int_as_float(bd.z);
#pragma unroll
            for (int i = 0; i < 12; i++) acc[i] *= alpha;
            const int n = bd.y & 255;
#pragma unroll 1
            for (int i = 0; i < n; i++) {
                const float pv0 = __uint_as_float(pv.x), pv1 = __uint_as_float(pv.y);
                const uint32_t t = oV + vslot * KBYTES;
                                if (!ready) mbar_wait(bar + B_FV + vslot * 8, vph);
                TS_ONCE(1); TS(5);
                int4 x0[3], x1[3];
#pragma unroll
                for (int j = 0; j < NO_COMPUTE(3); j++) {
                    x0[j] = lds128(t + j * 128);
                    x1[j] = lds128(t + 768 + j * 128);
                }
                __syncwarp();
                if (lane == 0) mbar_arrive(bar + B_EV + vslot * 8);
                if (++vslot == NV) { vslot = 0; vph ^= 1; }
                ready = mbar_test(bar + B_FV + vslot * 8, vph);
                pv = lds64(pa += TR * 4);
#pragma unroll
                for (int j = 0; j < NO_COMPUTE(3); j++) {
                    acc[j * 4 + 0] = fmaf(pv1, (float)x1[j].x, fmaf(pv0, (float)x0[j].x, acc[j * 4 + 0]));
                    acc[j * 4 + 1] = fmaf(pv1, (float)x1[j].y, fmaf(pv0, (float)x0[j].y, acc[j * 4 + 1]));
                    acc[j * 4 + 2] = fmaf(pv1, (float)x1[j].z, fmaf(pv0, (float)x0[j].z, acc[j * 4 + 2]));
                    acc[j * 4 + 3] = fmaf(pv1, (float)x1[j].w, fmaf(pv0, (float)x0[j].w, acc[j * 4 + 3]));
                }
            }
            if (bd.y & F_LAST) {
                float o[3];
#pragma unroll
                for (int j = 0; j < 3; j++) {
                    const float u0 = (up ? acc[j * 4 + 2] : acc[j * 4 + 0]) + __shfl_xor_sync(0xffffffffu, up ? acc[j * 4 + 0] : acc[j * 4 + 2], 16);
                    const float u1 = (up ? acc[j * 4 + 3] : acc[j * 4 + 1]) + __shfl_xor_sync(0xffffffffu, up ? acc[j * 4 + 1] : acc[j * 4 + 3], 16);
                    o[j] = (up2 ? u1 : u0) + __shfl_xor_sync(0xffffffffu, up2 ? u0 : u1, 8);
                }
                if (!early) {
                    mbar_wait(sbar + B_FC, (seg / NSEG) & 1);
                    cf = lds128(s + oG);
                    lse = lds32(s + S_LSE);
                }
                o[0] = fmaf(o[0], __int_as_float(cf.w), __int_as_float(cf.x));
                o[1] = fmaf(o[1], __int_as_float(cf.w), __int_as_float(cf.y));
                o[2] = fmaf(o[2], __int_as_float(cf.w), __int_as_float(cf.z));
                if (bd.y & F_FIN) {
                    __nv_bfloat16* op = p.out + (bd.x + oO);
#pragma unroll
                    for (int j = 0; j < 3; j++) op[j * 32] = __float2bfloat16_rn(o[j]);
                } else {
                    asm volatile("st.relaxed.gpu.global.v4.u32 [%0], {%1,%2,%3,%4};"
                                 ::"l"(g_mail + (bd.x + oM)),
                                   "r"(nz(o[0])), "r"(nz(o[1])), "r"(nz(o[2])), "r"(lse) : "memory");
                }
#pragma unroll
                for (int i = 0; i < 12; i++) acc[i] = 0.f;
            }
            b++;
            if (bd.y & F_SEGEND) {
                if (!(bd.y & F_LAST)) mbar_wait(sbar + B_FC, (seg / NSEG) & 1);
                __syncwarp();
                if (lane == 0) mbar_arrive(sbar + B_SE);
                seg++; b = 0;
            }
            TS(6);
        }
    } else if (w == W_S) {
        float m = NEG, lsum = 0.f, corr = 0.f;
        uint32_t batch = 0;
        for (uint32_t seg = 0;; seg++) {
            const uint32_t s = sb + OFF_SEG + (seg % NSEG) * SEG_BYTES, sbar = bar + (seg % NSEG) * 8;
            const uint32_t sph = (seg / NSEG) & 1;
            mbar_wait(sbar + B_HDR, sph);
            const int4 desc = lds128(s + S_DESC);
            if (desc.y & F_END) {
                if (lane == 0) {
                    sts128(s + S_BD, 0, F_END, 0, 0);
                    mbar_arrive(bar + B_PR + (batch % NBAT) * 8);
                }
                break;
            }
            if (desc.y & F_FIRST) { m = NEG; lsum = 0.f; corr = 0.f; }
            const int index = (desc.y & F_FIN) ? desc.x * D : (desc.x * (NM + 1) + desc.z) * 64;
            int b = 0;
            for (int left = desc.y & 255; left > 0; left -= 4, b++, batch++) {
                const bool valid = lane < left * TR;
                const uint32_t sc = s + S_SC + ((((b * 4 + (lane >> 3)) << (desc.w & 255)) + (desc.w >> 8)) * TR + (lane & 7)) * 2;
                const float vs = bf_lo(lds16(sc + 2 * SCB)), vz = bf_lo(lds16(sc + 3 * SCB));
                mbar_wait(bar + B_LG + (batch % NBAT) * 8, (batch / NBAT) & 1);
                const float dot = __uint_as_float(lds32(s + S_LG + (b * 32 + lane) * 4)) +
                                  __uint_as_float(lds32(s + S_LG + SEGT * TR * 4 + (b * 32 + lane) * 4));
                const float sv = rbf(rbf(dot) * 0.07216878364870322f) * LOG2E;
                int key = __float_as_int(fmaxf(m, valid ? sv : m));
                key ^= (key >> 31) & 0x7fffffff;
                key = __reduce_max_sync(0xffffffffu, key);
                const float mn = __int_as_float(key ^ ((key >> 31) & 0x7fffffff));
                const float alpha = ex2(m - mn), pr = ex2(sv - mn), pv = pr * vs;
                m = mn;
                sts32(s + S_LG + (b * 32 + lane) * 4, pv);
                if (lane == 0)
                    sts128(s + S_BD + b * 16, index, left > 4 ? 4 : (left | F_SEGEND | (desc.y & (F_LAST | F_FIN))),
                           __float_as_uint(alpha), 0);
                __syncwarp();
                if (lane == 0) mbar_arrive(bar + B_PR + (batch % NBAT) * 8);
                lsum = fmaf(lsum, alpha, valid ? pr : 0.f);
                corr = fmaf(corr, alpha, valid ? pv * vz : 0.f);
                TS(3);
            }
            float L = lsum, C = corr;
            if (desc.y & F_LAST) {
#pragma unroll
                for (int o = 16; o > 0; o >>= 1) {
                    L += __shfl_xor_sync(0xffffffffu, L, o);
                    C += __shfl_xor_sync(0xffffffffu, C, o);
                }
            }
            mbar_wait(sbar + B_GD, sph);
            if (desc.y & F_LAST) {
                int4 g0 = make_int4(0, 0, 0, 0xff7fffff), g1 = g0;
                if (desc.y & (F_SEMI | F_FIN)) {
                    g0 = lds128(s + S_G + lane * 16);
                    g1 = lds128(s + S_G + (32 + lane) * 16);
                }
                const float M = fmaxf(m, __int_as_float(g0.w));
                const float e = ex2(m - M), a = ex2(__int_as_float(g0.w) - M);
                const float W = fmaf(L, e, a), inv = rcp(W);
                const float c1 = e * inv, ca = a * inv, cc = -C * c1;
                sts128(s + S_G + lane * 16, __float_as_uint(fmaf(__int_as_float(g0.x), ca, cc)),
                       __float_as_uint(fmaf(__int_as_float(g0.y), ca, cc)),
                       __float_as_uint(fmaf(__int_as_float(g0.z), ca, cc)), __float_as_uint(c1));
                sts128(s + S_G + (32 + lane) * 16, __float_as_uint(fmaf(__int_as_float(g1.x), ca, cc)),
                       __float_as_uint(fmaf(__int_as_float(g1.y), ca, cc)),
                       __float_as_uint(fmaf(__int_as_float(g1.z), ca, cc)), __float_as_uint(c1));
                if (lane == 0) sts32(s + S_LSE, __uint_as_float(nz(M + lg2(W))));
            }
            __syncwarp();
            if (lane == 0) mbar_arrive(sbar + B_FC);
            TS(4);
        }
    } else if (w == W_G0 || w == W_G1) {
        for (uint32_t seg = w == W_G1;; seg += NGW) {
            const uint32_t s = sb + OFF_SEG + (seg % NSEG) * SEG_BYTES, sbar = bar + (seg % NSEG) * 8;
            mbar_wait(sbar + B_HDR, (seg / NSEG) & 1);
            const int4 desc = lds128(s + S_DESC);
            if (desc.y & F_END) break;
            TS(1);
            if (desc.y & (F_SEMI | F_FIN)) {
                const int cnt = (desc.y & F_FIN) ? 1 : NM;
                uint4* mail = g_mail + (desc.x * (NM + 1) + ((desc.y & F_FIN) ? NM : 0)) * 64 + lane;
                float M = NEG, W = 0.f, O[6] = {0.f, 0.f, 0.f, 0.f, 0.f, 0.f};
#pragma unroll 1
                for (int i0 = 0; i0 < cnt; i0 += 4, mail += 4 * 64) {
                    uint4 pk[8];
                    bool ready;
                    int it = 0;
                    do {
                        ready = true;
#pragma unroll
                        for (int i = 0; i < 8; i++) {
                            pk[i] = make_uint4(1u, 1u, 1u, 0xff7fffffu);
                            if (i0 + (i >> 1) < cnt)
                                asm volatile("ld.relaxed.gpu.global.v4.u32 {%0,%1,%2,%3}, [%4];"
                                             : "=r"(pk[i].x), "=r"(pk[i].y), "=r"(pk[i].z), "=r"(pk[i].w)
                                             : "l"(mail + i * 32) : "memory");
                        }
#pragma unroll
                        for (int i = 0; i < 8; i++) ready = ready && pk[i].x && pk[i].y && pk[i].z && pk[i].w;
                        if (++it > (1 << 22)) __trap();
                    } while (!ready);
#pragma unroll
                    for (int i = 0; i < 8; i++)
                        if (i0 + (i >> 1) < cnt) mail[i * 32] = make_uint4(0u, 0u, 0u, 0u);
                    float Mn = M;
#pragma unroll
                    for (int i = 0; i < 8; i += 2) Mn = fmaxf(Mn, __uint_as_float(pk[i].w));
                    const float a = ex2(M - Mn);
                    M = Mn; W *= a;
#pragma unroll
                    for (int i = 0; i < 6; i++) O[i] *= a;
#pragma unroll
                    for (int i = 0; i < 8; i += 2) {
                        const float e = ex2(__uint_as_float(pk[i].w) - M);
                        W += e;
                        O[0] = fmaf(e, __uint_as_float(pk[i].x), O[0]);
                        O[1] = fmaf(e, __uint_as_float(pk[i].y), O[1]);
                        O[2] = fmaf(e, __uint_as_float(pk[i].z), O[2]);
                        O[3] = fmaf(e, __uint_as_float(pk[i + 1].x), O[3]);
                        O[4] = fmaf(e, __uint_as_float(pk[i + 1].y), O[4]);
                        O[5] = fmaf(e, __uint_as_float(pk[i + 1].z), O[5]);
                    }
                }
                const float inv = rcp(W), lse = M + lg2(W);
#pragma unroll
                for (int k = 0; k < 2; k++)
                    sts128(s + S_G + (k * 32 + lane) * 16, __float_as_uint(O[3 * k] * inv), __float_as_uint(O[3 * k + 1] * inv),
                           __float_as_uint(O[3 * k + 2] * inv), __float_as_uint(lse));
            }
            __syncwarp();
            if (lane == 0) mbar_arrive(sbar + B_GD);
            TS(2);
        }
    } else if (IS_K(w)) {
        const int g = lane >> 3, l = lane & 7, godd = g & 1;
        const uint32_t sgA = pin(godd ? 0x3f803f80u : 0xbf80bf80u), sgB = pin(godd ? 0xbf80bf80u : 0x3f803f80u);
        const uint32_t oKA = pin(sb + g * (2 * D * 4) + l * 16 + godd * 384), oKB = pin(oKA - godd * 768 + 384);
        const uint32_t oCA = pin(sb + T_C + g * (2 * D * 2) + l * 8 + godd * 192), oCB = pin(oCA - godd * 384 + 192);
        const uint32_t oL = pin(S_LG + (l >> 2) * (SEGT * TR * 4) + g * 8);
        uint2 qr[6];
        uint32_t kslot = K_IDX(w), j = kslot, batch0 = 0, kph = 0;
        for (uint32_t seg = 0;; seg++) {
            const uint32_t s = sb + OFF_SEG + (seg % NSEG) * SEG_BYTES, sbar = bar + (seg % NSEG) * 8;
            mbar_wait(sbar + B_HDR, (seg / NSEG) & 1);
            const uint32_t desc = lds32(s + S_DESC + 4), geo = lds32(s + S_DESC + 12);
            if (desc & F_END) break;
            const uint32_t nt = desc & 255;
            if (desc & F_FIRST) {
#pragma unroll
                for (int i = 0; i < 3; i++) {
                    const uint32_t oa = l * 8 + godd * 192 + i * 64, ob = oa + 192 - godd * 384;
                    const uint2 a = lds64(s + S_Q + oa), b = lds64(s + S_Q + ob);
                    const uint2 ca = lds64(sb + OFF_QT + oa), cb = lds64(sb + OFF_QT + ob);
                    const uint2 sa = lds64(sb + OFF_QT + QBYTES + oa), sbv = lds64(sb + OFF_QT + QBYTES + ob);
                    qr[i].x = rope2(a.x, ca.x, b.x, sa.x, sgA);
                    qr[i].y = rope2(a.y, ca.y, b.y, sa.y, sgA);
                    qr[i + 3].x = rope2(b.x, cb.x, a.x, sbv.x, sgB);
                    qr[i + 3].y = rope2(b.y, cb.y, a.y, sbv.y, sgB);
                }
            }
            for (; j < nt; j += NKW) {
                const uint32_t t = kslot * KSLOT;
                const uint32_t sc = s + S_SC + ((j << (geo & 255)) + (geo >> 8)) * (TR * 2) + g * 4;
                const uint32_t sks = lds32(sc), skz = lds32(sc + SCB);
                const uint32_t ks2[2] = {__byte_perm(sks, 0, 0x1010), __byte_perm(sks, 0, 0x3232)};
                const uint32_t kz2[2] = {__byte_perm(skz, 0, 0x1010), __byte_perm(skz, 0, 0x3232)};
                mbar_wait(bar + B_FK + kslot * 8, kph);
                TS_ONCE(1); TS(3);
                float cA[4] = {0.f, 0.f, 0.f, 0.f}, cB[4] = {0.f, 0.f, 0.f, 0.f};
#pragma unroll
                for (int jj = 0; jj < NO_COMPUTE(3); jj++) {
                    uint2 ra[2], rb[2];
#pragma unroll
                    for (int ps = 0; ps < 2; ps++) {
                        const int4 xa = lds128(t + oKA + ps * 768 + jj * 128);
                        const int4 xb = lds128(t + oKB + ps * 768 + jj * 128);
                        const uint2 ca = lds64(t + oCA + ps * 384 + jj * 64);
                        const uint2 cb = lds64(t + oCB + ps * 384 + jj * 64);
                        const uint2 sa = lds64(t + oCA + CBYTES + ps * 384 + jj * 64);
                        const uint2 sbv = lds64(t + oCB + CBYTES + ps * 384 + jj * 64);
                        const uint32_t a0 = bmul(bsub(i2bf2(xa.x, xa.y), kz2[ps]), ks2[ps]);
                        const uint32_t a1 = bmul(bsub(i2bf2(xa.z, xa.w), kz2[ps]), ks2[ps]);
                        const uint32_t b0 = bmul(bsub(i2bf2(xb.x, xb.y), kz2[ps]), ks2[ps]);
                        const uint32_t b1 = bmul(bsub(i2bf2(xb.z, xb.w), kz2[ps]), ks2[ps]);
                        ra[ps].x = rope2(a0, ca.x, b0, sa.x, sgA);
                        ra[ps].y = rope2(a1, ca.y, b1, sa.y, sgA);
                        rb[ps].x = rope2(b0, cb.x, a0, sbv.x, sgB);
                        rb[ps].y = rope2(b1, cb.y, a1, sbv.y, sgB);
                    }
                    mma_bf16(cA, ra[0].x, ra[1].x, ra[0].y, ra[1].y, qr[jj].x, qr[jj].y);
                    mma_bf16(cB, rb[0].x, rb[1].x, rb[0].y, rb[1].y, qr[jj + 3].x, qr[jj + 3].y);
                }
                __syncwarp();
                if (lane == 0) mbar_arrive(bar + B_EK + kslot * 8);
                TS_ONCE(2);
                if ((lane & 3) == g)
                    sts64(s + oL + j * (TR * 4),
                          l < 4 ? cA[0] + cB[0] : cA[1] + cB[1], l < 4 ? cA[2] + cB[2] : cA[3] + cB[3]);
                __syncwarp();
                if (lane == 0) mbar_arrive(bar + B_LG + ((batch0 + (j >> 2)) % NBAT) * 8, j == nt - 1 ? 4 - (j & 3) : 1);
                TS(4);
                kslot += NKW;
                if (kslot >= NK) { kslot -= NK; kph ^= 1; }
            }
            j -= nt;
            batch0 += (nt + 3) >> 2;
            __syncwarp();
            if (lane == 0) mbar_arrive(sbar + B_SE);
        }
    } else {
        if (elect_one()) {
            uint64_t pol;
            asm volatile("createpolicy.fractional.L2::evict_first.b64 %0, 1.0;" : "=l"(pol));
            uint32_t kslot = 0, vslot = 0, seg = 0, kph = 1, vph = 1;
            uint32_t win = NV;
            int pend[LEAD];
#pragma unroll
            for (int i = 0; i < LEAD; i++) pend[i] = -1;
            auto push_v = [&](int tile) {
                if (pend[0] >= 0) {
                    const uint32_t b = bar + vslot * 8;
                    mbar_wait(b + B_EV, vph);
                    mbar_expect(b + B_FV, KBYTES);
                    bulk_stream(sb + OFF_V + vslot * KBYTES, p.qv + (size_t)pend[0] * (TR * D), KBYTES, b + B_FV, pol);
                    if (++vslot == NV) { vslot = 0; vph ^= 1; }
                }
#pragma unroll
                for (int i = 0; i + 1 < LEAD; i++) pend[i] = pend[i + 1];
                pend[LEAD - 1] = tile;
            };
            asm volatile("mbarrier.expect_tx.shared::cta.b64 [%0], %1;" ::"r"(bar + B_HDR), "r"(2 * QBYTES) : "memory");
            bulk_plain(sb + OFF_QT, p.qcos, QBYTES, bar + B_HDR);
            bulk_plain(sb + OFF_QT + QBYTES, p.qsin, QBYTES, bar + B_HDR);
            uint32_t c = blockIdx.x;
            TS(1);
            while (c < NCLAIM) {
                const Claim cl = decode_claim(c);
                uint32_t tile = cl.tile0 + cl.off;
                auto tiles = [&](int cnt) {
#pragma unroll 1
                    for (int j = 0; j < cnt; j++, tile += 1u << cl.sh) {
                        push_v(tile);
                        const uint32_t t = sb + kslot * KSLOT, b = bar + kslot * 8;
                        const uint32_t ro = (tile % TPH) * (TR * D);
                        mbar_wait(b + B_EK, kph);
                        mbar_expect(b + B_FK, KSLOT);
                        bulk_stream(t, p.qk + (size_t)tile * (TR * D), KBYTES, b + B_FK, pol);
                        bulk_plain(t + T_C, p.kcos + ro, CBYTES, b + B_FK);
                        bulk_plain(t + T_S, p.ksin + ro, CBYTES, b + B_FK);
                        TS_ONCE(2); TS(3);
                        if (++kslot == NK) { kslot = 0; kph ^= 1; }
                    }
                };
                int nt;
                for (int left = cl.ntiles;; left -= nt) {
                    nt = min(SEGT, left);
                    const bool first = left == cl.ntiles, last = left == nt;
                    const uint32_t s = sb + OFF_SEG + (seg % NSEG) * SEG_BYTES, b = bar + (seg % NSEG) * 8;
                    mbar_wait(b + B_SE, ((seg / NSEG) & 1) ^ 1);
                    sts128(s + S_DESC, cl.head,
                           nt | (first ? F_FIRST : 0) | (last ? F_LAST : 0) | (c >= C_F ? F_FIN : c >= C_S ? F_SEMI : 0),
                           cl.piece, cl.sh | cl.off << 8);
                    const uint32_t scb = nt * TR * 2 << cl.sh;
                    const uint32_t r = (tile - cl.off) * TR;
                    mbar_expect(b + B_HDR, 4 * scb + (first ? QBYTES : 0));
                    if (first) bulk_stream(s + S_Q, p.q + cl.head * D, QBYTES, b + B_HDR, pol);
                    bulk_stream(s + S_SC, p.ks + r, scb, b + B_HDR, pol);
                    bulk_stream(s + S_SC + SCB, p.kz + r, scb, b + B_HDR, pol);
                    bulk_stream(s + S_SC + 2 * SCB, p.vs + r, scb, b + B_HDR, pol);
                    bulk_stream(s + S_SC + 3 * SCB, p.vz + r, scb, b + B_HDR, pol);
                    seg++;
                    tiles(last ? max(nt - LA, 0) : nt);
                    if (last) break;
                }
                const unsigned nx = atomicInc(&g_queue, NCLAIM - 1);
                tiles(min(nt, LA));
                c = gridDim.x + nx;
            }
            TS(4);
#pragma unroll 1
            for (int i = 0; i < LEAD; i++) push_v(-1);
            TS(5);
#pragma unroll 1
            for (int i = 0; i < NGW; i++, seg++) {
                const uint32_t s = sb + OFF_SEG + (seg % NSEG) * SEG_BYTES, b = bar + (seg % NSEG) * 8;
                mbar_wait(b + B_SE, ((seg / NSEG) & 1) ^ 1);
                sts128(s + S_DESC, 0, F_END, 0, 0);
                mbar_arrive(b + B_HDR);
            }
        }
    }
}

}

extern "C" void kernel_launch(void* const* d_in, const int* in_sizes, int n_in, void* d_out, int out_size) {
    (void)in_sizes; (void)n_in; (void)out_size;
    static int sms = 0;
    if (sms == 0) {
        int dev = 0;
        cudaGetDevice(&dev);
        cudaDeviceGetAttribute(&sms, cudaDevAttrMultiProcessorCount, dev);
        cudaFuncSetAttribute(kv_rope_decode_kernel, cudaFuncAttributeMaxDynamicSharedMemorySize, SMEM_BYTES);
    }
    Params p;
    p.q    = (const __nv_bfloat16*)d_in[0];
    p.qk   = (const int*)d_in[1];
    p.ks   = (const __nv_bfloat16*)d_in[2];
    p.kz   = (const __nv_bfloat16*)d_in[3];
    p.qv   = (const int*)d_in[4];
    p.vs   = (const __nv_bfloat16*)d_in[5];
    p.vz   = (const __nv_bfloat16*)d_in[6];
    p.qcos = (const __nv_bfloat16*)d_in[7];
    p.qsin = (const __nv_bfloat16*)d_in[8];
    p.kcos = (const __nv_bfloat16*)d_in[9];
    p.ksin = (const __nv_bfloat16*)d_in[10];
    p.out  = (__nv_bfloat16*)d_out;
    kv_rope_decode_kernel<<<sms, NTHREADS, SMEM_BYTES>>>(p);
}
```

```cpp
#include <cuda_runtime.h>
#include <cuda_bf16.h>
#include <stdint.h>

namespace {

#define CFG_NVW 6
#define CFG_NK 8
#define CFG_NV 4
#define CFG_LEAD 5
#define CFG_MAIN 16
#define CFG_SEMI 0xfdb9
#define CFG_FIN 0x7531
#define CFG_GSH 2
#define EXP_M 0
#define CFG_LA 3
#define CFG_PF0 3

constexpr int D      = 192;
constexpr int SKV    = 2048;
constexpr int NHEAD  = 256;
constexpr int TR     = 8;
constexpr int TPH    = SKV / TR;
constexpr int NKW    = 4;
constexpr int NVW    = CFG_NVW;
constexpr int NB     = 6 / NVW;
constexpr int NGW    = 2;
constexpr int NK     = CFG_NK;
constexpr int NV     = CFG_NV;
constexpr int LEAD   = CFG_LEAD;
constexpr int NSEG   = 8;
constexpr int SEGT   = 16;
constexpr int NBAT   = 16;
constexpr int W_V = NKW, W_PROD = W_V + NVW, W_S = W_PROD + 1, W_G = W_S + 1, NWARPS = W_G + NGW;
constexpr int NTHREADS = NWARPS * 32 + 32;

constexpr int MAINP  = CFG_MAIN;
constexpr int GSH    = CFG_GSH;
constexpr int LA     = CFG_LA;
__host__ __device__ constexpr int semi_size(int h) { return ((CFG_SEMI >> (12 - 4 * (h >> 6))) & 15) + 1; }
__host__ __device__ constexpr int fin_size(int h) { return ((CFG_FIN >> (12 - 4 * (h >> 6))) & 15) + 1; }
constexpr int NM     = (TPH - semi_size(0) - fin_size(0) + MAINP - 1) / MAINP;
constexpr int C_S    = NHEAD * NM, C_F = C_S + NHEAD, NCLAIM = C_F + NHEAD;
constexpr bool sizes_ok(int h) { return h >= NHEAD || (semi_size(h) + fin_size(h) < TPH - (NM - 1) * MAINP && sizes_ok(h + 64)); }
static_assert(sizes_ok(0), "schedule");

constexpr int KBYTES = TR * D * 4;
constexpr int CBYTES = TR * D * 2;
constexpr int QBYTES = D * 2;
constexpr int T_C = KBYTES, T_S = T_C + CBYTES, KSLOT = T_S + CBYTES;
constexpr int SCB = SEGT * TR * 2 << GSH;
static_assert(GSH == 0 || MAINP == SEGT, "interleaved pieces are single segments");
constexpr int S_Q = 0, S_SC = QBYTES, S_DESC = S_SC + 4 * SCB, S_BD = S_DESC + 16,
              S_LG = S_BD + 4 * 16, S_G = S_LG + 2 * SEGT * TR * 4, S_CF = S_G + (D + 4) * 4,
              SEG_BYTES = (S_CF + 16 + 127) / 128 * 128;
constexpr int OFF_V = NK * KSLOT, OFF_SEG = OFF_V + NV * KBYTES, OFF_QT = OFF_SEG + NSEG * SEG_BYTES,
              OFF_TAG = OFF_QT + 2 * QBYTES, OFF_BAR = OFF_TAG + 16;
constexpr int B_FK = 0, B_EK = 64, B_PR = 128, B_HDR = 256, B_GD = 320, B_FC = 384, B_FV = 448, B_LG = 512,
              B_SE = 640, B_EV = 768;
constexpr int SMEM_BYTES = OFF_BAR + 896;
static_assert(NK <= 8 && NV <= 8 && NSEG == 8 && NBAT == 16, "barrier layout");
static_assert(SMEM_BYTES <= 232448 && SMEM_BYTES > 232448 / 2, "smem");
static_assert(NSEG % NGW == 0 && NK % NKW == 0 && NB * NVW == 6 && NM <= 32 && LEAD >= 1, "cfg");
static_assert(LEAD + NV >= 4 && LEAD + NV < NBAT && LEAD < NSEG, "cfg");

__device__ unsigned int g_queue;
constexpr int REC = 200;
__device__ unsigned int g_epoch;
__device__ __align__(32) uint32_t g_mail[NHEAD * (NM + 1) * REC];

__device__ __forceinline__ uint32_t smem_u32(const void* p) { return (uint32_t)__cvta_generic_to_shared(p); }
__device__ __forceinline__ uint32_t pin(uint32_t x) {
    return __shfl_sync(0xffffffffu, x, threadIdx.x & 31);
}
__device__ __forceinline__ bool elect_one() {
    uint32_t pred;
    asm volatile("{\n.reg .pred p;\nelect.sync _|p, 0xffffffff;\nselp.u32 %0, 1, 0, p;\n}" : "=r"(pred));
    return pred;
}
__device__ __forceinline__ void mbar_init(uint32_t bar, uint32_t cnt) {
    asm volatile("mbarrier.init.shared::cta.b64 [%0], %1;" ::"r"(bar), "r"(cnt) : "memory");
}
__device__ __forceinline__ void mbar_expect(uint32_t bar, uint32_t bytes) {
    asm volatile("mbarrier.arrive.expect_tx.shared::cta.b64 _, [%0], %1;" ::"r"(bar), "r"(bytes) : "memory");
}
__device__ __forceinline__ void mbar_arrive(uint32_t bar) {
    asm volatile("mbarrier.arrive.shared::cta.b64 _, [%0];" ::"r"(bar) : "memory");
}
__device__ __forceinline__ void mbar_arrive(uint32_t bar, uint32_t cnt) {
    asm volatile("mbarrier.arrive.shared::cta.b64 _, [%0], %1;" ::"r"(bar), "r"(cnt) : "memory");
}
__device__ __forceinline__ bool mbar_test(uint32_t bar, uint32_t parity) {
    uint32_t ok;
    asm volatile("{\n.reg .pred p;\nmbarrier.test_wait.parity.shared::cta.b64 p, [%1], %2;\nselp.u32 %0, 1, 0, p;\n}"
                 : "=r"(ok) : "r"(bar), "r"(parity) : "memory");
    return ok;
}
__device__ __forceinline__ void mbar_wait(uint32_t bar, uint32_t parity) {
    asm volatile("{\n.reg .pred p;\n.reg .u32 n;\n"
                 "mbarrier.try_wait.parity.shared::cta.b64 p, [%0], %1;\n"
                 "@p bra DONE;\n"
                 "mov.u32 n, 0;\n"
                 "LOOP:\n"
                 "mbarrier.try_wait.parity.shared::cta.b64 p, [%0], %1;\n"
                 "@p bra DONE;\n"
                 "add.u32 n, n, 1;\n"
                 "setp.lt.u32 p, n, 0x400000;\n"
                 "@p bra LOOP;\n"
                 "trap;\n"
                 "DONE:\n}" ::"r"(bar), "r"(parity) : "memory");
}
__device__ __forceinline__ void bulk_stream(uint32_t dst, const void* src, uint32_t bytes, uint32_t bar, uint64_t pol) {
    asm volatile("cp.async.bulk.shared::cluster.global.mbarrier::complete_tx::bytes.L2::cache_hint [%0], [%1], %2, [%3], %4;"
                 ::"r"(dst), "l"(src), "r"(bytes), "r"(bar), "l"(pol) : "memory");
}
__device__ __forceinline__ void bulk_plain(uint32_t dst, const void* src, uint32_t bytes, uint32_t bar) {
    asm volatile("cp.async.bulk.shared::cluster.global.mbarrier::complete_tx::bytes [%0], [%1], %2, [%3];"
                 ::"r"(dst), "l"(src), "r"(bytes), "r"(bar) : "memory");
}
__device__ __forceinline__ void l2_prefetch(const void* src, uint32_t bytes, uint64_t pol) {
    asm volatile("cp.async.bulk.prefetch.L2.global.L2::cache_hint [%0], %1, %2;" ::"l"(src), "r"(bytes), "l"(pol) : "memory");
}
__device__ __forceinline__ void l2_prefetch(const void* src, uint32_t bytes) {
    asm volatile("cp.async.bulk.prefetch.L2.global [%0], %1;" ::"l"(src), "r"(bytes) : "memory");
}
__device__ __forceinline__ int4 lds128(uint32_t a) {
    int4 v;
    asm volatile("ld.shared.v4.s32 {%0,%1,%2,%3}, [%4];" : "=r"(v.x), "=r"(v.y), "=r"(v.z), "=r"(v.w) : "r"(a));
    return v;
}
__device__ __forceinline__ uint2 lds64(uint32_t a) {
    uint2 v;
    asm volatile("ld.shared.v2.u32 {%0,%1}, [%2];" : "=r"(v.x), "=r"(v.y) : "r"(a));
    return v;
}
__device__ __forceinline__ uint32_t lds32(uint32_t a) {
    uint32_t v;
    asm volatile("ld.shared.u32 %0, [%1];" : "=r"(v) : "r"(a));
    return v;
}
__device__ __forceinline__ uint32_t lds16(uint32_t a) {
    uint16_t v;
    asm volatile("ld.shared.u16 %0, [%1];" : "=h"(v) : "r"(a));
    return v;
}
__device__ __forceinline__ void sts32(uint32_t a, float x) {
    asm volatile("st.shared.f32 [%0], %1;" ::"r"(a), "f"(x) : "memory");
}
__device__ __forceinline__ void sts128(uint32_t a, uint32_t x, uint32_t y, uint32_t z, uint32_t w) {
    asm volatile("st.shared.v4.u32 [%0], {%1,%2,%3,%4};" ::"r"(a), "r"(x), "r"(y), "r"(z), "r"(w) : "memory");
}
__device__ __forceinline__ void sts64(uint32_t a, float x, float y) {
    asm volatile("st.shared.v2.f32 [%0], {%1,%2};" ::"r"(a), "f"(x), "f"(y) : "memory");
}
__device__ __forceinline__ float bf_lo(uint32_t v) { return __uint_as_float(v << 16); }
__device__ __forceinline__ float bf_hi(uint32_t v) { return __uint_as_float(v & 0xffff0000u); }
__device__ __forceinline__ float rbf(float x) {
    uint32_t d; asm("cvt.rn.bf16x2.f32 %0, %1, %2;" : "=r"(d) : "f"(x), "f"(0.f)); return __uint_as_float(d);
}
__device__ __forceinline__ float rcp(float x) {
    float y;
    asm("rcp.approx.ftz.f32 %0, %1;" : "=f"(y) : "f"(x));
    return y;
}
__device__ __forceinline__ float lg2(float x) {
    float y;
    asm("lg2.approx.ftz.f32 %0, %1;" : "=f"(y) : "f"(x));
    return y;
}
__device__ __forceinline__ float ex2(float x) {
    float y;
    asm("ex2.approx.ftz.f32 %0, %1;" : "=f"(y) : "f"(x));
    return y;
}
__device__ __forceinline__ uint32_t bmul(uint32_t a, uint32_t b) {
    uint32_t d; asm("mul.rn.bf16x2 %0, %1, %2;" : "=r"(d) : "r"(a), "r"(b)); return d;
}
__device__ __forceinline__ uint32_t bsub(uint32_t a, uint32_t b) {
    uint32_t d; asm("sub.rn.bf16x2 %0, %1, %2;" : "=r"(d) : "r"(a), "r"(b)); return d;
}
__device__ __forceinline__ uint32_t bfma(uint32_t a, uint32_t b, uint32_t c) {
    uint32_t d; asm("fma.rn.bf16x2 %0, %1, %2, %3;" : "=r"(d) : "r"(a), "r"(b), "r"(c)); return d;
}
__device__ __forceinline__ uint32_t i2bf2(int lo, int hi) {
    uint32_t d; asm("cvt.rn.bf16x2.f32 %0, %1, %2;" : "=r"(d) : "f"((float)hi), "f"((float)lo)); return d;
}
__device__ __forceinline__ uint32_t rope2(uint32_t x, uint32_t c, uint32_t y, uint32_t s, uint32_t sg) {
    return bfma(bmul(y, s), sg, bmul(x, c));
}
__device__ __forceinline__ void mma_bf16(float (&c)[4], uint32_t a0, uint32_t a1, uint32_t a2, uint32_t a3,
                                         uint32_t b0, uint32_t b1) {
    asm("mma.sync.aligned.m16n8k16.row.col.f32.bf16.bf16.f32 {%0,%1,%2,%3}, {%4,%5,%6,%7}, {%8,%9}, {%0,%1,%2,%3};"
        : "+f"(c[0]), "+f"(c[1]), "+f"(c[2]), "+f"(c[3])
        : "r"(a0), "r"(a1), "r"(a2), "r"(a3), "r"(b0), "r"(b1));
}
__device__ __forceinline__ void mail_put(uint32_t* p, float x, uint32_t tag) {
    asm volatile("st.relaxed.gpu.global.u32 [%0], %1;" ::"l"(p), "r"((__float_as_uint(x) & ~1u) | tag) : "memory");
}

#define TS(i)
#define TS_ONCE(i)

#define NO_COMPUTE(x) x
#define CVT(x) (float)(x)
struct Claim { uint32_t head, tile0, piece, sh, off; int ntiles; };

__device__ __forceinline__ Claim decode_claim(uint32_t c) {
    Claim cl;
    cl.sh = cl.off = 0;
    if (c < C_S) {
        cl.head = c / NM; cl.piece = c - cl.head * NM; cl.tile0 = cl.head * TPH + cl.piece * MAINP;
        cl.ntiles = cl.piece < NM - 1 ? MAINP : TPH - (NM - 1) * MAINP - semi_size(cl.head) - fin_size(cl.head);
        if (cl.piece < ((NM - 1) >> GSH << GSH)) {
            cl.sh = GSH; cl.off = cl.piece & ((1 << GSH) - 1); cl.tile0 -= cl.off * MAINP;
        }
    } else {
        cl.head = (c - C_S) % NHEAD; cl.piece = NM;
        cl.ntiles = fin_size(cl.head); cl.tile0 = (cl.head + 1) * TPH - cl.ntiles;
        if (c < C_F) { cl.ntiles = semi_size(cl.head); cl.tile0 -= cl.ntiles; }
    }
    return cl;
}

struct Params {
    const int* qk; const __nv_bfloat16* kcos; const __nv_bfloat16* ksin; const int* qv;
    const __nv_bfloat16* ks; const __nv_bfloat16* kz; const __nv_bfloat16* vs; const __nv_bfloat16* vz;
    const __nv_bfloat16* q; const __nv_bfloat16* qcos; const __nv_bfloat16* qsin;
    __nv_bfloat16* out;
};

constexpr float NEG = -3.0e38f;
constexpr float LOG2E = 1.4426950408889634f;
constexpr int F_FIRST = 256, F_LAST = 512, F_SEMI = 1024, F_FIN = 2048, F_SEGEND = 4096, F_END = 8192;

__global__ void __launch_bounds__(NTHREADS, 1)
kv_rope_decode_kernel(const Params p) {
    extern __shared__ __align__(128) unsigned char smem[];
    if (threadIdx.x >= NWARPS * 32 && elect_one()) {
        l2_prefetch(p.kcos + (blockIdx.x % (TPH / 2)) * (2 * TR * D), 2 * CBYTES);
        l2_prefetch(p.ksin + (blockIdx.x % (TPH / 2)) * (2 * TR * D), 2 * CBYTES);
        uint64_t pol;
        asm volatile("createpolicy.fractional.L2::evict_first.b64 %0, 1.0;" : "=l"(pol));
        const uint32_t h = blockIdx.x / NM, pc = blockIdx.x - h * NM;
        const uint32_t off = pc < ((NM - 1) >> GSH << GSH) ? pc & ((1 << GSH) - 1) : 0;
        l2_prefetch(p.qk + (size_t)(h * TPH + (pc - off) * MAINP + off * CFG_PF0) * (TR * D), CFG_PF0 * KBYTES, pol);
    }
    const int w = __shfl_sync(0xffffffffu, threadIdx.x >> 5, 0), lane = threadIdx.x & 31;
    if (w == NWARPS) return;
    const uint32_t sb = __shfl_sync(0xffffffffu, smem_u32(smem), 0);
    const uint32_t bar = sb + OFF_BAR;

    const int grp = w - (w > W_PROD);
    if (grp < 7 && w != W_PROD && elect_one()) {
        const uint32_t cnt = grp == 4 ? 4 : grp == 5 ? NKW + NVW : grp == 6 ? NVW : 1;
#pragma unroll
        for (int i = 0; i < 16; i++) mbar_init(bar + grp * 128 + i * 8, cnt);
        asm volatile("fence.mbarrier_init.release.cluster;" ::: "memory");
    }
    asm volatile("bar.sync 0, %0;" ::"n"(NWARPS * 32) : "memory");

    if ((unsigned)(w - W_V) < NVW) {
        const int v = w - W_V, g = lane >> 3, l = lane & 7;
        const bool up = lane & 16, up2 = lane & 8;
        const uint32_t oV = pin(sb + OFF_V + g * (2 * D * 4) + v * (NB * 128) + l * 16), oP = pin(S_LG + g * 8);
        const uint32_t col = pin(v * (NB * 32) + l * 4 + (up ? 2 : 0) + (up2 ? 1 : 0));
        float acc[4 * NB];
#pragma unroll
        for (int i = 0; i < 4 * NB; i++) acc[i] = 0.f;
        uint32_t vslot = 0, seg = 0, b = 0, vph = 0;
        for (uint32_t batch = 0;; batch++) {
            const uint32_t s = sb + OFF_SEG + (seg % NSEG) * SEG_BYTES, sbar = bar + (seg % NSEG) * 8;
            mbar_wait(bar + B_PR + (batch % NBAT) * 8, (batch / NBAT) & 1);
            const int4 bd = lds128(s + S_BD + b * 16);
            const bool early = mbar_test(sbar + B_FC, (seg / NSEG) & 1);
            bool ready = mbar_test(bar + B_FV + vslot * 8, vph);
            uint32_t pa = s + oP + b * 128;
            uint2 pv = lds64(pa);
            int4 cf = lds128(s + S_CF);
            uint32_t gv[NB];
#pragma unroll
            for (int j = 0; j < NB; j++) gv[j] = lds32(s + S_G + (col + j * 32) * 4);
            if (bd.y & F_END) break;
            TS(3);
            const float alpha = __int_as_float(bd.z);
#pragma unroll
            for (int i = 0; i < 4 * NB; i++) acc[i] *= alpha;
            const int n = bd.y & 255;
#pragma unroll 1
            for (int i = 0; i < n; i++) {
                const float pv0 = __uint_as_float(pv.x), pv1 = __uint_as_float(pv.y);
                const uint32_t t = oV + vslot * KBYTES;
                if (!ready) mbar_wait(bar + B_FV + vslot * 8, vph);
                TS_ONCE(1); TS(5);
                int4 x0[NB], x1[NB];
#pragma unroll
                for (int j = 0; j < NO_COMPUTE(NB); j++) {
                    x0[j] = lds128(t + j * 128);
                    x1[j] = lds128(t + 768 + j * 128);
                }
                __syncwarp();
                if (lane == 0) mbar_arrive(bar + B_EV + vslot * 8);
                if (++vslot == NV) { vslot = 0; vph ^= 1; }
                ready = mbar_test(bar + B_FV + vslot * 8, vph);
                pv = lds64(pa += TR * 4);
#pragma unroll
                for (int j = 0; j < NO_COMPUTE(NB); j++) {
                    acc[j * 4 + 0] = fmaf(pv1, CVT(x1[j].x), fmaf(pv0, CVT(x0[j].x), acc[j * 4 + 0]));
                    acc[j * 4 + 1] = fmaf(pv1, CVT(x1[j].y), fmaf(pv0, CVT(x0[j].y), acc[j * 4 + 1]));
                    acc[j * 4 + 2] = fmaf(pv1, CVT(x1[j].z), fmaf(pv0, CVT(x0[j].z), acc[j * 4 + 2]));
                    acc[j * 4 + 3] = fmaf(pv1, CVT(x1[j].w), fmaf(pv0, CVT(x0[j].w), acc[j * 4 + 3]));
                }
            }
            if (bd.y & F_LAST) {
                float o[NB];
#pragma unroll
                for (int j = 0; j < NB; j++) {
                    const float u0 = (up ? acc[j * 4 + 2] : acc[j * 4 + 0]) + __shfl_xor_sync(0xffffffffu, up ? acc[j * 4 + 0] : acc[j * 4 + 2], 16);
                    const float u1 = (up ? acc[j * 4 + 3] : acc[j * 4 + 1]) + __shfl_xor_sync(0xffffffffu, up ? acc[j * 4 + 1] : acc[j * 4 + 3], 16);
                    o[j] = (up2 ? u1 : u0) + __shfl_xor_sync(0xffffffffu, up2 ? u0 : u1, 8);
                }
                if (!early) {
                    mbar_wait(sbar + B_FC, (seg / NSEG) & 1);
                    cf = lds128(s + S_CF);
#pragma unroll
                    for (int j = 0; j < NB; j++) gv[j] = lds32(s + S_G + (col + j * 32) * 4);
                }
#pragma unroll
                for (int j = 0; j < NB; j++) {
                    const float gj = (bd.y & (F_SEMI | F_FIN)) ? __uint_as_float(gv[j]) : 0.f;
                    o[j] = fmaf(o[j], __int_as_float(cf.x), fmaf(gj, __int_as_float(cf.y), __int_as_float(cf.z)));
                }
                if (bd.y & F_FIN) {
#pragma unroll
                    for (int j = 0; j < NB; j++) p.out[bd.x + col + j * 32] = __float2bfloat16_rn(o[j]);
                } else {
#pragma unroll
                    for (int j = 0; j < NB; j++) mail_put(g_mail + (bd.x + col + j * 32), o[j], cf.w & 1);
                    if (col < REC - D) mail_put(g_mail + (bd.x + D + col), __int_as_float(cf.w), cf.w & 1);
                }
#pragma unroll
                for (int i = 0; i < 4 * NB; i++) acc[i] = 0.f;
            }
            b++;
            if (bd.y & F_SEGEND) {
                if (!(bd.y & F_LAST)) mbar_wait(sbar + B_FC, (seg / NSEG) & 1);
                __syncwarp();
                if (lane == 0) mbar_arrive(sbar + B_SE);
                seg++; b = 0;
            }
            TS(6);
        }
    } else if (w == W_S) {
        float m = NEG, lsum = 0.f, corr = 0.f;
        uint32_t batch = 0;
        for (uint32_t seg = 0;; seg++) {
            const uint32_t s = sb + OFF_SEG + (seg % NSEG) * SEG_BYTES, sbar = bar + (seg % NSEG) * 8;
            const uint32_t sph = (seg / NSEG) & 1;
            mbar_wait(sbar + B_HDR, sph);
            const int4 desc = lds128(s + S_DESC);
            if (desc.y & F_END) {
                if (lane == 0) {
                    sts128(s + S_BD, 0, F_END, 0, 0);
                    mbar_arrive(bar + B_PR + (batch % NBAT) * 8);
                }
                break;
            }
            if (desc.y & F_FIRST) { m = NEG; lsum = 0.f; corr = 0.f; }
            const int index = (desc.y & F_FIN) ? desc.x * D : (desc.x * (NM + 1) + desc.z) * REC;
            int b = 0;
            for (int left = desc.y & 255; left > 0; left -= 4, b++, batch++) {
                const bool valid = lane < left * TR;
                const uint32_t sc = s + S_SC + ((((b * 4 + (lane >> 3)) << (desc.w & 255)) + (desc.w >> 8)) * TR + (lane & 7)) * 2;
                const float vs = bf_lo(lds16(sc + 2 * SCB)), vz = bf_lo(lds16(sc + 3 * SCB));
                mbar_wait(bar + B_LG + (batch % NBAT) * 8, (batch / NBAT) & 1);
                const float dot = __uint_as_float(lds32(s + S_LG + (b * 32 + lane) * 4)) +
                                  __uint_as_float(lds32(s + S_LG + SEGT * TR * 4 + (b * 32 + lane) * 4));
                const float sv = rbf(rbf(dot) * 0.07216878364870322f) * LOG2E;
                int key = __float_as_int(fmaxf(m, valid ? sv : m));
                key ^= (key >> 31) & 0x7fffffff;
                key = __reduce_max_sync(0xffffffffu, key);
                const float mn = __int_as_float(key ^ ((key >> 31) & 0x7fffffff));
                const float alpha = ex2(m - mn), pr = ex2(sv - mn), pv = pr * vs;
                m = mn;
                sts32(s + S_LG + (b * 32 + lane) * 4, pv);
                if (lane == 0)
                    sts128(s + S_BD + b * 16, index, left > 4 ? 4 : (left | F_SEGEND | (desc.y & (F_LAST | F_SEMI | F_FIN))),
                           __float_as_uint(alpha), 0);
                __syncwarp();
                if (lane == 0) mbar_arrive(bar + B_PR + (batch % NBAT) * 8);
                lsum = fmaf(lsum, alpha, valid ? pr : 0.f);
                corr = fmaf(corr, alpha, valid ? pv * vz : 0.f);
                TS(3);
            }
            float L = lsum, C = corr;
            if (desc.y & F_LAST) {
#pragma unroll
                for (int o = 16; o > 0; o >>= 1) {
                    L += __shfl_xor_sync(0xffffffffu, L, o);
                    C += __shfl_xor_sync(0xffffffffu, C, o);
                }
            }
            mbar_wait(sbar + B_GD, sph);
            if (desc.y & F_LAST) {
                const uint32_t tag = lds32(sb + OFF_TAG);
                const float gl = (desc.y & (F_SEMI | F_FIN)) ? __uint_as_float(lds32(s + S_G + D * 4)) : -3.4e38f;
                const float M = fmaxf(m, gl), e = ex2(m - M), a = ex2(gl - M);
                const float W = fmaf(L, e, a), inv = rcp(W);
                if (lane == 0)
                    sts128(s + S_CF, __float_as_uint(e * inv), __float_as_uint(a * inv), __float_as_uint(-C * e * inv),
                           (__float_as_uint(M + lg2(W)) & ~1u) | tag);
            }
            __syncwarp();
            if (lane == 0) mbar_arrive(sbar + B_FC);
            TS(4);
        }
    } else if ((unsigned)(w - W_G) < NGW) {
        if (w == W_G) {
            if (lane == 0) sts32(sb + OFF_TAG, __uint_as_float(~*(volatile unsigned int*)&g_epoch & 1));
        } else {
            mbar_wait(bar + B_GD, 0);
        }
        for (uint32_t seg = w - W_G;; seg += NGW) {
            const uint32_t s = sb + OFF_SEG + (seg % NSEG) * SEG_BYTES, sbar = bar + (seg % NSEG) * 8;
            mbar_wait(sbar + B_HDR, (seg / NSEG) & 1);
            const int4 desc = lds128(s + S_DESC);
            if (desc.y & F_END) break;
            TS(1);
            if (desc.y & (EXP_M == 6 ? F_FIN : EXP_M == 7 ? F_SEMI : F_SEMI | F_FIN)) {
                const uint32_t tag = lds32(sb + OFF_TAG);
                const int cnt = (desc.y & F_FIN) ? 1 : NM;
                const uint32_t* mail = g_mail + (desc.x * (NM + 1) + ((desc.y & F_FIN) ? NM : 0)) * REC;
                float M = NEG, W = 0.f, O[6] = {0.f, 0.f, 0.f, 0.f, 0.f, 0.f};
#pragma unroll 1
                for (int i0 = 0; i0 < cnt; i0 += 5, mail += 5 * REC) {
                    uint2 pk[15];
                    uint32_t ls[5], stale;
                    int it = 0;
                    do {
                        stale = 0;
#pragma unroll
                        for (int i = 0; i < 5; i++) {
                            ls[i] = 0xff7ffffeu | tag;
                            pk[3 * i] = pk[3 * i + 1] = pk[3 * i + 2] = make_uint2(tag, tag);
                            if (i0 + i < cnt) {
                                asm volatile("ld.relaxed.gpu.global.u32 %0, [%1];" : "=r"(ls[i]) : "l"(mail + i * REC + D) : "memory");
#pragma unroll
                                for (int k = 0; k < 3; k++)
                                    asm volatile("ld.relaxed.gpu.global.v2.u32 {%0,%1}, [%2];"
                                                 : "=r"(pk[3 * i + k].x), "=r"(pk[3 * i + k].y)
                                                 : "l"(mail + i * REC + k * 64 + lane * 2) : "memory");
                            }
                        }
#pragma unroll
                        for (int i = 0; i < 5; i++) stale |= ls[i] ^ tag;
#pragma unroll
                        for (int i = 0; i < 15; i++) stale |= (pk[i].x ^ tag) | (pk[i].y ^ tag);
                        if (++it > (1 << 22)) __trap();
                    } while ((stale & 1) && EXP_M != 5 && !(EXP_M == 8 && (desc.y & F_FIN)) && !(EXP_M == 9 && (desc.y & F_SEMI)));
                    float Mn = M;
#pragma unroll
                    for (int i = 0; i < 5; i++) Mn = fmaxf(Mn, __uint_as_float(ls[i]));
                    const float a = ex2(M - Mn);
                    M = Mn; W *= a;
#pragma unroll
                    for (int i = 0; i < 6; i++) O[i] *= a;
#pragma unroll
                    for (int i = 0; i < 5; i++) {
                        const float e = ex2(__uint_as_float(ls[i]) - M);
                        W += e;
#pragma unroll
                        for (int k = 0; k < 3; k++) {
                            O[2 * k] = fmaf(e, __uint_as_float(pk[3 * i + k].x), O[2 * k]);
                            O[2 * k + 1] = fmaf(e, __uint_as_float(pk[3 * i + k].y), O[2 * k + 1]);
                        }
                    }
                }
                const float inv = rcp(W);
#pragma unroll
                for (int k = 0; k < 3; k++) sts64(s + S_G + k * 256 + lane * 8, O[2 * k] * inv, O[2 * k + 1] * inv);
                if (lane == 0) sts32(s + S_G + D * 4, M + lg2(W));
            }
            __syncwarp();
            if (lane == 0) mbar_arrive(sbar + B_GD);
            TS(2);
        }
    } else if ((w >> 2) == 0) {
        const int g = lane >> 3, l = lane & 7, godd = g & 1;
        const uint32_t sgA = pin(godd ? 0x3f803f80u : 0xbf80bf80u), sgB = pin(godd ? 0xbf80bf80u : 0x3f803f80u);
        const uint32_t oKA = pin(sb + g * (2 * D * 4) + l * 16 + godd * 384), oKB = pin(oKA - godd * 768 + 384);
        const uint32_t oCA = pin(sb + T_C + g * (2 * D * 2) + l * 8 + godd * 192), oCB = pin(oCA - godd * 384 + 192);
        const uint32_t oL = pin(S_LG + (l >> 2) * (SEGT * TR * 4) + g * 8);
        uint2 qr[6];
        uint32_t kslot = w, j = kslot, batch0 = 0, kph = 0;
        for (uint32_t seg = 0;; seg++) {
            const uint32_t s = sb + OFF_SEG + (seg % NSEG) * SEG_BYTES, sbar = bar + (seg % NSEG) * 8;
            mbar_wait(sbar + B_HDR, (seg / NSEG) & 1);
            const uint32_t desc = lds32(s + S_DESC + 4), geo = lds32(s + S_DESC + 12);
            if (desc & F_END) break;
            const uint32_t nt = desc & 255;
            if (desc & F_FIRST) {
#pragma unroll
                for (int i = 0; i < 3; i++) {
                    const uint32_t oa = l * 8 + godd * 192 + i * 64, ob = oa + 192 - godd * 384;
                    const uint2 a = lds64(s + S_Q + oa), b = lds64(s + S_Q + ob);
                    const uint2 ca = lds64(sb + OFF_QT + oa), cb = lds64(sb + OFF_QT + ob);
                    const uint2 sa = lds64(sb + OFF_QT + QBYTES + oa), sbv = lds64(sb + OFF_QT + QBYTES + ob);
                    qr[i].x = rope2(a.x, ca.x, b.x, sa.x, sgA);
                    qr[i].y = rope2(a.y, ca.y, b.y, sa.y, sgA);
                    qr[i + 3].x = rope2(b.x, cb.x, a.x, sbv.x, sgB);
                    qr[i + 3].y = rope2(b.y, cb.y, a.y, sbv.y, sgB);
                }
            }
            for (; j < nt; j += NKW) {
                const uint32_t t = kslot * KSLOT;
                const uint32_t sc = s + S_SC + ((j << (geo & 255)) + (geo >> 8)) * (TR * 2) + g * 4;
                const uint32_t sks = lds32(sc), skz = lds32(sc + SCB);
                const uint32_t ks2[2] = {__byte_perm(sks, 0, 0x1010), __byte_perm(sks, 0, 0x3232)};
                const uint32_t kz2[2] = {__byte_perm(skz, 0, 0x1010), __byte_perm(skz, 0, 0x3232)};
                mbar_wait(bar + B_FK + kslot * 8, kph);
                TS_ONCE(1); TS(3);
                float cA[4] = {0.f, 0.f, 0.f, 0.f}, cB[4] = {0.f, 0.f, 0.f, 0.f};
#pragma unroll
                for (int jj = 0; jj < NO_COMPUTE(3); jj++) {
                    uint2 ra[2], rb[2];
#pragma unroll
                    for (int ps = 0; ps < 2; ps++) {
                        const int4 xa = lds128(t + oKA + ps * 768 + jj * 128);
                        const int4 xb = lds128(t + oKB + ps * 768 + jj * 128);
                        const uint2 ca = lds64(t + oCA + ps * 384 + jj * 64);
                        const uint2 cb = lds64(t + oCB + ps * 384 + jj * 64);
                        const uint2 sa = lds64(t + oCA + CBYTES + ps * 384 + jj * 64);
                        const uint2 sbv = lds64(t + oCB + CBYTES + ps * 384 + jj * 64);
                        const uint32_t a0 = bmul(bsub(i2bf2(xa.x, xa.y), kz2[ps]), ks2[ps]);
                        const uint32_t a1 = bmul(bsub(i2bf2(xa.z, xa.w), kz2[ps]), ks2[ps]);
                        const uint32_t b0 = bmul(bsub(i2bf2(xb.x, xb.y), kz2[ps]), ks2[ps]);
                        const uint32_t b1 = bmul(bsub(i2bf2(xb.z, xb.w), kz2[ps]), ks2[ps]);
                        ra[ps].x = rope2(a0, ca.x, b0, sa.x, sgA);
                        ra[ps].y = rope2(a1, ca.y, b1, sa.y, sgA);
                        rb[ps].x = rope2(b0, cb.x, a0, sbv.x, sgB);
                        rb[ps].y = rope2(b1, cb.y, a1, sbv.y, sgB);
                    }
                    mma_bf16(cA, ra[0].x, ra[1].x, ra[0].y, ra[1].y, qr[jj].x, qr[jj].y);
                    mma_bf16(cB, rb[0].x, rb[1].x, rb[0].y, rb[1].y, qr[jj + 3].x, qr[jj + 3].y);
                }
                __syncwarp();
                if (lane == 0) mbar_arrive(bar + B_EK + kslot * 8);
                TS_ONCE(2);
                if ((lane & 3) == g)
                    sts64(s + oL + j * (TR * 4),
                          l < 4 ? cA[0] + cB[0] : cA[1] + cB[1], l < 4 ? cA[2] + cB[2] : cA[3] + cB[3]);
                __syncwarp();
                if (lane == 0) mbar_arrive(bar + B_LG + ((batch0 + (j >> 2)) % NBAT) * 8, j == nt - 1 ? 4 - (j & 3) : 1);
                TS(4);
                kslot += NKW;
                if (kslot >= NK) { kslot -= NK; kph ^= 1; }
            }
            j -= nt;
            batch0 += (nt + 3) >> 2;
            __syncwarp();
            if (lane == 0) mbar_arrive(sbar + B_SE);
        }
    } else {
        if (elect_one()) {
            uint64_t pol;
            asm volatile("createpolicy.fractional.L2::evict_first.b64 %0, 1.0;" : "=l"(pol));
            uint32_t kslot = 0, vslot = 0, seg = 0, kph = 1, vph = 1;
            uint32_t win = NV;
            int pend[LEAD];
#pragma unroll
            for (int i = 0; i < LEAD; i++) pend[i] = -1;
            auto push_v = [&](int tile) {
                if (pend[0] >= 0) {
                    const uint32_t b = bar + vslot * 8;
                    mbar_wait(b + B_EV, vph);
                    mbar_expect(b + B_FV, KBYTES);
                    bulk_stream(sb + OFF_V + vslot * KBYTES, p.qv + (size_t)pend[0] * (TR * D), KBYTES, b + B_FV, pol);
                    if (++vslot == NV) { vslot = 0; vph ^= 1; }
                }
#pragma unroll
                for (int i = 0; i + 1 < LEAD; i++) pend[i] = pend[i + 1];
                pend[LEAD - 1] = tile;
            };
            asm volatile("mbarrier.expect_tx.shared::cta.b64 [%0], %1;" ::"r"(bar + B_HDR), "r"(2 * QBYTES) : "memory");
            bulk_plain(sb + OFF_QT, p.qcos, QBYTES, bar + B_HDR);
            bulk_plain(sb + OFF_QT + QBYTES, p.qsin, QBYTES, bar + B_HDR);
            uint32_t c = blockIdx.x;
            TS(1);
            while (c < NCLAIM) {
                const Claim cl = decode_claim(c);
                uint32_t tile = cl.tile0 + cl.off;
                auto tiles = [&](int cnt) {
#pragma unroll 1
                    for (int j = 0; j < cnt; j++, tile += 1u << cl.sh) {
                        push_v(tile);
                        const uint32_t t = sb + kslot * KSLOT, b = bar + kslot * 8;
                        const uint32_t ro = (tile % TPH) * (TR * D);
                        mbar_wait(b + B_EK, kph);
                        mbar_expect(b + B_FK, KSLOT);
                        bulk_stream(t, p.qk + (size_t)tile * (TR * D), KBYTES, b + B_FK, pol);
                        bulk_plain(t + T_C, p.kcos + ro, CBYTES, b + B_FK);
                        bulk_plain(t + T_S, p.ksin + ro, CBYTES, b + B_FK);
                        TS_ONCE(2); TS(3);
                        if (++kslot == NK) { kslot = 0; kph ^= 1; }
                    }
                };
                int nt;
                for (int left = cl.ntiles;; left -= nt) {
                    nt = min(SEGT, left);
                    const bool first = left == cl.ntiles, last = left == nt;
                    const uint32_t s = sb + OFF_SEG + (seg % NSEG) * SEG_BYTES, b = bar + (seg % NSEG) * 8;
                    mbar_wait(b + B_SE, ((seg / NSEG) & 1) ^ 1);
                    sts128(s + S_DESC, cl.head,
                           nt | (first ? F_FIRST : 0) | (last ? F_LAST : 0) | (c >= C_F ? F_FIN : c >= C_S ? F_SEMI : 0),
                           cl.piece, cl.sh | cl.off << 8);
                    const uint32_t scb = nt * TR * 2 << cl.sh;
                    const uint32_t r = (tile - cl.off) * TR;
                    mbar_expect(b + B_HDR, 4 * scb + (first ? QBYTES : 0));
                    if (first) bulk_stream(s + S_Q, p.q + cl.head * D, QBYTES, b + B_HDR, pol);
                    bulk_stream(s + S_SC, p.ks + r, scb, b + B_HDR, pol);
                    bulk_stream(s + S_SC + SCB, p.kz + r, scb, b + B_HDR, pol);
                    bulk_stream(s + S_SC + 2 * SCB, p.vs + r, scb, b + B_HDR, pol);
                    bulk_stream(s + S_SC + 3 * SCB, p.vz + r, scb, b + B_HDR, pol);
                    seg++;
                    tiles(last ? max(nt - LA, 0) : nt);
                    if (last) break;
                }
                if (c == blockIdx.x) mbar_wait(bar + B_GD, 0);
                const unsigned nx = atomicInc(&g_queue, NCLAIM - 1);
                tiles(min(nt, LA));
                if (nx == NCLAIM - 1) g_epoch = lds32(sb + OFF_TAG);
                c = gridDim.x + nx;
            }
            TS(4);
#pragma unroll 1
            for (int i = 0; i < LEAD; i++) push_v(-1);
            TS(5);
#pragma unroll 1
            for (int i = 0; i < NGW; i++, seg++) {
                const uint32_t s = sb + OFF_SEG + (seg % NSEG) * SEG_BYTES, b = bar + (seg % NSEG) * 8;
                mbar_wait(b + B_SE, ((seg / NSEG) & 1) ^ 1);
                sts128(s + S_DESC, 0, F_END, 0, 0);
                mbar_arrive(b + B_HDR);
            }
        }
    }
}

}

extern "C" void kernel_launch(void* const* d_in, const int* in_sizes, int n_in, void* d_out, int out_size) {
    (void)in_sizes; (void)n_in; (void)out_size;
    static int sms = 0;
    if (sms == 0) {
        int dev = 0;
        cudaGetDevice(&dev);
        cudaDeviceGetAttribute(&sms, cudaDevAttrMultiProcessorCount, dev);
        cudaFuncSetAttribute(kv_rope_decode_kernel, cudaFuncAttributeMaxDynamicSharedMemorySize, SMEM_BYTES);
    }
    Params p;
    p.q    = (const __nv_bfloat16*)d_in[0];
    p.qk   = (const int*)d_in[1];
    p.ks   = (const __nv_bfloat16*)d_in[2];
    p.kz   = (const __nv_bfloat16*)d_in[3];
    p.qv   = (const int*)d_in[4];
    p.vs   = (const __nv_bfloat16*)d_in[5];
    p.vz   = (const __nv_bfloat16*)d_in[6];
    p.qcos = (const __nv_bfloat16*)d_in[7];
    p.qsin = (const __nv_bfloat16*)d_in[8];
    p.kcos = (const __nv_bfloat16*)d_in[9];
    p.ksin = (const __nv_bfloat16*)d_in[10];
    p.out  = (__nv_bfloat16*)d_out;
    kv_rope_decode_kernel<<<sms, NTHREADS, SMEM_BYTES>>>(p);
}
```

```cpp
#include <cuda_runtime.h>
#include <cuda_bf16.h>
#include <stdint.h>

namespace {

#define CFG_NVW 6
#define CFG_NK 8
#define CFG_NV 4
#define CFG_LEAD 5
#define CFG_MAIN 16
#define CFG_SEMI 0xfdb9
#define CFG_FIN 0x7531
#define CFG_GSH 2
#define CFG_LA 3
#define CFG_PF0 3

constexpr int D      = 192;
constexpr int SKV    = 2048;
constexpr int NHEAD  = 256;
constexpr int TR     = 8;
constexpr int TPH    = SKV / TR;
constexpr int NKW    = 4;
constexpr int NVW    = CFG_NVW;
constexpr int NB     = 6 / NVW;
constexpr int NGW    = 2;
constexpr int NK     = CFG_NK;
constexpr int NV     = CFG_NV;
constexpr int LEAD   = CFG_LEAD;
constexpr int NSEG   = 8;
constexpr int SEGT   = 16;
constexpr int NBAT   = 16;
constexpr int W_V = NKW, W_PROD = W_V + NVW, W_S = W_PROD + 1, W_G = W_S + 1, NWARPS = W_G + NGW;
constexpr int NTHREADS = NWARPS * 32 + 32;

constexpr int MAINP  = CFG_MAIN;
constexpr int GSH    = CFG_GSH;
constexpr int LA     = CFG_LA;
__host__ __device__ constexpr int semi_size(int h) { return ((CFG_SEMI >> (12 - 4 * (h >> 6))) & 15) + 1; }
__host__ __device__ constexpr int fin_size(int h) { return ((CFG_FIN >> (12 - 4 * (h >> 6))) & 15) + 1; }
constexpr int NM     = (TPH - semi_size(0) - fin_size(0) + MAINP - 1) / MAINP;
constexpr int C_S    = NHEAD * NM, C_F = C_S + NHEAD, NCLAIM = C_F + NHEAD;
constexpr bool sizes_ok(int h) { return h >= NHEAD || (semi_size(h) + fin_size(h) < TPH - (NM - 1) * MAINP && sizes_ok(h + 64)); }
static_assert(sizes_ok(0), "schedule");

constexpr int KBYTES = TR * D * 4;
constexpr int CBYTES = TR * D * 2;
constexpr int QBYTES = D * 2;
constexpr int T_C = KBYTES, T_S = T_C + CBYTES, KSLOT = T_S + CBYTES;
constexpr int SCB = SEGT * TR * 2 << GSH;
static_assert(GSH == 0 || MAINP == SEGT, "interleaved pieces are single segments");
constexpr int S_Q = 0, S_SC = QBYTES, S_DESC = S_SC + 4 * SCB, S_BD = S_DESC + 16,
              S_LG = S_BD + 4 * 16, S_G = S_LG + 2 * SEGT * TR * 4, S_CF = S_G + (D + 4) * 4,
              SEG_BYTES = (S_CF + 16 + 127) / 128 * 128;
constexpr int OFF_V = NK * KSLOT, OFF_SEG = OFF_V + NV * KBYTES, OFF_QT = OFF_SEG + NSEG * SEG_BYTES,
              OFF_TAG = OFF_QT + 2 * QBYTES, OFF_BAR = OFF_TAG + 16;
constexpr int B_FK = 0, B_EK = 64, B_PR = 128, B_HDR = 256, B_GD = 320, B_FC = 384, B_FV = 448, B_LG = 512,
              B_SE = 640, B_EV = 768;
constexpr int SMEM_BYTES = OFF_BAR + 896;
static_assert(NK <= 8 && NV <= 8 && NSEG == 8 && NBAT == 16, "barrier layout");
static_assert(SMEM_BYTES <= 232448 && SMEM_BYTES > 232448 / 2, "smem");
static_assert(NSEG % NGW == 0 && NK % NKW == 0 && NB * NVW == 6 && NM <= 32 && LEAD >= 1, "cfg");
static_assert(LEAD + NV >= 4 && LEAD + NV < NBAT && LEAD < NSEG, "cfg");

__device__ unsigned int g_queue;
constexpr int REC = 200;
__device__ unsigned int g_epoch;
__device__ __align__(32) uint32_t g_mail[NHEAD * NM * REC];

__device__ __forceinline__ uint32_t smem_u32(const void* p) { return (uint32_t)__cvta_generic_to_shared(p); }
__device__ __forceinline__ uint32_t pin(uint32_t x) {
    return __shfl_sync(0xffffffffu, x, threadIdx.x & 31);
}
__device__ __forceinline__ bool elect_one() {
    uint32_t pred;
    asm volatile("{\n.reg .pred p;\nelect.sync _|p, 0xffffffff;\nselp.u32 %0, 1, 0, p;\n}" : "=r"(pred));
    return pred;
}
__device__ __forceinline__ void mbar_init(uint32_t bar, uint32_t cnt) {
    asm volatile("mbarrier.init.shared::cta.b64 [%0], %1;" ::"r"(bar), "r"(cnt) : "memory");
}
__device__ __forceinline__ void mbar_expect(uint32_t bar, uint32_t bytes) {
    asm volatile("mbarrier.arrive.expect_tx.shared::cta.b64 _, [%0], %1;" ::"r"(bar), "r"(bytes) : "memory");
}
__device__ __forceinline__ void mbar_arrive(uint32_t bar) {
    asm volatile("mbarrier.arrive.shared::cta.b64 _, [%0];" ::"r"(bar) : "memory");
}
__device__ __forceinline__ void mbar_arrive(uint32_t bar, uint32_t cnt) {
    asm volatile("mbarrier.arrive.shared::cta.b64 _, [%0], %1;" ::"r"(bar), "r"(cnt) : "memory");
}
__device__ __forceinline__ bool mbar_test(uint32_t bar, uint32_t parity) {
    uint32_t ok;
    asm volatile("{\n.reg .pred p;\nmbarrier.test_wait.parity.shared::cta.b64 p, [%1], %2;\nselp.u32 %0, 1, 0, p;\n}"
                 : "=r"(ok) : "r"(bar), "r"(parity) : "memory");
    return ok;
}
__device__ __forceinline__ void mbar_wait(uint32_t bar, uint32_t parity) {
    asm volatile("{\n.reg .pred p;\n.reg .u32 n;\n"
                 "mbarrier.try_wait.parity.shared::cta.b64 p, [%0], %1;\n"
                 "@p bra DONE;\n"
                 "mov.u32 n, 0;\n"
                 "LOOP:\n"
                 "mbarrier.try_wait.parity.shared::cta.b64 p, [%0], %1;\n"
                 "@p bra DONE;\n"
                 "add.u32 n, n, 1;\n"
                 "setp.lt.u32 p, n, 0x400000;\n"
                 "@p bra LOOP;\n"
                 "trap;\n"
                 "DONE:\n}" ::"r"(bar), "r"(parity) : "memory");
}
__device__ __forceinline__ void bulk_stream(uint32_t dst, const void* src, uint32_t bytes, uint32_t bar, uint64_t pol) {
    asm volatile("cp.async.bulk.shared::cluster.global.mbarrier::complete_tx::bytes.L2::cache_hint [%0], [%1], %2, [%3], %4;"
                 ::"r"(dst), "l"(src), "r"(bytes), "r"(bar), "l"(pol) : "memory");
}
__device__ __forceinline__ void bulk_plain(uint32_t dst, const void* src, uint32_t bytes, uint32_t bar) {
    asm volatile("cp.async.bulk.shared::cluster.global.mbarrier::complete_tx::bytes [%0], [%1], %2, [%3];"
                 ::"r"(dst), "l"(src), "r"(bytes), "r"(bar) : "memory");
}
__device__ __forceinline__ void l2_prefetch(const void* src, uint32_t bytes, uint64_t pol) {
    asm volatile("cp.async.bulk.prefetch.L2.global.L2::cache_hint [%0], %1, %2;" ::"l"(src), "r"(bytes), "l"(pol) : "memory");
}
__device__ __forceinline__ void l2_prefetch(const void* src, uint32_t bytes) {
    asm volatile("cp.async.bulk.prefetch.L2.global [%0], %1;" ::"l"(src), "r"(bytes) : "memory");
}
__device__ __forceinline__ int4 lds128(uint32_t a) {
    int4 v;
    asm volatile("ld.shared.v4.s32 {%0,%1,%2,%3}, [%4];" : "=r"(v.x), "=r"(v.y), "=r"(v.z), "=r"(v.w) : "r"(a));
    return v;
}
__device__ __forceinline__ uint2 lds64(uint32_t a) {
    uint2 v;
    asm volatile("ld.shared.v2.u32 {%0,%1}, [%2];" : "=r"(v.x), "=r"(v.y) : "r"(a));
    return v;
}
__device__ __forceinline__ uint32_t lds32(uint32_t a) {
    uint32_t v;
    asm volatile("ld.shared.u32 %0, [%1];" : "=r"(v) : "r"(a));
    return v;
}
__device__ __forceinline__ uint32_t lds16(uint32_t a) {
    uint16_t v;
    asm volatile("ld.shared.u16 %0, [%1];" : "=h"(v) : "r"(a));
    return v;
}
__device__ __forceinline__ void sts32(uint32_t a, float x) {
    asm volatile("st.shared.f32 [%0], %1;" ::"r"(a), "f"(x) : "memory");
}
__device__ __forceinline__ void sts128(uint32_t a, uint32_t x, uint32_t y, uint32_t z, uint32_t w) {
    asm volatile("st.shared.v4.u32 [%0], {%1,%2,%3,%4};" ::"r"(a), "r"(x), "r"(y), "r"(z), "r"(w) : "memory");
}
__device__ __forceinline__ void sts64(uint32_t a, float x, float y) {
    asm volatile("st.shared.v2.f32 [%0], {%1,%2};" ::"r"(a), "f"(x), "f"(y) : "memory");
}
__device__ __forceinline__ float bf_lo(uint32_t v) { return __uint_as_float(v << 16); }
__device__ __forceinline__ float bf_hi(uint32_t v) { return __uint_as_float(v & 0xffff0000u); }
__device__ __forceinline__ float rbf(float x) {
    uint32_t d; asm("cvt.rn.bf16x2.f32 %0, %1, %2;" : "=r"(d) : "f"(x), "f"(0.f)); return __uint_as_float(d);
}
__device__ __forceinline__ float rcp(float x) {
    float y;
    asm("rcp.approx.ftz.f32 %0, %1;" : "=f"(y) : "f"(x));
    return y;
}
__device__ __forceinline__ float lg2(float x) {
    float y;
    asm("lg2.approx.ftz.f32 %0, %1;" : "=f"(y) : "f"(x));
    return y;
}
__device__ __forceinline__ float ex2(float x) {
    float y;
    asm("ex2.approx.ftz.f32 %0, %1;" : "=f"(y) : "f"(x));
    return y;
}
__device__ __forceinline__ uint32_t bmul(uint32_t a, uint32_t b) {
    uint32_t d; asm("mul.rn.bf16x2 %0, %1, %2;" : "=r"(d) : "r"(a), "r"(b)); return d;
}
__device__ __forceinline__ uint32_t bsub(uint32_t a, uint32_t b) {
    uint32_t d; asm("sub.rn.bf16x2 %0, %1, %2;" : "=r"(d) : "r"(a), "r"(b)); return d;
}
__device__ __forceinline__ uint32_t bfma(uint32_t a, uint32_t b, uint32_t c) {
    uint32_t d; asm("fma.rn.bf16x2 %0, %1, %2, %3;" : "=r"(d) : "r"(a), "r"(b), "r"(c)); return d;
}
__device__ __forceinline__ uint32_t i2bf2(int lo, int hi) {
    uint32_t d; asm("cvt.rn.bf16x2.f32 %0, %1, %2;" : "=r"(d) : "f"((float)hi), "f"((float)lo)); return d;
}
__device__ __forceinline__ uint32_t rope2(uint32_t x, uint32_t c, uint32_t y, uint32_t s, uint32_t sg) {
    return bfma(bmul(y, s), sg, bmul(x, c));
}
__device__ __forceinline__ void mma_bf16(float (&c)[4], uint32_t a0, uint32_t a1, uint32_t a2, uint32_t a3,
                                         uint32_t b0, uint32_t b1) {
    asm("mma.sync.aligned.m16n8k16.row.col.f32.bf16.bf16.f32 {%0,%1,%2,%3}, {%4,%5,%6,%7}, {%8,%9}, {%0,%1,%2,%3};"
        : "+f"(c[0]), "+f"(c[1]), "+f"(c[2]), "+f"(c[3])
        : "r"(a0), "r"(a1), "r"(a2), "r"(a3), "r"(b0), "r"(b1));
}
__device__ __forceinline__ void mail_put(uint32_t* p, float x, uint32_t tag) {
    asm volatile("st.relaxed.gpu.global.u32 [%0], %1;" ::"l"(p), "r"((__float_as_uint(x) & ~3u) | tag) : "memory");
}

#define TS(i)
#define TS_ONCE(i)

#define NO_COMPUTE(x) x
#define CVT(x) (float)(x)
struct Claim { uint32_t head, tile0, piece, sh, off; int ntiles; };

__device__ __forceinline__ Claim decode_claim(uint32_t c) {
    Claim cl;
    cl.sh = cl.off = 0;
    if (c < C_S) {
        cl.head = c / NM; cl.piece = c - cl.head * NM; cl.tile0 = cl.head * TPH + cl.piece * MAINP;
        cl.ntiles = cl.piece < NM - 1 ? MAINP : TPH - (NM - 1) * MAINP - semi_size(cl.head) - fin_size(cl.head);
        if (cl.piece < ((NM - 1) >> GSH << GSH)) {
            cl.sh = GSH; cl.off = cl.piece & ((1 << GSH) - 1); cl.tile0 -= cl.off * MAINP;
        }
    } else {
        cl.head = (c - C_S) % NHEAD; cl.piece = 0;
        cl.ntiles = fin_size(cl.head); cl.tile0 = (cl.head + 1) * TPH - cl.ntiles;
        if (c < C_F) { cl.ntiles = semi_size(cl.head); cl.tile0 -= cl.ntiles; }
    }
    return cl;
}

struct Params {
    const int* qk; const __nv_bfloat16* kcos; const __nv_bfloat16* ksin; const int* qv;
    const __nv_bfloat16* ks; const __nv_bfloat16* kz; const __nv_bfloat16* vs; const __nv_bfloat16* vz;
    const __nv_bfloat16* q; const __nv_bfloat16* qcos; const __nv_bfloat16* qsin;
    __nv_bfloat16* out;
};

constexpr float NEG = -3.0e38f;
constexpr float LOG2E = 1.4426950408889634f;
constexpr int F_FIRST = 256, F_LAST = 512, F_SEMI = 1024, F_FIN = 2048, F_SEGEND = 4096, F_END = 8192;

__global__ void __launch_bounds__(NTHREADS, 1)
kv_rope_decode_kernel(const Params p) {
    extern __shared__ __align__(128) unsigned char smem[];
    if (threadIdx.x >= NWARPS * 32 && elect_one()) {
        l2_prefetch(p.kcos + (blockIdx.x % (TPH / 2)) * (2 * TR * D), 2 * CBYTES);
        l2_prefetch(p.ksin + (blockIdx.x % (TPH / 2)) * (2 * TR * D), 2 * CBYTES);
        uint64_t pol;
        asm volatile("createpolicy.fractional.L2::evict_first.b64 %0, 1.0;" : "=l"(pol));
        const uint32_t h = blockIdx.x / NM, pc = blockIdx.x - h * NM;
        const uint32_t off = pc < ((NM - 1) >> GSH << GSH) ? pc & ((1 << GSH) - 1) : 0;
        l2_prefetch(p.qk + (size_t)(h * TPH + (pc - off) * MAINP + off * CFG_PF0) * (TR * D), CFG_PF0 * KBYTES, pol);
    }
    const int w = __shfl_sync(0xffffffffu, threadIdx.x >> 5, 0), lane = threadIdx.x & 31;
    if (w == NWARPS) return;
    const uint32_t sb = __shfl_sync(0xffffffffu, smem_u32(smem), 0);
    const uint32_t bar = sb + OFF_BAR;

    const int grp = w - (w > W_PROD);
    if (grp < 7 && w != W_PROD && elect_one()) {
        const uint32_t cnt = grp == 4 ? 4 : grp == 5 ? NKW + NVW : grp == 6 ? NVW : 1;
#pragma unroll
        for (int i = 0; i < 16; i++) mbar_init(bar + grp * 128 + i * 8, cnt);
        asm volatile("fence.mbarrier_init.release.cluster;" ::: "memory");
    }
    asm volatile("bar.sync 0, %0;" ::"n"(NWARPS * 32) : "memory");

    if ((unsigned)(w - W_V) < NVW) {
        const int v = w - W_V, g = lane >> 3, l = lane & 7;
        const bool up = lane & 16, up2 = lane & 8;
        const uint32_t oV = pin(sb + OFF_V + g * (2 * D * 4) + v * (NB * 128) + l * 16), oP = pin(S_LG + g * 8);
        const uint32_t col = pin(v * (NB * 32) + l * 4 + (up ? 2 : 0) + (up2 ? 1 : 0));
        float acc[4 * NB];
#pragma unroll
        for (int i = 0; i < 4 * NB; i++) acc[i] = 0.f;
        uint32_t vslot = 0, seg = 0, b = 0, vph = 0;
        for (uint32_t batch = 0;; batch++) {
            const uint32_t s = sb + OFF_SEG + (seg % NSEG) * SEG_BYTES, sbar = bar + (seg % NSEG) * 8;
            mbar_wait(bar + B_PR + (batch % NBAT) * 8, (batch / NBAT) & 1);
            const int4 bd = lds128(s + S_BD + b * 16);
            const bool early = mbar_test(sbar + B_FC, (seg / NSEG) & 1);
            bool ready = mbar_test(bar + B_FV + vslot * 8, vph);
            uint32_t pa = s + oP + b * 128;
            uint2 pv = lds64(pa);
            int4 cf = lds128(s + S_CF);
            uint32_t gv[NB];
#pragma unroll
            for (int j = 0; j < NB; j++) gv[j] = lds32(s + S_G + (col + j * 32) * 4);
            if (bd.y & F_END) break;
            TS(3);
            const float alpha = __int_as_float(bd.z);
#pragma unroll
            for (int i = 0; i < 4 * NB; i++) acc[i] *= alpha;
            const int n = bd.y & 255;
#pragma unroll 1
            for (int i = 0; i < n; i++) {
                const float pv0 = __uint_as_float(pv.x), pv1 = __uint_as_float(pv.y);
                const uint32_t t = oV + vslot * KBYTES;
                if (!ready) mbar_wait(bar + B_FV + vslot * 8, vph);
                TS_ONCE(1); TS(5);
                int4 x0[NB], x1[NB];
#pragma unroll
                for (int j = 0; j < NO_COMPUTE(NB); j++) {
                    x0[j] = lds128(t + j * 128);
                    x1[j] = lds128(t + 768 + j * 128);
                }
                __syncwarp();
                if (lane == 0) mbar_arrive(bar + B_EV + vslot * 8);
                if (++vslot == NV) { vslot = 0; vph ^= 1; }
                ready = mbar_test(bar + B_FV + vslot * 8, vph);
                pv = lds64(pa += TR * 4);
#pragma unroll
                for (int j = 0; j < NO_COMPUTE(NB); j++) {
                    acc[j * 4 + 0] = fmaf(pv1, CVT(x1[j].x), fmaf(pv0, CVT(x0[j].x), acc[j * 4 + 0]));
                    acc[j * 4 + 1] = fmaf(pv1, CVT(x1[j].y), fmaf(pv0, CVT(x0[j].y), acc[j * 4 + 1]));
                    acc[j * 4 + 2] = fmaf(pv1, CVT(x1[j].z), fmaf(pv0, CVT(x0[j].z), acc[j * 4 + 2]));
                    acc[j * 4 + 3] = fmaf(pv1, CVT(x1[j].w), fmaf(pv0, CVT(x0[j].w), acc[j * 4 + 3]));
                }
            }
            if (bd.y & F_LAST) {
                float o[NB];
#pragma unroll
                for (int j = 0; j < NB; j++) {
                    const float u0 = (up ? acc[j * 4 + 2] : acc[j * 4 + 0]) + __shfl_xor_sync(0xffffffffu, up ? acc[j * 4 + 0] : acc[j * 4 + 2], 16);
                    const float u1 = (up ? acc[j * 4 + 3] : acc[j * 4 + 1]) + __shfl_xor_sync(0xffffffffu, up ? acc[j * 4 + 1] : acc[j * 4 + 3], 16);
                    o[j] = (up2 ? u1 : u0) + __shfl_xor_sync(0xffffffffu, up2 ? u0 : u1, 8);
                }
                if (!early) {
                    mbar_wait(sbar + B_FC, (seg / NSEG) & 1);
                    cf = lds128(s + S_CF);
#pragma unroll
                    for (int j = 0; j < NB; j++) gv[j] = lds32(s + S_G + (col + j * 32) * 4);
                }
#pragma unroll
                for (int j = 0; j < NB; j++) {
                    const float gj = (bd.y & (F_SEMI | F_FIN)) ? __uint_as_float(gv[j]) : 0.f;
                    o[j] = fmaf(o[j], __int_as_float(cf.x), fmaf(gj, __int_as_float(cf.y), __int_as_float(cf.z)));
                }
                if (bd.y & F_FIN) {
#pragma unroll
                    for (int j = 0; j < NB; j++) p.out[bd.x + col + j * 32] = __float2bfloat16_rn(o[j]);
                } else {
#pragma unroll
                    for (int j = 0; j < NB; j++) mail_put(g_mail + (bd.x + col + j * 32), o[j], cf.w & 3);
                    if (col < REC - D) mail_put(g_mail + (bd.x + D + col), __int_as_float(cf.w), cf.w & 3);
                }
#pragma unroll
                for (int i = 0; i < 4 * NB; i++) acc[i] = 0.f;
            }
            b++;
            if (bd.y & F_SEGEND) {
                if (!(bd.y & F_LAST)) mbar_wait(sbar + B_FC, (seg / NSEG) & 1);
                __syncwarp();
                if (lane == 0) mbar_arrive(sbar + B_SE);
                seg++; b = 0;
            }
            TS(6);
        }
    } else if (w == W_S) {
        float m = NEG, lsum = 0.f, corr = 0.f;
        uint32_t batch = 0;
        for (uint32_t seg = 0;; seg++) {
            const uint32_t s = sb + OFF_SEG + (seg % NSEG) * SEG_BYTES, sbar = bar + (seg % NSEG) * 8;
            const uint32_t sph = (seg / NSEG) & 1;
            mbar_wait(sbar + B_HDR, sph);
            const int4 desc = lds128(s + S_DESC);
            if (desc.y & F_END) {
                if (lane == 0) {
                    sts128(s + S_BD, 0, F_END, 0, 0);
                    mbar_arrive(bar + B_PR + (batch % NBAT) * 8);
                }
                break;
            }
            if (desc.y & F_FIRST) { m = NEG; lsum = 0.f; corr = 0.f; }
            const int index = (desc.y & F_FIN) ? desc.x * D : (desc.x * NM + desc.z) * REC;
            int b = 0;
            for (int left = desc.y & 255; left > 0; left -= 4, b++, batch++) {
                const bool valid = lane < left * TR;
                const uint32_t sc = s + S_SC + ((((b * 4 + (lane >> 3)) << (desc.w & 255)) + (desc.w >> 8)) * TR + (lane & 7)) * 2;
                const float vs = bf_lo(lds16(sc + 2 * SCB)), vz = bf_lo(lds16(sc + 3 * SCB));
                mbar_wait(bar + B_LG + (batch % NBAT) * 8, (batch / NBAT) & 1);
                const float dot = __uint_as_float(lds32(s + S_LG + (b * 32 + lane) * 4)) +
                                  __uint_as_float(lds32(s + S_LG + SEGT * TR * 4 + (b * 32 + lane) * 4));
                const float sv = rbf(rbf(dot) * 0.07216878364870322f) * LOG2E;
                int key = __float_as_int(fmaxf(m, valid ? sv : m));
                key ^= (key >> 31) & 0x7fffffff;
                key = __reduce_max_sync(0xffffffffu, key);
                const float mn = __int_as_float(key ^ ((key >> 31) & 0x7fffffff));
                const float alpha = ex2(m - mn), pr = ex2(sv - mn), pv = pr * vs;
                m = mn;
                sts32(s + S_LG + (b * 32 + lane) * 4, pv);
                if (lane == 0)
                    sts128(s + S_BD + b * 16, index, left > 4 ? 4 : (left | F_SEGEND | (desc.y & (F_LAST | F_SEMI | F_FIN))),
                           __float_as_uint(alpha), 0);
                __syncwarp();
                if (lane == 0) mbar_arrive(bar + B_PR + (batch % NBAT) * 8);
                lsum = fmaf(lsum, alpha, valid ? pr : 0.f);
                corr = fmaf(corr, alpha, valid ? pv * vz : 0.f);
                TS(3);
            }
            float L = lsum, C = corr;
            if (desc.y & F_LAST) {
#pragma unroll
                for (int o = 16; o > 0; o >>= 1) {
                    L += __shfl_xor_sync(0xffffffffu, L, o);
                    C += __shfl_xor_sync(0xffffffffu, C, o);
                }
            }
            mbar_wait(sbar + B_GD, sph);
            if (desc.y & F_LAST) {
                const uint32_t tag = lds32(sb + OFF_TAG) | ((desc.y & F_SEMI) ? 2 : 0);
                const float gl = (desc.y & (F_SEMI | F_FIN)) ? __uint_as_float(lds32(s + S_G + D * 4)) : -3.4e38f;
                const float M = fmaxf(m, gl), e = ex2(m - M), a = ex2(gl - M);
                const float W = fmaf(L, e, a), inv = rcp(W);
                if (lane == 0)
                    sts128(s + S_CF, __float_as_uint(e * inv), __float_as_uint(a * inv), __float_as_uint(-C * e * inv),
                           (__float_as_uint(M + lg2(W)) & ~3u) | tag);
            }
            __syncwarp();
            if (lane == 0) mbar_arrive(sbar + B_FC);
            TS(4);
        }
    } else if ((unsigned)(w - W_G) < NGW) {
        if (w == W_G) {
            if (lane == 0) sts32(sb + OFF_TAG, __uint_as_float(~*(volatile unsigned int*)&g_epoch & 1));
        } else {
            mbar_wait(bar + B_GD, 0);
        }
        for (uint32_t seg = w - W_G;; seg += NGW) {
            const uint32_t s = sb + OFF_SEG + (seg % NSEG) * SEG_BYTES, sbar = bar + (seg % NSEG) * 8;
            mbar_wait(sbar + B_HDR, (seg / NSEG) & 1);
            const int4 desc = lds128(s + S_DESC);
            if (desc.y & F_END) break;
            TS(1);
            if (desc.y & (F_SEMI | F_FIN)) {
                const uint32_t tag = lds32(sb + OFF_TAG) | ((desc.y & F_FIN) ? 2 : 0);
                const int cnt = (desc.y & F_FIN) ? 1 : NM;
                const uint32_t* mail = g_mail + desc.x * (NM * REC);
                float M = NEG, W = 0.f, O[6] = {0.f, 0.f, 0.f, 0.f, 0.f, 0.f};
#pragma unroll 1
                for (int i0 = 0; i0 < cnt; i0 += 5, mail += 5 * REC) {
                    uint2 pk[15];
                    uint32_t ls[5], stale;
                    int it = 0;
                    do {
                        stale = 0;
#pragma unroll
                        for (int i = 0; i < 5; i++) {
                            ls[i] = 0xff7ffffcu | tag;
                            pk[3 * i] = pk[3 * i + 1] = pk[3 * i + 2] = make_uint2(tag, tag);
                            if (i0 + i < cnt) {
                                asm volatile("ld.relaxed.gpu.global.u32 %0, [%1];" : "=r"(ls[i]) : "l"(mail + i * REC + D) : "memory");
#pragma unroll
                                for (int k = 0; k < 3; k++)
                                    asm volatile("ld.relaxed.gpu.global.v2.u32 {%0,%1}, [%2];"
                                                 : "=r"(pk[3 * i + k].x), "=r"(pk[3 * i + k].y)
                                                 : "l"(mail + i * REC + k * 64 + lane * 2) : "memory");
                            }
                        }
#pragma unroll
                        for (int i = 0; i < 5; i++) stale |= ls[i] ^ tag;
#pragma unroll
                        for (int i = 0; i < 15; i++) stale |= (pk[i].x ^ tag) | (pk[i].y ^ tag);
                        if (++it > (1 << 22)) __trap();
                    } while (stale & 3);
                    float Mn = M;
#pragma unroll
                    for (int i = 0; i < 5; i++) Mn = fmaxf(Mn, __uint_as_float(ls[i]));
                    const float a = ex2(M - Mn);
                    M = Mn; W *= a;
#pragma unroll
                    for (int i = 0; i < 6; i++) O[i] *= a;
#pragma unroll
                    for (int i = 0; i < 5; i++) {
                        const float e = ex2(__uint_as_float(ls[i]) - M);
                        W += e;
#pragma unroll
                        for (int k = 0; k < 3; k++) {
                            O[2 * k] = fmaf(e, __uint_as_float(pk[3 * i + k].x), O[2 * k]);
                            O[2 * k + 1] = fmaf(e, __uint_as_float(pk[3 * i + k].y), O[2 * k + 1]);
                        }
                    }
                }
                const float inv = rcp(W);
#pragma unroll
                for (int k = 0; k < 3; k++) sts64(s + S_G + k * 256 + lane * 8, O[2 * k] * inv, O[2 * k + 1] * inv);
                if (lane == 0) sts32(s + S_G + D * 4, M + lg2(W));
            }
            __syncwarp();
            if (lane == 0) mbar_arrive(sbar + B_GD);
            TS(2);
        }
    } else if ((w >> 2) == 0) {
        const int g = lane >> 3, l = lane & 7, godd = g & 1;
        const uint32_t sgA = pin(godd ? 0x3f803f80u : 0xbf80bf80u), sgB = pin(godd ? 0xbf80bf80u : 0x3f803f80u);
        const uint32_t oKA = pin(sb + g * (2 * D * 4) + l * 16 + godd * 384), oKB = pin(oKA - godd * 768 + 384);
        const uint32_t oCA = pin(sb + T_C + g * (2 * D * 2) + l * 8 + godd * 192), oCB = pin(oCA - godd * 384 + 192);
        const uint32_t oL = pin(S_LG + (l >> 2) * (SEGT * TR * 4) + g * 8);
        uint2 qr[6];
        uint32_t kslot = w, j = kslot, batch0 = 0, kph = 0;
        for (uint32_t seg = 0;; seg++) {
            const uint32_t s = sb + OFF_SEG + (seg % NSEG) * SEG_BYTES, sbar = bar + (seg % NSEG) * 8;
            mbar_wait(sbar + B_HDR, (seg / NSEG) & 1);
            const uint32_t desc = lds32(s + S_DESC + 4), geo = lds32(s + S_DESC + 12);
            if (desc & F_END) break;
            const uint32_t nt = desc & 255;
            if (desc & F_FIRST) {
#pragma unroll
                for (int i = 0; i < 3; i++) {
                    const uint32_t oa = l * 8 + godd * 192 + i * 64, ob = oa + 192 - godd * 384;
                    const uint2 a = lds64(s + S_Q + oa), b = lds64(s + S_Q + ob);
                    const uint2 ca = lds64(sb + OFF_QT + oa), cb = lds64(sb + OFF_QT + ob);
                    const uint2 sa = lds64(sb + OFF_QT + QBYTES + oa), sbv = lds64(sb + OFF_QT + QBYTES + ob);
                    qr[i].x = rope2(a.x, ca.x, b.x, sa.x, sgA);
                    qr[i].y = rope2(a.y, ca.y, b.y, sa.y, sgA);
                    qr[i + 3].x = rope2(b.x, cb.x, a.x, sbv.x, sgB);
                    qr[i + 3].y = rope2(b.y, cb.y, a.y, sbv.y, sgB);
                }
            }
            for (; j < nt; j += NKW) {
                const uint32_t t = kslot * KSLOT;
                const uint32_t sc = s + S_SC + ((j << (geo & 255)) + (geo >> 8)) * (TR * 2) + g * 4;
                const uint32_t sks = lds32(sc), skz = lds32(sc + SCB);
                const uint32_t ks2[2] = {__byte_perm(sks, 0, 0x1010), __byte_perm(sks, 0, 0x3232)};
                const uint32_t kz2[2] = {__byte_perm(skz, 0, 0x1010), __byte_perm(skz, 0, 0x3232)};
                mbar_wait(bar + B_FK + kslot * 8, kph);
                TS_ONCE(1); TS(3);
                float cA[4] = {0.f, 0.f, 0.f, 0.f}, cB[4] = {0.f, 0.f, 0.f, 0.f};
#pragma unroll
                for (int jj = 0; jj < NO_COMPUTE(3); jj++) {
                    uint2 ra[2], rb[2];
#pragma unroll
                    for (int ps = 0; ps < 2; ps++) {
                        const int4 xa = lds128(t + oKA + ps * 768 + jj * 128);
                        const int4 xb = lds128(t + oKB + ps * 768 + jj * 128);
                        const uint2 ca = lds64(t + oCA + ps * 384 + jj * 64);
                        const uint2 cb = lds64(t + oCB + ps * 384 + jj * 64);
                        const uint2 sa = lds64(t + oCA + CBYTES + ps * 384 + jj * 64);
                        const uint2 sbv = lds64(t + oCB + CBYTES + ps * 384 + jj * 64);
                        const uint32_t a0 = bmul(bsub(i2bf2(xa.x, xa.y), kz2[ps]), ks2[ps]);
                        const uint32_t a1 = bmul(bsub(i2bf2(xa.z, xa.w), kz2[ps]), ks2[ps]);
                        const uint32_t b0 = bmul(bsub(i2bf2(xb.x, xb.y), kz2[ps]), ks2[ps]);
                        const uint32_t b1 = bmul(bsub(i2bf2(xb.z, xb.w), kz2[ps]), ks2[ps]);
                        ra[ps].x = rope2(a0, ca.x, b0, sa.x, sgA);
                        ra[ps].y = rope2(a1, ca.y, b1, sa.y, sgA);
                        rb[ps].x = rope2(b0, cb.x, a0, sbv.x, sgB);
                        rb[ps].y = rope2(b1, cb.y, a1, sbv.y, sgB);
                    }
                    mma_bf16(cA, ra[0].x, ra[1].x, ra[0].y, ra[1].y, qr[jj].x, qr[jj].y);
                    mma_bf16(cB, rb[0].x, rb[1].x, rb[0].y, rb[1].y, qr[jj + 3].x, qr[jj + 3].y);
                }
                __syncwarp();
                if (lane == 0) mbar_arrive(bar + B_EK + kslot * 8);
                TS_ONCE(2);
                if ((lane & 3) == g)
                    sts64(s + oL + j * (TR * 4),
                          l < 4 ? cA[0] + cB[0] : cA[1] + cB[1], l < 4 ? cA[2] + cB[2] : cA[3] + cB[3]);
                __syncwarp();
                if (lane == 0) mbar_arrive(bar + B_LG + ((batch0 + (j >> 2)) % NBAT) * 8, j == nt - 1 ? 4 - (j & 3) : 1);
                TS(4);
                kslot += NKW;
                if (kslot >= NK) { kslot -= NK; kph ^= 1; }
            }
            j -= nt;
            batch0 += (nt + 3) >> 2;
            __syncwarp();
            if (lane == 0) mbar_arrive(sbar + B_SE);
        }
    } else {
        if (elect_one()) {
            uint64_t pol;
            asm volatile("createpolicy.fractional.L2::evict_first.b64 %0, 1.0;" : "=l"(pol));
            uint32_t kslot = 0, vslot = 0, seg = 0, kph = 1, vph = 1;
            uint32_t win = NV;
            int pend[LEAD];
#pragma unroll
            for (int i = 0; i < LEAD; i++) pend[i] = -1;
            auto push_v = [&](int tile) {
                if (pend[0] >= 0) {
                    const uint32_t b = bar + vslot * 8;
                    mbar_wait(b + B_EV, vph);
                    mbar_expect(b + B_FV, KBYTES);
                    bulk_stream(sb + OFF_V + vslot * KBYTES, p.qv + (size_t)pend[0] * (TR * D), KBYTES, b + B_FV, pol);
                    if (++vslot == NV) { vslot = 0; vph ^= 1; }
                }
#pragma unroll
                for (int i = 0; i + 1 < LEAD; i++) pend[i] = pend[i + 1];
                pend[LEAD - 1] = tile;
            };
            asm volatile("mbarrier.expect_tx.shared::cta.b64 [%0], %1;" ::"r"(bar + B_HDR), "r"(2 * QBYTES) : "memory");
            bulk_plain(sb + OFF_QT, p.qcos, QBYTES, bar + B_HDR);
            bulk_plain(sb + OFF_QT + QBYTES, p.qsin, QBYTES, bar + B_HDR);
            uint32_t c = blockIdx.x;
            TS(1);
            while (c < NCLAIM) {
                const Claim cl = decode_claim(c);
                uint32_t tile = cl.tile0 + cl.off;
                auto tiles = [&](int cnt) {
#pragma unroll 1
                    for (int j = 0; j < cnt; j++, tile += 1u << cl.sh) {
                        push_v(tile);
                        const uint32_t t = sb + kslot * KSLOT, b = bar + kslot * 8;
                        const uint32_t ro = (tile % TPH) * (TR * D);
                        mbar_wait(b + B_EK, kph);
                        mbar_expect(b + B_FK, KSLOT);
                        bulk_stream(t, p.qk + (size_t)tile * (TR * D), KBYTES, b + B_FK, pol);
                        bulk_plain(t + T_C, p.kcos + ro, CBYTES, b + B_FK);
                        bulk_plain(t + T_S, p.ksin + ro, CBYTES, b + B_FK);
                        TS_ONCE(2); TS(3);
                        if (++kslot == NK) { kslot = 0; kph ^= 1; }
                    }
                };
                int nt;
                for (int left = cl.ntiles;; left -= nt) {
                    nt = min(SEGT, left);
                    const bool first = left == cl.ntiles, last = left == nt;
                    const uint32_t s = sb + OFF_SEG + (seg % NSEG) * SEG_BYTES, b = bar + (seg % NSEG) * 8;
                    mbar_wait(b + B_SE, ((seg / NSEG) & 1) ^ 1);
                    sts128(s + S_DESC, cl.head,
                           nt | (first ? F_FIRST : 0) | (last ? F_LAST : 0) | (c >= C_F ? F_FIN : c >= C_S ? F_SEMI : 0),
                           cl.piece, cl.sh | cl.off << 8);
                    const uint32_t scb = nt * TR * 2 << cl.sh;
                    const uint32_t r = (tile - cl.off) * TR;
                    mbar_expect(b + B_HDR, 4 * scb + (first ? QBYTES : 0));
                    if (first) bulk_stream(s + S_Q, p.q + cl.head * D, QBYTES, b + B_HDR, pol);
                    bulk_stream(s + S_SC, p.ks + r, scb, b + B_HDR, pol);
                    bulk_stream(s + S_SC + SCB, p.kz + r, scb, b + B_HDR, pol);
                    bulk_stream(s + S_SC + 2 * SCB, p.vs + r, scb, b + B_HDR, pol);
                    bulk_stream(s + S_SC + 3 * SCB, p.vz + r, scb, b + B_HDR, pol);
                    seg++;
                    tiles(last ? max(nt - LA, 0) : nt);
                    if (last) break;
                }
                if (c == blockIdx.x) mbar_wait(bar + B_GD, 0);
                const unsigned nx = atomicInc(&g_queue, NCLAIM - 1);
                tiles(min(nt, LA));
                if (nx == NCLAIM - 1) g_epoch = lds32(sb + OFF_TAG);
                c = gridDim.x + nx;
            }
            TS(4);
#pragma unroll 1
            for (int i = 0; i < LEAD; i++) push_v(-1);
            TS(5);
#pragma unroll 1
            for (int i = 0; i < NGW; i++, seg++) {
                const uint32_t s = sb + OFF_SEG + (seg % NSEG) * SEG_BYTES, b = bar + (seg % NSEG) * 8;
                mbar_wait(b + B_SE, ((seg / NSEG) & 1) ^ 1);
                sts128(s + S_DESC, 0, F_END, 0, 0);
                mbar_arrive(b + B_HDR);
            }
        }
    }
}

}

extern "C" void kernel_launch(void* const* d_in, const int* in_sizes, int n_in, void* d_out, int out_size) {
    (void)in_sizes; (void)n_in; (void)out_size;
    static int sms = 0;
    if (sms == 0) {
        int dev = 0;
        cudaGetDevice(&dev);
        cudaDeviceGetAttribute(&sms, cudaDevAttrMultiProcessorCount, dev);
        cudaFuncSetAttribute(kv_rope_decode_kernel, cudaFuncAttributeMaxDynamicSharedMemorySize, SMEM_BYTES);
    }
    Params p;
    p.q    = (const __nv_bfloat16*)d_in[0];
    p.qk   = (const int*)d_in[1];
    p.ks   = (const __nv_bfloat16*)d_in[2];
    p.kz   = (const __nv_bfloat16*)d_in[3];
    p.qv   = (const int*)d_in[4];
    p.vs   = (const __nv_bfloat16*)d_in[5];
    p.vz   = (const __nv_bfloat16*)d_in[6];
    p.qcos = (const __nv_bfloat16*)d_in[7];
    p.qsin = (const __nv_bfloat16*)d_in[8];
    p.kcos = (const __nv_bfloat16*)d_in[9];
    p.ksin = (const __nv_bfloat16*)d_in[10];
    p.out  = (__nv_bfloat16*)d_out;
    kv_rope_decode_kernel<<<sms, NTHREADS, SMEM_BYTES>>>(p);
}
```

```cpp
#include <cuda_runtime.h>
#include <cuda_bf16.h>
#include <stdint.h>

namespace {

#define CFG_NVW 6
#define CFG_NK 8
#define CFG_NV 4
#define CFG_LEAD 5
#define CFG_MAIN 16
#define CFG_SEMI 0xfdb9
#define CFG_FIN 0x7531
#define CFG_GSH 2
#define CFG_BM 2
#define CFG_BF 2
#define CFG_LA 3
#define CFG_PF0 3

constexpr int D      = 192;
constexpr int SKV    = 2048;
constexpr int NHEAD  = 256;
constexpr int TR     = 8;
constexpr int TPH    = SKV / TR;
constexpr int NKW    = 4;
constexpr int NVW    = CFG_NVW;
constexpr int NB     = 6 / NVW;
constexpr int NGW    = 2;
constexpr int NK     = CFG_NK;
constexpr int NV     = CFG_NV;
constexpr int LEAD   = CFG_LEAD;
constexpr int NSEG   = 8;
constexpr int SEGT   = 16;
constexpr int NBAT   = 16;
constexpr int W_V = NKW, W_PROD = W_V + NVW, W_S = W_PROD + 1, W_G = W_S + 1, NWARPS = W_G + NGW;
constexpr int NTHREADS = NWARPS * 32 + 32;

constexpr int MAINP  = CFG_MAIN;
constexpr int GSH    = CFG_GSH;
constexpr int LA     = CFG_LA;
__host__ __device__ constexpr int semi_size(int h) { return ((CFG_SEMI >> (12 - 4 * (h >> 6))) & 15) + 1; }
__host__ __device__ constexpr int fin_size(int h) { return ((CFG_FIN >> (12 - 4 * (h >> 6))) & 15) + 1; }
constexpr int NM     = (TPH - semi_size(0) - fin_size(0) + MAINP - 1) / MAINP;
constexpr int C_S    = NHEAD * NM, C_F = C_S + NHEAD, NCLAIM = C_F + NHEAD;
constexpr bool sizes_ok(int h) { return h >= NHEAD || (semi_size(h) + fin_size(h) < TPH - (NM - 1) * MAINP && sizes_ok(h + 64)); }
static_assert(sizes_ok(0), "schedule");

constexpr int KBYTES = TR * D * 4;
constexpr int CBYTES = TR * D * 2;
constexpr int QBYTES = D * 2;
constexpr int T_C = KBYTES, T_S = T_C + CBYTES, KSLOT = T_S + CBYTES;
constexpr int SCB = SEGT * TR * 2 << GSH;
static_assert(GSH == 0 || MAINP == SEGT, "interleaved pieces are single segments");
constexpr int S_Q = 0, S_SC = QBYTES, S_DESC = S_SC + 4 * SCB, S_BD = S_DESC + 16,
              S_LG = S_BD + SEGT * 8, S_G = S_LG + 2 * SEGT * TR * 4, S_CF = S_G + (D + 4) * 4,
              SEG_BYTES = (S_CF + 16 + 127) / 128 * 128;
constexpr int OFF_V = NK * KSLOT, OFF_SEG = OFF_V + NV * KBYTES, OFF_QT = OFF_SEG + NSEG * SEG_BYTES,
              OFF_TAG = OFF_QT + 2 * QBYTES, OFF_BAR = OFF_TAG + 16;
constexpr int B_FK = 0, B_EK = 64, B_PR = 128, B_HDR = 256, B_GD = 320, B_FC = 384, B_FV = 448, B_LG = 512,
              B_SE = 640, B_EV = 768;
constexpr int SMEM_BYTES = OFF_BAR + 896;
static_assert(NK <= 8 && NV <= 8 && NSEG == 8 && NBAT == 16, "barrier layout");
static_assert(SMEM_BYTES <= 232448 && SMEM_BYTES > 232448 / 2, "smem");
static_assert(NSEG % NGW == 0 && NK % NKW == 0 && NB * NVW == 6 && NM <= 32 && LEAD >= 1, "cfg");
static_assert(LEAD + NV >= 4 && LEAD + NV < NBAT && LEAD < NSEG, "cfg");

__device__ unsigned int g_queue;
constexpr int REC = 200;
__device__ unsigned int g_epoch;
__device__ __align__(32) uint32_t g_mail[NHEAD * NM * REC];

__device__ __forceinline__ uint32_t smem_u32(const void* p) { return (uint32_t)__cvta_generic_to_shared(p); }
__device__ __forceinline__ uint32_t pin(uint32_t x) {
    return __shfl_sync(0xffffffffu, x, threadIdx.x & 31);
}
template <class T> __device__ __forceinline__ T* pin(T* p) {
    return (T*)__shfl_sync(0xffffffffu, (unsigned long long)p, threadIdx.x & 31);
}
__device__ __forceinline__ bool elect_one() {
    uint32_t pred;
    asm volatile("{\n.reg .pred p;\nelect.sync _|p, 0xffffffff;\nselp.u32 %0, 1, 0, p;\n}" : "=r"(pred));
    return pred;
}
__device__ __forceinline__ void mbar_init(uint32_t bar, uint32_t cnt) {
    asm volatile("mbarrier.init.shared::cta.b64 [%0], %1;" ::"r"(bar), "r"(cnt) : "memory");
}
__device__ __forceinline__ void mbar_expect(uint32_t bar, uint32_t bytes) {
    asm volatile("mbarrier.arrive.expect_tx.shared::cta.b64 _, [%0], %1;" ::"r"(bar), "r"(bytes) : "memory");
}
__device__ __forceinline__ void mbar_arrive(uint32_t bar) {
    asm volatile("mbarrier.arrive.shared::cta.b64 _, [%0];" ::"r"(bar) : "memory");
}
__device__ __forceinline__ void mbar_arrive(uint32_t bar, uint32_t cnt) {
    asm volatile("mbarrier.arrive.shared::cta.b64 _, [%0], %1;" ::"r"(bar), "r"(cnt) : "memory");
}
__device__ __forceinline__ bool mbar_test(uint32_t bar, uint32_t parity) {
    uint32_t ok;
    asm volatile("{\n.reg .pred p;\nmbarrier.test_wait.parity.shared::cta.b64 p, [%1], %2;\nselp.u32 %0, 1, 0, p;\n}"
                 : "=r"(ok) : "r"(bar), "r"(parity) : "memory");
    return ok;
}
__device__ __forceinline__ void mbar_wait(uint32_t bar, uint32_t parity) {
    asm volatile("{\n.reg .pred p;\n.reg .u32 n;\n"
                 "mbarrier.try_wait.parity.shared::cta.b64 p, [%0], %1;\n"
                 "@p bra DONE;\n"
                 "mov.u32 n, 0;\n"
                 "LOOP:\n"
                 "mbarrier.try_wait.parity.shared::cta.b64 p, [%0], %1;\n"
                 "@p bra DONE;\n"
                 "add.u32 n, n, 1;\n"
                 "setp.lt.u32 p, n, 0x400000;\n"
                 "@p bra LOOP;\n"
                 "trap;\n"
                 "DONE:\n}" ::"r"(bar), "r"(parity) : "memory");
}
__device__ __forceinline__ void bulk_stream(uint32_t dst, const void* src, uint32_t bytes, uint32_t bar, uint64_t pol) {
    asm volatile("cp.async.bulk.shared::cluster.global.mbarrier::complete_tx::bytes.L2::cache_hint [%0], [%1], %2, [%3], %4;"
                 ::"r"(dst), "l"(src), "r"(bytes), "r"(bar), "l"(pol) : "memory");
}
__device__ __forceinline__ void bulk_plain(uint32_t dst, const void* src, uint32_t bytes, uint32_t bar) {
    asm volatile("cp.async.bulk.shared::cluster.global.mbarrier::complete_tx::bytes [%0], [%1], %2, [%3];"
                 ::"r"(dst), "l"(src), "r"(bytes), "r"(bar) : "memory");
}
__device__ __forceinline__ void l2_prefetch(const void* src, uint32_t bytes, uint64_t pol) {
    asm volatile("cp.async.bulk.prefetch.L2.global.L2::cache_hint [%0], %1, %2;" ::"l"(src), "r"(bytes), "l"(pol) : "memory");
}
__device__ __forceinline__ void l2_prefetch(const void* src, uint32_t bytes) {
    asm volatile("cp.async.bulk.prefetch.L2.global [%0], %1;" ::"l"(src), "r"(bytes) : "memory");
}
__device__ __forceinline__ int4 lds128(uint32_t a) {
    int4 v;
    asm volatile("ld.shared.v4.s32 {%0,%1,%2,%3}, [%4];" : "=r"(v.x), "=r"(v.y), "=r"(v.z), "=r"(v.w) : "r"(a));
    return v;
}
__device__ __forceinline__ uint2 lds64(uint32_t a) {
    uint2 v;
    asm volatile("ld.shared.v2.u32 {%0,%1}, [%2];" : "=r"(v.x), "=r"(v.y) : "r"(a));
    return v;
}
__device__ __forceinline__ uint32_t lds32(uint32_t a) {
    uint32_t v;
    asm volatile("ld.shared.u32 %0, [%1];" : "=r"(v) : "r"(a));
    return v;
}
__device__ __forceinline__ uint32_t lds16(uint32_t a) {
    uint16_t v;
    asm volatile("ld.shared.u16 %0, [%1];" : "=h"(v) : "r"(a));
    return v;
}
__device__ __forceinline__ void sts32(uint32_t a, float x) {
    asm volatile("st.shared.f32 [%0], %1;" ::"r"(a), "f"(x) : "memory");
}
__device__ __forceinline__ void sts128(uint32_t a, uint32_t x, uint32_t y, uint32_t z, uint32_t w) {
    asm volatile("st.shared.v4.u32 [%0], {%1,%2,%3,%4};" ::"r"(a), "r"(x), "r"(y), "r"(z), "r"(w) : "memory");
}
__device__ __forceinline__ void sts64(uint32_t a, float x, float y) {
    asm volatile("st.shared.v2.f32 [%0], {%1,%2};" ::"r"(a), "f"(x), "f"(y) : "memory");
}
__device__ __forceinline__ float bf_lo(uint32_t v) { return __uint_as_float(v << 16); }
__device__ __forceinline__ float bf_hi(uint32_t v) { return __uint_as_float(v & 0xffff0000u); }
__device__ __forceinline__ float rbf(float x) {
    uint32_t d; asm("cvt.rn.bf16x2.f32 %0, %1, %2;" : "=r"(d) : "f"(x), "f"(0.f)); return __uint_as_float(d);
}
__device__ __forceinline__ float rcp(float x) {
    float y;
    asm("rcp.approx.ftz.f32 %0, %1;" : "=f"(y) : "f"(x));
    return y;
}
__device__ __forceinline__ float lg2(float x) {
    float y;
    asm("lg2.approx.ftz.f32 %0, %1;" : "=f"(y) : "f"(x));
    return y;
}
__device__ __forceinline__ float ex2(float x) {
    float y;
    asm("ex2.approx.ftz.f32 %0, %1;" : "=f"(y) : "f"(x));
    return y;
}
__device__ __forceinline__ uint32_t bmul(uint32_t a, uint32_t b) {
    uint32_t d; asm("mul.rn.bf16x2 %0, %1, %2;" : "=r"(d) : "r"(a), "r"(b)); return d;
}
__device__ __forceinline__ uint32_t bsub(uint32_t a, uint32_t b) {
    uint32_t d; asm("sub.rn.bf16x2 %0, %1, %2;" : "=r"(d) : "r"(a), "r"(b)); return d;
}
__device__ __forceinline__ uint32_t bfma(uint32_t a, uint32_t b, uint32_t c) {
    uint32_t d; asm("fma.rn.bf16x2 %0, %1, %2, %3;" : "=r"(d) : "r"(a), "r"(b), "r"(c)); return d;
}
__device__ __forceinline__ uint32_t i2bf2(int lo, int hi) {
    uint32_t d; asm("cvt.rn.bf16x2.f32 %0, %1, %2;" : "=r"(d) : "f"((float)hi), "f"((float)lo)); return d;
}
__device__ __forceinline__ uint32_t rope2(uint32_t x, uint32_t c, uint32_t y, uint32_t s, uint32_t sg) {
    return bfma(bmul(y, s), sg, bmul(x, c));
}
__device__ __forceinline__ void mma_bf16(float (&c)[4], uint32_t a0, uint32_t a1, uint32_t a2, uint32_t a3,
                                         uint32_t b0, uint32_t b1) {
    asm("mma.sync.aligned.m16n8k16.row.col.f32.bf16.bf16.f32 {%0,%1,%2,%3}, {%4,%5,%6,%7}, {%8,%9}, {%0,%1,%2,%3};"
        : "+f"(c[0]), "+f"(c[1]), "+f"(c[2]), "+f"(c[3])
        : "r"(a0), "r"(a1), "r"(a2), "r"(a3), "r"(b0), "r"(b1));
}
__device__ __forceinline__ void mail_put(uint32_t* p, float x, uint32_t tag) {
    asm volatile("st.relaxed.gpu.global.u32 [%0], %1;" ::"l"(p), "r"((__float_as_uint(x) & ~3u) | tag) : "memory");
}

#define TS(i)
#define TS_ONCE(i)

#define NO_COMPUTE(x) x
#define NO_COMPUTE_K(x) x
#define CVT(x) (float)(x)
struct Claim { uint32_t head, tile0, piece, sh, off; int ntiles; };

__device__ __forceinline__ Claim decode_claim(uint32_t c) {
    Claim cl;
    cl.sh = cl.off = 0;
    if (c < C_S) {
        cl.head = c / NM; cl.piece = c - cl.head * NM; cl.tile0 = cl.head * TPH + cl.piece * MAINP;
        cl.ntiles = cl.piece < NM - 1 ? MAINP : TPH - (NM - 1) * MAINP - semi_size(cl.head) - fin_size(cl.head);
        if (cl.piece < ((NM - 1) >> GSH << GSH)) {
            cl.sh = GSH; cl.off = cl.piece & ((1 << GSH) - 1); cl.tile0 -= cl.off * MAINP;
        }
    } else {
        cl.head = (c - C_S) % NHEAD; cl.piece = 0;
        cl.ntiles = fin_size(cl.head); cl.tile0 = (cl.head + 1) * TPH - cl.ntiles;
        if (c < C_F) { cl.ntiles = semi_size(cl.head); cl.tile0 -= cl.ntiles; }
    }
    return cl;
}

struct Params {
    const int* qk; const __nv_bfloat16* kcos; const __nv_bfloat16* ksin; const int* qv;
    const __nv_bfloat16* ks; const __nv_bfloat16* kz; const __nv_bfloat16* vs; const __nv_bfloat16* vz;
    const __nv_bfloat16* q; const __nv_bfloat16* qcos; const __nv_bfloat16* qsin;
    __nv_bfloat16* out;
};

constexpr float NEG = -3.0e38f;
constexpr float LOG2E = 1.4426950408889634f;
constexpr int F_NT = 31, F_FIRST = 32, F_LAST = 64, F_SEMI = 128, F_FIN = 256, F_SEGEND = 512, F_END = 1024;
static_assert(NHEAD * NM * REC < (1 << 20), "batch descriptor");

__global__ void __launch_bounds__(NTHREADS, 1)
kv_rope_decode_kernel(const Params p) {
    extern __shared__ __align__(128) unsigned char smem[];
    if (threadIdx.x >= NWARPS * 32 && elect_one()) {
        l2_prefetch(p.kcos + (blockIdx.x % (TPH / 2)) * (2 * TR * D), 2 * CBYTES);
        l2_prefetch(p.ksin + (blockIdx.x % (TPH / 2)) * (2 * TR * D), 2 * CBYTES);
        uint64_t pol;
        asm volatile("createpolicy.fractional.L2::evict_first.b64 %0, 1.0;" : "=l"(pol));
        const uint32_t h = blockIdx.x / NM, pc = blockIdx.x - h * NM;
        const uint32_t off = pc < ((NM - 1) >> GSH << GSH) ? pc & ((1 << GSH) - 1) : 0;
        l2_prefetch(p.qk + (size_t)(h * TPH + (pc - off) * MAINP + off * CFG_PF0) * (TR * D), CFG_PF0 * KBYTES, pol);
    }
    const int w = __shfl_sync(0xffffffffu, threadIdx.x >> 5, 0), lane = threadIdx.x & 31;
    if (w == NWARPS) return;
    const uint32_t sb = __shfl_sync(0xffffffffu, smem_u32(smem), 0);
    const uint32_t bar = sb + OFF_BAR;

    const int grp = w - (w > W_PROD);
    if (grp < 7 && w != W_PROD && elect_one()) {
        const uint32_t cnt = grp == 4 ? 4 : grp == 5 ? NKW + NVW : grp == 6 ? NVW : 1;
#pragma unroll
        for (int i = 0; i < 16; i++) mbar_init(bar + grp * 128 + i * 8, cnt);
        asm volatile("fence.mbarrier_init.release.cluster;" ::: "memory");
    }
    asm volatile("bar.sync 0, %0;" ::"n"(NWARPS * 32) : "memory");

    if ((unsigned)(w - W_V) < NVW) {
        const int v = w - W_V, g = lane >> 3, l = lane & 7;
        const bool up = lane & 16, up2 = lane & 8;
        const uint32_t oV = pin(sb + OFF_V + g * (2 * D * 4) + v * (NB * 128) + l * 16), oP = pin(S_LG + g * 8);
        const uint32_t col = pin(v * (NB * 32) + l * 4 + (up ? 2 : 0) + (up2 ? 1 : 0));
        __nv_bfloat16* const outp = pin(p.out + col);
        uint32_t* const mailp = pin(g_mail + col);
        float acc[4 * NB];
#pragma unroll
        for (int i = 0; i < 4 * NB; i++) acc[i] = 0.f;
        uint32_t vslot = 0, seg = 0, vph = 0;
        uint32_t s = sb + OFF_SEG, t0 = 0;
        mbar_wait(bar + B_PR, 0);
        uint2 bd = lds64(s + S_BD);
        uint2 pv = lds64(s + oP);
        bool ready = false;
        int4 x0[NB], x1[NB];
        auto load_tile = [&]() {
            const uint32_t t = oV + vslot * KBYTES;
            if (!ready) mbar_wait(bar + B_FV + vslot * 8, vph);
            TS_ONCE(1); TS(5);
#pragma unroll
            for (int j = 0; j < NO_COMPUTE(NB); j++) {
                x0[j] = lds128(t + j * 128);
                x1[j] = lds128(t + 768 + j * 128);
            }
            __syncwarp();
            if (lane == 0) mbar_arrive(bar + B_EV + vslot * 8);
            if (++vslot == NV) { vslot = 0; vph ^= 1; }
            ready = mbar_test(bar + B_FV + vslot * 8, vph);
        };
        auto fma_tile = [&]() {
            const float pv0 = __uint_as_float(pv.x), pv1 = __uint_as_float(pv.y);
#pragma unroll
            for (int j = 0; j < NO_COMPUTE(NB); j++) {
                acc[j * 4 + 0] = fmaf(pv1, CVT(x1[j].x), fmaf(pv0, CVT(x0[j].x), acc[j * 4 + 0]));
                acc[j * 4 + 1] = fmaf(pv1, CVT(x1[j].y), fmaf(pv0, CVT(x0[j].y), acc[j * 4 + 1]));
                acc[j * 4 + 2] = fmaf(pv1, CVT(x1[j].z), fmaf(pv0, CVT(x0[j].z), acc[j * 4 + 2]));
                acc[j * 4 + 3] = fmaf(pv1, CVT(x1[j].w), fmaf(pv0, CVT(x0[j].w), acc[j * 4 + 3]));
            }
        };
        for (uint32_t batch = 1; !(bd.y & F_END); batch++) {
            TS(3);
            const uint32_t n = bd.y & F_NT, sbar = bar + (seg % NSEG) * 8;
            const bool segend = bd.y & F_SEGEND;
            const uint32_t seg2 = seg + segend, t2 = segend ? 0 : t0 + n;
            const uint32_t s2 = sb + OFF_SEG + (seg2 % NSEG) * SEG_BYTES;
#pragma unroll
            for (int i = 0; i < 4 * NB; i++) acc[i] *= __uint_as_float(bd.x);
#pragma unroll 1
            for (uint32_t i = 1; i < n; i++) {
                load_tile();
                const uint2 pn = lds64(s + oP + (t0 + i) * (TR * 4));
                fma_tile();
                pv = pn;
            }
            load_tile();
            const bool early = mbar_test(sbar + B_FC, (seg / NSEG) & 1);
            const bool next = mbar_test(bar + B_PR + (batch % NBAT) * 8, (batch / NBAT) & 1);
            fma_tile();
            int4 cf;
            uint32_t gv[NB];
            uint2 bn, pn;
            if (early) {
                cf = lds128(s + S_CF);
#pragma unroll
                for (int j = 0; j < NB; j++) gv[j] = lds32(s + S_G + (col + j * 32) * 4);
            }
            if (bd.y & F_LAST) {
                float o[NB];
#pragma unroll
                for (int j = 0; j < NB; j++) {
                    const float u0 = (up ? acc[j * 4 + 2] : acc[j * 4 + 0]) + __shfl_xor_sync(0xffffffffu, up ? acc[j * 4 + 0] : acc[j * 4 + 2], 16);
                    const float u1 = (up ? acc[j * 4 + 3] : acc[j * 4 + 1]) + __shfl_xor_sync(0xffffffffu, up ? acc[j * 4 + 1] : acc[j * 4 + 3], 16);
                    o[j] = (up2 ? u1 : u0) + __shfl_xor_sync(0xffffffffu, up2 ? u0 : u1, 8);
                }
                if (!early) {
                    mbar_wait(sbar + B_FC, (seg / NSEG) & 1);
                    cf = lds128(s + S_CF);
#pragma unroll
                    for (int j = 0; j < NB; j++) gv[j] = lds32(s + S_G + (col + j * 32) * 4);
                }
#pragma unroll
                for (int j = 0; j < NB; j++) {
                    const float gj = (bd.y & (F_SEMI | F_FIN)) ? __uint_as_float(gv[j]) : 0.f;
                    o[j] = fmaf(o[j], __int_as_float(cf.x), fmaf(gj, __int_as_float(cf.y), __int_as_float(cf.z)));
                }
                if (bd.y & F_FIN) {
#pragma unroll
                    for (int j = 0; j < NB; j++) {
                        const __nv_bfloat16 r = __float2bfloat16_rn(o[j]);
                        asm volatile("st.global.b16 [%0], %1;" ::"l"(outp + (bd.y >> 12) + j * 32), "h"(*(const uint16_t*)&r) : "memory");
                    }
                } else {
#pragma unroll
                    for (int j = 0; j < NB; j++) mail_put(mailp + (bd.y >> 12) + j * 32, o[j], cf.w & 3);
                    if (col < REC - D) mail_put(mailp + (bd.y >> 12) + D, __int_as_float(cf.w), cf.w & 3);
                }
#pragma unroll
                for (int i = 0; i < 4 * NB; i++) acc[i] = 0.f;
            }
            if (next) {
                bn = lds64(s2 + S_BD + t2 * 8);
                pn = lds64(s2 + oP + t2 * (TR * 4));
            }
            if (segend) {
                if (!(bd.y & F_LAST)) mbar_wait(sbar + B_FC, (seg / NSEG) & 1);
                __syncwarp();
                if (lane == 0) mbar_arrive(sbar + B_SE);
            }
            TS(6);
            if (!next) {
                mbar_wait(bar + B_PR + (batch % NBAT) * 8, (batch / NBAT) & 1);
                bn = lds64(s2 + S_BD + t2 * 8);
                pn = lds64(s2 + oP + t2 * (TR * 4));
            }
            bd = bn; pv = pn; s = s2; t0 = t2; seg = seg2;
        }
    } else if (w == W_S) {
        float m = NEG, lsum = 0.f, corr = 0.f;
        uint32_t batch = 0;
        for (uint32_t seg = 0;; seg++) {
            const uint32_t s = sb + OFF_SEG + (seg % NSEG) * SEG_BYTES, sbar = bar + (seg % NSEG) * 8;
            const uint32_t sph = (seg / NSEG) & 1;
            mbar_wait(sbar + B_HDR, sph);
            const int4 desc = lds128(s + S_DESC);
            if (desc.y & F_END) {
                if (lane == 0) {
                    sts64(s + S_BD, 0.f, __uint_as_float(F_END));
                    mbar_arrive(bar + B_PR + (batch % NBAT) * 8);
                }
                break;
            }
            if (desc.y & F_FIRST) { m = NEG; lsum = 0.f; corr = 0.f; }
            const uint32_t index = (desc.y & F_FIN) ? desc.x * D : (desc.x * NM + desc.z) * REC;
            const int nt = desc.y & F_NT, bs = 1 << ((desc.y & F_FIN) ? CFG_BF : CFG_BM);
#pragma unroll 1
            for (int t0 = 0; t0 < nt; t0 += bs, batch++) {
                const int n = min(bs, nt - t0);
                const bool valid = lane < n * TR;
                const uint32_t tl = t0 + (valid ? lane >> 3 : 0), la = s + S_LG + (tl * TR + (lane & 7)) * 4;
                const uint32_t sc = s + S_SC + (((tl << (desc.w & 255)) + (desc.w >> 8)) * TR + (lane & 7)) * 2;
                const float vs = bf_lo(lds16(sc + 2 * SCB)), vz = bf_lo(lds16(sc + 3 * SCB));
                mbar_wait(bar + B_LG + (batch % NBAT) * 8, (batch / NBAT) & 1);
                const float dot = __uint_as_float(lds32(la)) + __uint_as_float(lds32(la + SEGT * TR * 4));
                const float sv = rbf(rbf(dot) * 0.07216878364870322f) * LOG2E;
                int key = __float_as_int(fmaxf(m, sv));
                key ^= (key >> 31) & 0x7fffffff;
                key = __reduce_max_sync(0xffffffffu, key);
                const float mn = __int_as_float(key ^ ((key >> 31) & 0x7fffffff));
                const float alpha = ex2(m - mn), pr = ex2(sv - mn), pv = pr * vs;
                m = mn;
                if (valid) sts32(la, pv);
                if (lane == 0)
                    sts64(s + S_BD + t0 * 8, alpha,
                          __uint_as_float(n | (t0 + n < nt ? 0 : index << 12 | F_SEGEND | (desc.y & (F_LAST | F_SEMI | F_FIN)))));
                __syncwarp();
                if (lane == 0) mbar_arrive(bar + B_PR + (batch % NBAT) * 8);
                lsum = fmaf(lsum, alpha, valid ? pr : 0.f);
                corr = fmaf(corr, alpha, valid ? pv * vz : 0.f);
                TS(3);
            }
            float L = lsum, C = corr;
            if (desc.y & F_LAST) {
#pragma unroll
                for (int o = 16; o > 0; o >>= 1) {
                    L += __shfl_xor_sync(0xffffffffu, L, o);
                    C += __shfl_xor_sync(0xffffffffu, C, o);
                }
            }
            mbar_wait(sbar + B_GD, sph);
            if (desc.y & F_LAST) {
                const uint32_t tag = lds32(sb + OFF_TAG) | ((desc.y & F_SEMI) ? 2 : 0);
                const float gl = (desc.y & (F_SEMI | F_FIN)) ? __uint_as_float(lds32(s + S_G + D * 4)) : -3.4e38f;
                const float M = fmaxf(m, gl), e = ex2(m - M), a = ex2(gl - M);
                const float W = fmaf(L, e, a), inv = rcp(W);
                if (lane == 0)
                    sts128(s + S_CF, __float_as_uint(e * inv), __float_as_uint(a * inv), __float_as_uint(-C * e * inv),
                           (__float_as_uint(M + lg2(W)) & ~3u) | tag);
            }
            __syncwarp();
            if (lane == 0) mbar_arrive(sbar + B_FC);
            TS(4);
        }
    } else if ((unsigned)(w - W_G) < NGW) {
        if (w == W_G) {
            if (lane == 0) sts32(sb + OFF_TAG, __uint_as_float(~*(volatile unsigned int*)&g_epoch & 1));
        } else {
            mbar_wait(bar + B_GD, 0);
        }
        for (uint32_t seg = w - W_G;; seg += NGW) {
            const uint32_t s = sb + OFF_SEG + (seg % NSEG) * SEG_BYTES, sbar = bar + (seg % NSEG) * 8;
            mbar_wait(sbar + B_HDR, (seg / NSEG) & 1);
            const int4 desc = lds128(s + S_DESC);
            if (desc.y & F_END) break;
            TS(1);
            if (desc.y & (F_SEMI | F_FIN)) {
                const uint32_t tag = lds32(sb + OFF_TAG) | ((desc.y & F_FIN) ? 2 : 0);
                const int cnt = (desc.y & F_FIN) ? 1 : NM;
                const uint32_t* mail = g_mail + desc.x * (NM * REC);
                float M = NEG, W = 0.f, O[6] = {0.f, 0.f, 0.f, 0.f, 0.f, 0.f};
#pragma unroll 1
                for (int i0 = 0; i0 < cnt; i0 += 5, mail += 5 * REC) {
                    uint2 pk[15];
                    uint32_t ls[5], stale;
                    int it = 0;
                    do {
                        stale = 0;
#pragma unroll
                        for (int i = 0; i < 5; i++) {
                            ls[i] = 0xff7ffffcu | tag;
                            pk[3 * i] = pk[3 * i + 1] = pk[3 * i + 2] = make_uint2(tag, tag);
                            if (i0 + i < cnt) {
                                asm volatile("ld.relaxed.gpu.global.u32 %0, [%1];" : "=r"(ls[i]) : "l"(mail + i * REC + D) : "memory");
#pragma unroll
                                for (int k = 0; k < 3; k++)
                                    asm volatile("ld.relaxed.gpu.global.v2.u32 {%0,%1}, [%2];"
                                                 : "=r"(pk[3 * i + k].x), "=r"(pk[3 * i + k].y)
                                                 : "l"(mail + i * REC + k * 64 + lane * 2) : "memory");
                            }
                        }
#pragma unroll
                        for (int i = 0; i < 5; i++) stale |= ls[i] ^ tag;
#pragma unroll
                        for (int i = 0; i < 15; i++) stale |= (pk[i].x ^ tag) | (pk[i].y ^ tag);
                        if (++it > (1 << 22)) __trap();
                    } while (stale & 3);
                    float Mn = M;
#pragma unroll
                    for (int i = 0; i < 5; i++) Mn = fmaxf(Mn, __uint_as_float(ls[i]));
                    const float a = ex2(M - Mn);
                    M = Mn; W *= a;
#pragma unroll
                    for (int i = 0; i < 6; i++) O[i] *= a;
#pragma unroll
                    for (int i = 0; i < 5; i++) {
                        const float e = ex2(__uint_as_float(ls[i]) - M);
                        W += e;
#pragma unroll
                        for (int k = 0; k < 3; k++) {
                            O[2 * k] = fmaf(e, __uint_as_float(pk[3 * i + k].x), O[2 * k]);
                            O[2 * k + 1] = fmaf(e, __uint_as_float(pk[3 * i + k].y), O[2 * k + 1]);
                        }
                    }
                }
                const float inv = rcp(W);
#pragma unroll
                for (int k = 0; k < 3; k++) sts64(s + S_G + k * 256 + lane * 8, O[2 * k] * inv, O[2 * k + 1] * inv);
                if (lane == 0) sts32(s + S_G + D * 4, M + lg2(W));
            }
            __syncwarp();
            if (lane == 0) mbar_arrive(sbar + B_GD);
            TS(2);
        }
    } else if ((w >> 2) == 0) {
        const int g = lane >> 3, l = lane & 7, godd = g & 1;
        const uint32_t sgA = pin(godd ? 0x3f803f80u : 0xbf80bf80u), sgB = pin(godd ? 0xbf80bf80u : 0x3f803f80u);
        const uint32_t oKA = pin(sb + g * (2 * D * 4) + l * 16 + godd * 384), oKB = pin(oKA - godd * 768 + 384);
        const uint32_t oCA = pin(sb + T_C + g * (2 * D * 2) + l * 8 + godd * 192), oCB = pin(oCA - godd * 384 + 192);
        const uint32_t oL = pin(S_LG + (l >> 2) * (SEGT * TR * 4) + g * 8);
        uint2 qr[6];
        uint32_t kslot = w, j = kslot, batch0 = 0, kph = 0;
        for (uint32_t seg = 0;; seg++) {
            const uint32_t s = sb + OFF_SEG + (seg % NSEG) * SEG_BYTES, sbar = bar + (seg % NSEG) * 8;
            mbar_wait(sbar + B_HDR, (seg / NSEG) & 1);
            const uint32_t desc = lds32(s + S_DESC + 4), geo = lds32(s + S_DESC + 12);
            if (desc & F_END) break;
            const uint32_t nt = desc & F_NT, bsh = (desc & F_FIN) ? CFG_BF : CFG_BM;
            if (desc & F_FIRST) {
#pragma unroll
                for (int i = 0; i < 3; i++) {
                    const uint32_t oa = l * 8 + godd * 192 + i * 64, ob = oa + 192 - godd * 384;
                    const uint2 a = lds64(s + S_Q + oa), b = lds64(s + S_Q + ob);
                    const uint2 ca = lds64(sb + OFF_QT + oa), cb = lds64(sb + OFF_QT + ob);
                    const uint2 sa = lds64(sb + OFF_QT + QBYTES + oa), sbv = lds64(sb + OFF_QT + QBYTES + ob);
                    qr[i].x = rope2(a.x, ca.x, b.x, sa.x, sgA);
                    qr[i].y = rope2(a.y, ca.y, b.y, sa.y, sgA);
                    qr[i + 3].x = rope2(b.x, cb.x, a.x, sbv.x, sgB);
                    qr[i + 3].y = rope2(b.y, cb.y, a.y, sbv.y, sgB);
                }
            }
            for (; j < nt; j += NKW) {
                const uint32_t t = kslot * KSLOT;
                const uint32_t sc = s + S_SC + ((j << (geo & 255)) + (geo >> 8)) * (TR * 2) + g * 4;
                const uint32_t sks = lds32(sc), skz = lds32(sc + SCB);
                const uint32_t ks2[2] = {__byte_perm(sks, 0, 0x1010), __byte_perm(sks, 0, 0x3232)};
                const uint32_t kz2[2] = {__byte_perm(skz, 0, 0x1010), __byte_perm(skz, 0, 0x3232)};
                mbar_wait(bar + B_FK + kslot * 8, kph);
                TS_ONCE(1); TS(3);
                float cA[4] = {0.f, 0.f, 0.f, 0.f}, cB[4] = {0.f, 0.f, 0.f, 0.f};
#pragma unroll
                for (int jj = 0; jj < NO_COMPUTE_K(3); jj++) {
                    uint2 ra[2], rb[2];
#pragma unroll
                    for (int ps = 0; ps < 2; ps++) {
                        const int4 xa = lds128(t + oKA + ps * 768 + jj * 128);
                        const int4 xb = lds128(t + oKB + ps * 768 + jj * 128);
                        const uint2 ca = lds64(t + oCA + ps * 384 + jj * 64);
                        const uint2 cb = lds64(t + oCB + ps * 384 + jj * 64);
                        const uint2 sa = lds64(t + oCA + CBYTES + ps * 384 + jj * 64);
                        const uint2 sbv = lds64(t + oCB + CBYTES + ps * 384 + jj * 64);
                        const uint32_t a0 = bmul(bsub(i2bf2(xa.x, xa.y), kz2[ps]), ks2[ps]);
                        const uint32_t a1 = bmul(bsub(i2bf2(xa.z, xa.w), kz2[ps]), ks2[ps]);
                        const uint32_t b0 = bmul(bsub(i2bf2(xb.x, xb.y), kz2[ps]), ks2[ps]);
                        const uint32_t b1 = bmul(bsub(i2bf2(xb.z, xb.w), kz2[ps]), ks2[ps]);
                        ra[ps].x = rope2(a0, ca.x, b0, sa.x, sgA);
                        ra[ps].y = rope2(a1, ca.y, b1, sa.y, sgA);
                        rb[ps].x = rope2(b0, cb.x, a0, sbv.x, sgB);
                        rb[ps].y = rope2(b1, cb.y, a1, sbv.y, sgB);
                    }
                    mma_bf16(cA, ra[0].x, ra[1].x, ra[0].y, ra[1].y, qr[jj].x, qr[jj].y);
                    mma_bf16(cB, rb[0].x, rb[1].x, rb[0].y, rb[1].y, qr[jj + 3].x, qr[jj + 3].y);
                }
                __syncwarp();
                if (lane == 0) mbar_arrive(bar + B_EK + kslot * 8);
                TS_ONCE(2);
                if ((lane & 3) == g)
                    sts64(s + oL + j * (TR * 4),
                          l < 4 ? cA[0] + cB[0] : cA[1] + cB[1], l < 4 ? cA[2] + cB[2] : cA[3] + cB[3]);
                __syncwarp();
                if (lane == 0)
                    mbar_arrive(bar + B_LG + ((batch0 + (j >> bsh)) % NBAT) * 8, j == nt - 1 ? 4 - ((j << (2 - bsh)) & 3) : 4 >> bsh);
                TS(4);
                kslot += NKW;
                if (kslot >= NK) { kslot -= NK; kph ^= 1; }
            }
            j -= nt;
            batch0 += (nt + (1 << bsh) - 1) >> bsh;
            __syncwarp();
            if (lane == 0) mbar_arrive(sbar + B_SE);
        }
    } else {
        if (elect_one()) {
            uint64_t pol;
            asm volatile("createpolicy.fractional.L2::evict_first.b64 %0, 1.0;" : "=l"(pol));
            uint32_t kslot = 0, vslot = 0, seg = 0, kph = 1, vph = 1;
            uint32_t win = NV;
            int pend[LEAD];
#pragma unroll
            for (int i = 0; i < LEAD; i++) pend[i] = -1;
            auto push_v = [&](int tile) {
                if (pend[0] >= 0) {
                    const uint32_t b = bar + vslot * 8;
                    mbar_wait(b + B_EV, vph);
                    mbar_expect(b + B_FV, KBYTES);
                    bulk_stream(sb + OFF_V + vslot * KBYTES, p.qv + (size_t)pend[0] * (TR * D), KBYTES, b + B_FV, pol);
                    if (++vslot == NV) { vslot = 0; vph ^= 1; }
                }
#pragma unroll
                for (int i = 0; i + 1 < LEAD; i++) pend[i] = pend[i + 1];
                pend[LEAD - 1] = tile;
            };
            asm volatile("mbarrier.expect_tx.shared::cta.b64 [%0], %1;" ::"r"(bar + B_HDR), "r"(2 * QBYTES) : "memory");
            bulk_plain(sb + OFF_QT, p.qcos, QBYTES, bar + B_HDR);
            bulk_plain(sb + OFF_QT + QBYTES, p.qsin, QBYTES, bar + B_HDR);
            uint32_t c = blockIdx.x;
            TS(1);
            while (c < NCLAIM) {
                const Claim cl = decode_claim(c);
                uint32_t tile = cl.tile0 + cl.off;
                auto tiles = [&](int cnt) {
#pragma unroll 1
                    for (int j = 0; j < cnt; j++, tile += 1u << cl.sh) {
                        push_v(tile);
                        const uint32_t t = sb + kslot * KSLOT, b = bar + kslot * 8;
                        const uint32_t ro = (tile % TPH) * (TR * D);
                        mbar_wait(b + B_EK, kph);
                        mbar_expect(b + B_FK, KSLOT);
                        bulk_stream(t, p.qk + (size_t)tile * (TR * D), KBYTES, b + B_FK, pol);
                        bulk_plain(t + T_C, p.kcos + ro, CBYTES, b + B_FK);
                        bulk_plain(t + T_S, p.ksin + ro, CBYTES, b + B_FK);
                        TS_ONCE(2); TS(3);
                        if (++kslot == NK) { kslot = 0; kph ^= 1; }
                    }
                };
                int nt;
                for (int left = cl.ntiles;; left -= nt) {
                    nt = min(SEGT, left);
                    const bool first = left == cl.ntiles, last = left == nt;
                    const uint32_t s = sb + OFF_SEG + (seg % NSEG) * SEG_BYTES, b = bar + (seg % NSEG) * 8;
                    mbar_wait(b + B_SE, ((seg / NSEG) & 1) ^ 1);
                    sts128(s + S_DESC, cl.head,
                           nt | (first ? F_FIRST : 0) | (last ? F_LAST : 0) | (c >= C_F ? F_FIN : c >= C_S ? F_SEMI : 0),
                           cl.piece, cl.sh | cl.off << 8);
                    const uint32_t scb = nt * TR * 2 << cl.sh;
                    const uint32_t r = (tile - cl.off) * TR;
                    mbar_expect(b + B_HDR, 4 * scb + (first ? QBYTES : 0));
                    if (first) bulk_plain(s + S_Q, p.q + cl.head * D, QBYTES, b + B_HDR);
                    bulk_plain(s + S_SC, p.ks + r, scb, b + B_HDR);
                    bulk_plain(s + S_SC + SCB, p.kz + r, scb, b + B_HDR);
                    bulk_plain(s + S_SC + 2 * SCB, p.vs + r, scb, b + B_HDR);
                    bulk_plain(s + S_SC + 3 * SCB, p.vz + r, scb, b + B_HDR);
                    seg++;
                    tiles(last ? max(nt - LA, 0) : nt);
                    if (last) break;
                }
                if (c == blockIdx.x) mbar_wait(bar + B_GD, 0);
                const unsigned nx = atomicInc(&g_queue, NCLAIM - 1);
                tiles(min(nt, LA));
                if (nx == NCLAIM - 1) g_epoch = lds32(sb + OFF_TAG);
                c = gridDim.x + nx;
            }
            TS(4);
#pragma unroll 1
            for (int i = 0; i < LEAD; i++) push_v(-1);
            TS(5);
#pragma unroll 1
            for (int i = 0; i < NGW; i++, seg++) {
                const uint32_t s = sb + OFF_SEG + (seg % NSEG) * SEG_BYTES, b = bar + (seg % NSEG) * 8;
                mbar_wait(b + B_SE, ((seg / NSEG) & 1) ^ 1);
                sts128(s + S_DESC, 0, F_END, 0, 0);
                mbar_arrive(b + B_HDR);
            }
        }
    }
}

}

extern "C" void kernel_launch(void* const* d_in, const int* in_sizes, int n_in, void* d_out, int out_size) {
    (void)in_sizes; (void)n_in; (void)out_size;
    static int sms = 0;
    if (sms == 0) {
        int dev = 0;
        cudaGetDevice(&dev);
        cudaDeviceGetAttribute(&sms, cudaDevAttrMultiProcessorCount, dev);
        cudaFuncSetAttribute(kv_rope_decode_kernel, cudaFuncAttributeMaxDynamicSharedMemorySize, SMEM_BYTES);
    }
    Params p;
    p.q    = (const __nv_bfloat16*)d_in[0];
    p.qk   = (const int*)d_in[1];
    p.ks   = (const __nv_bfloat16*)d_in[2];
    p.kz   = (const __nv_bfloat16*)d_in[3];
    p.qv   = (const int*)d_in[4];
    p.vs   = (const __nv_bfloat16*)d_in[5];
    p.vz   = (const __nv_bfloat16*)d_in[6];
    p.qcos = (const __nv_bfloat16*)d_in[7];
    p.qsin = (const __nv_bfloat16*)d_in[8];
    p.kcos = (const __nv_bfloat16*)d_in[9];
    p.ksin = (const __nv_bfloat16*)d_in[10];
    p.out  = (__nv_bfloat16*)d_out;
    kv_rope_decode_kernel<<<sms, NTHREADS, SMEM_BYTES>>>(p);
}
```

```cpp
#include <cuda_runtime.h>
#include <cuda_bf16.h>
#include <stdint.h>

namespace {

#define CFG_NKW 4
#define CFG_NVW 6
#define CFG_NK 8
#define CFG_NV 4
#define CFG_LEAD 5
#define CFG_MAIN 16
#define CFG_SEMI 0xfdb9
#define CFG_FIN 0x7531
#define CFG_GSH 2
#define CFG_BM 2
#define CFG_BF 2
#define CFG_LA 3
#define CFG_PF0 3

constexpr int D      = 192;
constexpr int SKV    = 2048;
constexpr int NHEAD  = 256;
constexpr int TR     = 8;
constexpr int TPH    = SKV / TR;
constexpr int NKW    = CFG_NKW;
constexpr int NVW    = CFG_NVW;
constexpr int NB     = 6 / NVW;
constexpr int NGW    = 2;
constexpr int NK     = CFG_NK;
constexpr int NV     = CFG_NV;
constexpr int LEAD   = CFG_LEAD;
constexpr int NSEG   = 8;
constexpr int SEGT   = 16;
constexpr int NBAT   = 16;
constexpr int W_V = NKW, W_PROD = W_V + NVW, W_S = W_PROD + 1, W_G = W_S + 1, NWARPS = W_G + NGW;
constexpr int NTHREADS = NWARPS * 32 + 32;

constexpr int MAINP  = CFG_MAIN;
constexpr int GSH    = CFG_GSH;
constexpr int LA     = CFG_LA;
__host__ __device__ constexpr int semi_size(int h) { return ((CFG_SEMI >> (12 - 4 * (h >> 6))) & 15) + 1; }
__host__ __device__ constexpr int fin_size(int h) { return ((CFG_FIN >> (12 - 4 * (h >> 6))) & 15) + 1; }
constexpr int NM     = (TPH - semi_size(0) - fin_size(0) + MAINP - 1) / MAINP;
constexpr int C_S    = NHEAD * NM, C_F = C_S + NHEAD, NCLAIM = C_F + NHEAD;
constexpr bool sizes_ok(int h) { return h >= NHEAD || (semi_size(h) + fin_size(h) < TPH - (NM - 1) * MAINP && sizes_ok(h + 64)); }
static_assert(sizes_ok(0), "schedule");

constexpr int KBYTES = TR * D * 4;
constexpr int CBYTES = TR * D * 2;
constexpr int QBYTES = D * 2;
constexpr int T_C = KBYTES, T_S = T_C + CBYTES, KSLOT = T_S + CBYTES;
constexpr int SCB = SEGT * TR * 2 << GSH;
static_assert(GSH == 0 || MAINP == SEGT, "interleaved pieces are single segments");
constexpr int S_Q = 0, S_SC = QBYTES, S_DESC = S_SC + 4 * SCB, S_BD = S_DESC + 16,
              S_LG = S_BD + SEGT * 8, S_PV = S_LG + SEGT * TR * 16, S_G = S_PV + SEGT * TR * 4,
              S_CF = S_G + (D + 4) * 4,
              SEG_BYTES = (S_CF + 16 + 127) / 128 * 128;
constexpr int OFF_V = NK * KSLOT, OFF_SEG = OFF_V + NV * KBYTES, OFF_QT = OFF_SEG + NSEG * SEG_BYTES,
              OFF_TAG = OFF_QT + 2 * QBYTES, OFF_BAR = OFF_TAG + 16;
constexpr int B_FK = 0, B_PR = 128, B_HDR = 256, B_GD = 320, B_FC = 384, B_FV = 448, B_LG = 512,
              B_SE = 640, B_EV = 768, B_EK = 896;
constexpr int SMEM_BYTES = OFF_BAR + 1024;
static_assert(NK <= 16 && NV <= 8 && NSEG == 8 && NBAT == 16, "barrier layout");
static_assert(SMEM_BYTES <= 232448 && SMEM_BYTES > 232448 / 2, "smem");
static_assert(NSEG % NGW == 0 && NK % (NKW / 2) == 0 && NB * NVW == 6 && NM <= 32 && LEAD >= 1, "cfg");
static_assert(LEAD + NV >= 4 && LEAD + NV < NBAT && LEAD < NSEG, "cfg");

__device__ unsigned int g_queue;
constexpr int REC = 200;
__device__ unsigned int g_epoch;
__device__ __align__(32) uint32_t g_mail[NHEAD * NM * REC];

__device__ __forceinline__ uint32_t smem_u32(const void* p) { return (uint32_t)__cvta_generic_to_shared(p); }
__device__ __forceinline__ uint32_t pin(uint32_t x) {
    return __shfl_sync(0xffffffffu, x, threadIdx.x & 31);
}
template <class T> __device__ __forceinline__ T* pin(T* p) {
    return (T*)__shfl_sync(0xffffffffu, (unsigned long long)p, threadIdx.x & 31);
}
__device__ __forceinline__ bool elect_one() {
    uint32_t pred;
    asm volatile("{\n.reg .pred p;\nelect.sync _|p, 0xffffffff;\nselp.u32 %0, 1, 0, p;\n}" : "=r"(pred));
    return pred;
}
__device__ __forceinline__ void mbar_init(uint32_t bar, uint32_t cnt) {
    asm volatile("mbarrier.init.shared::cta.b64 [%0], %1;" ::"r"(bar), "r"(cnt) : "memory");
}
__device__ __forceinline__ void mbar_expect(uint32_t bar, uint32_t bytes) {
    asm volatile("mbarrier.arrive.expect_tx.shared::cta.b64 _, [%0], %1;" ::"r"(bar), "r"(bytes) : "memory");
}
__device__ __forceinline__ void mbar_arrive(uint32_t bar) {
    asm volatile("mbarrier.arrive.shared::cta.b64 _, [%0];" ::"r"(bar) : "memory");
}
__device__ __forceinline__ void mbar_arrive(uint32_t bar, uint32_t cnt) {
    asm volatile("mbarrier.arrive.shared::cta.b64 _, [%0], %1;" ::"r"(bar), "r"(cnt) : "memory");
}
__device__ __forceinline__ bool mbar_test(uint32_t bar, uint32_t parity) {
    uint32_t ok;
    asm volatile("{\n.reg .pred p;\nmbarrier.test_wait.parity.shared::cta.b64 p, [%1], %2;\nselp.u32 %0, 1, 0, p;\n}"
                 : "=r"(ok) : "r"(bar), "r"(parity) : "memory");
    return ok;
}
__device__ __forceinline__ void mbar_wait(uint32_t bar, uint32_t parity) {
    asm volatile("{\n.reg .pred p;\n.reg .u32 n;\n"
                 "mbarrier.try_wait.parity.shared::cta.b64 p, [%0], %1;\n"
                 "@p bra DONE;\n"
                 "mov.u32 n, 0;\n"
                 "LOOP:\n"
                 "mbarrier.try_wait.parity.shared::cta.b64 p, [%0], %1;\n"
                 "@p bra DONE;\n"
                 "add.u32 n, n, 1;\n"
                 "setp.lt.u32 p, n, 0x400000;\n"
                 "@p bra LOOP;\n"
                 "trap;\n"
                 "DONE:\n}" ::"r"(bar), "r"(parity) : "memory");
}
__device__ __forceinline__ void bulk_stream(uint32_t dst, const void* src, uint32_t bytes, uint32_t bar, uint64_t pol) {
    asm volatile("cp.async.bulk.shared::cluster.global.mbarrier::complete_tx::bytes.L2::cache_hint [%0], [%1], %2, [%3], %4;"
                 ::"r"(dst), "l"(src), "r"(bytes), "r"(bar), "l"(pol) : "memory");
}
__device__ __forceinline__ void bulk_plain(uint32_t dst, const void* src, uint32_t bytes, uint32_t bar) {
    asm volatile("cp.async.bulk.shared::cluster.global.mbarrier::complete_tx::bytes [%0], [%1], %2, [%3];"
                 ::"r"(dst), "l"(src), "r"(bytes), "r"(bar) : "memory");
}
__device__ __forceinline__ void l2_prefetch(const void* src, uint32_t bytes, uint64_t pol) {
    asm volatile("cp.async.bulk.prefetch.L2.global.L2::cache_hint [%0], %1, %2;" ::"l"(src), "r"(bytes), "l"(pol) : "memory");
}
__device__ __forceinline__ void l2_prefetch(const void* src, uint32_t bytes) {
    asm volatile("cp.async.bulk.prefetch.L2.global [%0], %1;" ::"l"(src), "r"(bytes) : "memory");
}
__device__ __forceinline__ int4 lds128(uint32_t a) {
    int4 v;
    asm volatile("ld.shared.v4.s32 {%0,%1,%2,%3}, [%4];" : "=r"(v.x), "=r"(v.y), "=r"(v.z), "=r"(v.w) : "r"(a));
    return v;
}
__device__ __forceinline__ uint2 lds64(uint32_t a) {
    uint2 v;
    asm volatile("ld.shared.v2.u32 {%0,%1}, [%2];" : "=r"(v.x), "=r"(v.y) : "r"(a));
    return v;
}
__device__ __forceinline__ uint32_t lds32(uint32_t a) {
    uint32_t v;
    asm volatile("ld.shared.u32 %0, [%1];" : "=r"(v) : "r"(a));
    return v;
}
__device__ __forceinline__ uint32_t lds16(uint32_t a) {
    uint16_t v;
    asm volatile("ld.shared.u16 %0, [%1];" : "=h"(v) : "r"(a));
    return v;
}
__device__ __forceinline__ void sts32(uint32_t a, float x) {
    asm volatile("st.shared.f32 [%0], %1;" ::"r"(a), "f"(x) : "memory");
}
__device__ __forceinline__ void sts128(uint32_t a, uint32_t x, uint32_t y, uint32_t z, uint32_t w) {
    asm volatile("st.shared.v4.u32 [%0], {%1,%2,%3,%4};" ::"r"(a), "r"(x), "r"(y), "r"(z), "r"(w) : "memory");
}
__device__ __forceinline__ void sts64(uint32_t a, float x, float y) {
    asm volatile("st.shared.v2.f32 [%0], {%1,%2};" ::"r"(a), "f"(x), "f"(y) : "memory");
}
__device__ __forceinline__ float bf_lo(uint32_t v) { return __uint_as_float(v << 16); }
__device__ __forceinline__ float bf_hi(uint32_t v) { return __uint_as_float(v & 0xffff0000u); }
__device__ __forceinline__ float rbf(float x) {
    uint32_t d; asm("cvt.rn.bf16x2.f32 %0, %1, %2;" : "=r"(d) : "f"(x), "f"(0.f)); return __uint_as_float(d);
}
__device__ __forceinline__ float rcp(float x) {
    float y;
    asm("rcp.approx.ftz.f32 %0, %1;" : "=f"(y) : "f"(x));
    return y;
}
__device__ __forceinline__ float lg2(float x) {
    float y;
    asm("lg2.approx.ftz.f32 %0, %1;" : "=f"(y) : "f"(x));
    return y;
}
__device__ __forceinline__ float ex2(float x) {
    float y;
    asm("ex2.approx.ftz.f32 %0, %1;" : "=f"(y) : "f"(x));
    return y;
}
__device__ __forceinline__ uint32_t bmul(uint32_t a, uint32_t b) {
    uint32_t d; asm("mul.rn.bf16x2 %0, %1, %2;" : "=r"(d) : "r"(a), "r"(b)); return d;
}
__device__ __forceinline__ uint32_t bsub(uint32_t a, uint32_t b) {
    uint32_t d; asm("sub.rn.bf16x2 %0, %1, %2;" : "=r"(d) : "r"(a), "r"(b)); return d;
}
__device__ __forceinline__ uint32_t bfma(uint32_t a, uint32_t b, uint32_t c) {
    uint32_t d; asm("fma.rn.bf16x2 %0, %1, %2, %3;" : "=r"(d) : "r"(a), "r"(b), "r"(c)); return d;
}
__device__ __forceinline__ uint32_t i2bf2(int lo, int hi) {
    uint32_t d; asm("cvt.rn.bf16x2.f32 %0, %1, %2;" : "=r"(d) : "f"((float)hi), "f"((float)lo)); return d;
}
__device__ __forceinline__ uint32_t rope2(uint32_t x, uint32_t c, uint32_t y, uint32_t s, uint32_t sg) {
    return bfma(bmul(y, s), sg, bmul(x, c));
}
__device__ __forceinline__ void mma_bf16(float (&c)[4], uint32_t a0, uint32_t a1, uint32_t a2, uint32_t a3,
                                         uint32_t b0, uint32_t b1) {
    asm("mma.sync.aligned.m16n8k16.row.col.f32.bf16.bf16.f32 {%0,%1,%2,%3}, {%4,%5,%6,%7}, {%8,%9}, {%0,%1,%2,%3};"
        : "+f"(c[0]), "+f"(c[1]), "+f"(c[2]), "+f"(c[3])
        : "r"(a0), "r"(a1), "r"(a2), "r"(a3), "r"(b0), "r"(b1));
}
__device__ __forceinline__ void mail_put(uint32_t* p, float x, uint32_t tag) {
    asm volatile("st.relaxed.gpu.global.u32 [%0], %1;" ::"l"(p), "r"((__float_as_uint(x) & ~3u) | tag) : "memory");
}

#define TS(i)
#define TS_ONCE(i)

#define NO_COMPUTE(x) x
#define NO_COMPUTE_K(x) x
#define CVT(x) (float)(x)
struct Claim { uint32_t head, tile0, piece, sh, off; int ntiles; };

__device__ __forceinline__ Claim decode_claim(uint32_t c) {
    Claim cl;
    cl.sh = cl.off = 0;
    if (c < C_S) {
        cl.head = c / NM; cl.piece = c - cl.head * NM; cl.tile0 = cl.head * TPH + cl.piece * MAINP;
        cl.ntiles = cl.piece < NM - 1 ? MAINP : TPH - (NM - 1) * MAINP - semi_size(cl.head) - fin_size(cl.head);
        if (cl.piece < ((NM - 1) >> GSH << GSH)) {
            cl.sh = GSH; cl.off = cl.piece & ((1 << GSH) - 1); cl.tile0 -= cl.off * MAINP;
        }
    } else {
        cl.head = (c - C_S) % NHEAD; cl.piece = 0;
        cl.ntiles = fin_size(cl.head); cl.tile0 = (cl.head + 1) * TPH - cl.ntiles;
        if (c < C_F) { cl.ntiles = semi_size(cl.head); cl.tile0 -= cl.ntiles; }
    }
    return cl;
}

struct Params {
    const int* qk; const __nv_bfloat16* kcos; const __nv_bfloat16* ksin; const int* qv;
    const __nv_bfloat16* ks; const __nv_bfloat16* kz; const __nv_bfloat16* vs; const __nv_bfloat16* vz;
    const __nv_bfloat16* q; const __nv_bfloat16* qcos; const __nv_bfloat16* qsin;
    __nv_bfloat16* out;
};

constexpr float NEG = -3.0e38f;
constexpr float LOG2E = 1.4426950408889634f;
constexpr int F_NT = 31, F_FIRST = 32, F_LAST = 64, F_SEMI = 128, F_FIN = 256, F_SEGEND = 512, F_END = 1024;
static_assert(NHEAD * NM * REC < (1 << 20), "batch descriptor");

__global__ void __launch_bounds__(NTHREADS, 1)
kv_rope_decode_kernel(const Params p) {
    extern __shared__ __align__(128) unsigned char smem[];
    if (threadIdx.x >= NWARPS * 32 && elect_one()) {
        l2_prefetch(p.kcos + (blockIdx.x % (TPH / 2)) * (2 * TR * D), 2 * CBYTES);
        l2_prefetch(p.ksin + (blockIdx.x % (TPH / 2)) * (2 * TR * D), 2 * CBYTES);
        uint64_t pol;
        asm volatile("createpolicy.fractional.L2::evict_first.b64 %0, 1.0;" : "=l"(pol));
        const uint32_t h = blockIdx.x / NM, pc = blockIdx.x - h * NM;
        const uint32_t off = pc < ((NM - 1) >> GSH << GSH) ? pc & ((1 << GSH) - 1) : 0;
        l2_prefetch(p.qk + (size_t)(h * TPH + (pc - off) * MAINP + off * CFG_PF0) * (TR * D), CFG_PF0 * KBYTES, pol);
    }
    const int w = __shfl_sync(0xffffffffu, threadIdx.x >> 5, 0), lane = threadIdx.x & 31;
    if (w == NWARPS) return;
    const uint32_t sb = __shfl_sync(0xffffffffu, smem_u32(smem), 0);
    const uint32_t bar = sb + OFF_BAR;

    const int grp = w - (w > W_PROD);
    if (grp < 8 && w != W_PROD && elect_one()) {
        const uint32_t cnt = grp == 4 ? 8 : grp == 5 ? NKW + NVW : grp == 6 ? NVW : grp == 7 ? 2 : 1;
#pragma unroll
        for (int i = 0; i < 16; i++) mbar_init(bar + grp * 128 + i * 8, cnt);
        asm volatile("fence.mbarrier_init.release.cluster;" ::: "memory");
    }
    asm volatile("bar.sync 0, %0;" ::"n"(NWARPS * 32) : "memory");

    if ((unsigned)(w - W_V) < NVW) {
        const int v = w - W_V, g = lane >> 3, l = lane & 7;
        const bool up = lane & 16, up2 = lane & 8;
        const uint32_t oV = pin(sb + OFF_V + g * (2 * D * 4) + v * (NB * 128) + l * 16), oP = pin(S_PV + g * 8);
        const uint32_t col = pin(v * (NB * 32) + l * 4 + (up ? 2 : 0) + (up2 ? 1 : 0));
        __nv_bfloat16* const outp = pin(p.out + col);
        uint32_t* const mailp = pin(g_mail + col);
        float acc[4 * NB];
#pragma unroll
        for (int i = 0; i < 4 * NB; i++) acc[i] = 0.f;
        uint32_t vslot = 0, seg = 0, vph = 0;
        uint32_t s = sb + OFF_SEG, t0 = 0;
        mbar_wait(bar + B_PR, 0);
        uint2 bd = lds64(s + S_BD);
        uint2 pv = lds64(s + oP);
        bool ready = false;
        int4 x0[NB], x1[NB];
        auto load_tile = [&]() {
            const uint32_t t = oV + vslot * KBYTES;
            if (!ready) mbar_wait(bar + B_FV + vslot * 8, vph);
            TS_ONCE(1); TS(5);
#pragma unroll
            for (int j = 0; j < NO_COMPUTE(NB); j++) {
                x0[j] = lds128(t + j * 128);
                x1[j] = lds128(t + 768 + j * 128);
            }
            __syncwarp();
            if (lane == 0) mbar_arrive(bar + B_EV + vslot * 8);
            if (++vslot == NV) { vslot = 0; vph ^= 1; }
            ready = mbar_test(bar + B_FV + vslot * 8, vph);
        };
        auto fma_tile = [&]() {
            const float pv0 = __uint_as_float(pv.x), pv1 = __uint_as_float(pv.y);
#pragma unroll
            for (int j = 0; j < NO_COMPUTE(NB); j++) {
                acc[j * 4 + 0] = fmaf(pv1, CVT(x1[j].x), fmaf(pv0, CVT(x0[j].x), acc[j * 4 + 0]));
                acc[j * 4 + 1] = fmaf(pv1, CVT(x1[j].y), fmaf(pv0, CVT(x0[j].y), acc[j * 4 + 1]));
                acc[j * 4 + 2] = fmaf(pv1, CVT(x1[j].z), fmaf(pv0, CVT(x0[j].z), acc[j * 4 + 2]));
                acc[j * 4 + 3] = fmaf(pv1, CVT(x1[j].w), fmaf(pv0, CVT(x0[j].w), acc[j * 4 + 3]));
            }
        };
        for (uint32_t batch = 1; !(bd.y & F_END); batch++) {
            TS(3);
            const uint32_t n = bd.y & F_NT, sbar = bar + (seg % NSEG) * 8;
            const bool segend = bd.y & F_SEGEND;
            const uint32_t seg2 = seg + segend, t2 = segend ? 0 : t0 + n;
            const uint32_t s2 = sb + OFF_SEG + (seg2 % NSEG) * SEG_BYTES;
#pragma unroll
            for (int i = 0; i < 4 * NB; i++) acc[i] *= __uint_as_float(bd.x);
#pragma unroll 1
            for (uint32_t i = 1; i < n; i++) {
                load_tile();
                const uint2 pn = lds64(s + oP + (t0 + i) * (TR * 4));
                fma_tile();
                pv = pn;
            }
            load_tile();
            const bool early = mbar_test(sbar + B_FC, (seg / NSEG) & 1);
            const bool next = mbar_test(bar + B_PR + (batch % NBAT) * 8, (batch / NBAT) & 1);
            fma_tile();
            int4 cf;
            uint32_t gv[NB];
            uint2 bn, pn;
            if (early) {
                cf = lds128(s + S_CF);
#pragma unroll
                for (int j = 0; j < NB; j++) gv[j] = lds32(s + S_G + (col + j * 32) * 4);
            }
            if (bd.y & F_LAST) {
                float o[NB];
#pragma unroll
                for (int j = 0; j < NB; j++) {
                    const float u0 = (up ? acc[j * 4 + 2] : acc[j * 4 + 0]) + __shfl_xor_sync(0xffffffffu, up ? acc[j * 4 + 0] : acc[j * 4 + 2], 16);
                    const float u1 = (up ? acc[j * 4 + 3] : acc[j * 4 + 1]) + __shfl_xor_sync(0xffffffffu, up ? acc[j * 4 + 1] : acc[j * 4 + 3], 16);
                    o[j] = (up2 ? u1 : u0) + __shfl_xor_sync(0xffffffffu, up2 ? u0 : u1, 8);
                }
                if (!early) {
                    mbar_wait(sbar + B_FC, (seg / NSEG) & 1);
                    cf = lds128(s + S_CF);
#pragma unroll
                    for (int j = 0; j < NB; j++) gv[j] = lds32(s + S_G + (col + j * 32) * 4);
                }
#pragma unroll
                for (int j = 0; j < NB; j++) {
                    const float gj = (bd.y & (F_SEMI | F_FIN)) ? __uint_as_float(gv[j]) : 0.f;
                    o[j] = fmaf(o[j], __int_as_float(cf.x), fmaf(gj, __int_as_float(cf.y), __int_as_float(cf.z)));
                }
                if (bd.y & F_FIN) {
#pragma unroll
                    for (int j = 0; j < NB; j++) {
                        const __nv_bfloat16 r = __float2bfloat16_rn(o[j]);
                        asm volatile("st.global.b16 [%0], %1;" ::"l"(outp + (bd.y >> 12) + j * 32), "h"(*(const uint16_t*)&r) : "memory");
                    }
                } else {
#pragma unroll
                    for (int j = 0; j < NB; j++) mail_put(mailp + (bd.y >> 12) + j * 32, o[j], cf.w & 3);
                    if (col < REC - D) mail_put(mailp + (bd.y >> 12) + D, __int_as_float(cf.w), cf.w & 3);
                }
#pragma unroll
                for (int i = 0; i < 4 * NB; i++) acc[i] = 0.f;
            }
            if (next) {
                bn = lds64(s2 + S_BD + t2 * 8);
                pn = lds64(s2 + oP + t2 * (TR * 4));
            }
            if (segend) {
                if (!(bd.y & F_LAST)) mbar_wait(sbar + B_FC, (seg / NSEG) & 1);
                __syncwarp();
                if (lane == 0) mbar_arrive(sbar + B_SE);
            }
            TS(6);
            if (!next) {
                mbar_wait(bar + B_PR + (batch % NBAT) * 8, (batch / NBAT) & 1);
                bn = lds64(s2 + S_BD + t2 * 8);
                pn = lds64(s2 + oP + t2 * (TR * 4));
            }
            bd = bn; pv = pn; s = s2; t0 = t2; seg = seg2;
        }
    } else if (w == W_S) {
        float m = NEG, lsum = 0.f, corr = 0.f;
        uint32_t batch = 0;
        for (uint32_t seg = 0;; seg++) {
            const uint32_t s = sb + OFF_SEG + (seg % NSEG) * SEG_BYTES, sbar = bar + (seg % NSEG) * 8;
            const uint32_t sph = (seg / NSEG) & 1;
            mbar_wait(sbar + B_HDR, sph);
            const int4 desc = lds128(s + S_DESC);
            if (desc.y & F_END) {
                if (lane == 0) {
                    sts64(s + S_BD, 0.f, __uint_as_float(F_END));
                    mbar_arrive(bar + B_PR + (batch % NBAT) * 8);
                }
                break;
            }
            if (desc.y & F_FIRST) { m = NEG; lsum = 0.f; corr = 0.f; }
            const uint32_t index = (desc.y & F_FIN) ? desc.x * D : (desc.x * NM + desc.z) * REC;
            const int nt = desc.y & F_NT, bs = 1 << ((desc.y & F_FIN) ? CFG_BF : CFG_BM);
#pragma unroll 1
            for (int t0 = 0; t0 < nt; t0 += bs, batch++) {
                const int n = min(bs, nt - t0);
                const bool valid = lane < n * TR;
                const uint32_t tl = t0 + (valid ? lane >> 3 : 0), row = tl * TR + (lane & 7);
                const uint32_t sc = s + S_SC + (((tl << (desc.w & 255)) + (desc.w >> 8)) * TR + (lane & 7)) * 2;
                const float vs = bf_lo(lds16(sc + 2 * SCB)), vz = bf_lo(lds16(sc + 3 * SCB));
                mbar_wait(bar + B_LG + (batch % NBAT) * 8, (batch / NBAT) & 1);
                const int4 part = lds128(s + S_LG + row * 16);
                const float dot = (__int_as_float(part.x) + __int_as_float(part.y)) + (__int_as_float(part.z) + __int_as_float(part.w));
                const float sv = rbf(rbf(dot) * 0.07216878364870322f) * LOG2E;
                int key = __float_as_int(fmaxf(m, sv));
                key ^= (key >> 31) & 0x7fffffff;
                key = __reduce_max_sync(0xffffffffu, key);
                const float mn = __int_as_float(key ^ ((key >> 31) & 0x7fffffff));
                const float alpha = ex2(m - mn), pr = ex2(sv - mn), pv = pr * vs;
                m = mn;
                sts32(s + S_PV + row * 4, pv);
                if (lane == 0)
                    sts64(s + S_BD + t0 * 8, alpha,
                          __uint_as_float(n | (t0 + n < nt ? 0 : index << 12 | F_SEGEND | (desc.y & (F_LAST | F_SEMI | F_FIN)))));
                __syncwarp();
                if (lane == 0) mbar_arrive(bar + B_PR + (batch % NBAT) * 8);
                lsum = fmaf(lsum, alpha, valid ? pr : 0.f);
                corr = fmaf(corr, alpha, valid ? pv * vz : 0.f);
                TS(3);
            }
            float L = lsum, C = corr;
            if (desc.y & F_LAST) {
#pragma unroll
                for (int o = 16; o > 0; o >>= 1) {
                    L += __shfl_xor_sync(0xffffffffu, L, o);
                    C += __shfl_xor_sync(0xffffffffu, C, o);
                }
            }
            mbar_wait(sbar + B_GD, sph);
            if (desc.y & F_LAST) {
                const uint32_t tag = lds32(sb + OFF_TAG) | ((desc.y & F_SEMI) ? 2 : 0);
                const float gl = (desc.y & (F_SEMI | F_FIN)) ? __uint_as_float(lds32(s + S_G + D * 4)) : -3.4e38f;
                const float M = fmaxf(m, gl), e = ex2(m - M), a = ex2(gl - M);
                const float W = fmaf(L, e, a), inv = rcp(W);
                if (lane == 0)
                    sts128(s + S_CF, __float_as_uint(e * inv), __float_as_uint(a * inv), __float_as_uint(-C * e * inv),
                           (__float_as_uint(M + lg2(W)) & ~3u) | tag);
            }
            __syncwarp();
            if (lane == 0) mbar_arrive(sbar + B_FC);
            TS(4);
        }
    } else if ((unsigned)(w - W_G) < NGW) {
        if (w == W_G) {
            if (lane == 0) sts32(sb + OFF_TAG, __uint_as_float(~*(volatile unsigned int*)&g_epoch & 1));
        } else {
            mbar_wait(bar + B_GD, 0);
        }
        for (uint32_t seg = w - W_G;; seg += NGW) {
            const uint32_t s = sb + OFF_SEG + (seg % NSEG) * SEG_BYTES, sbar = bar + (seg % NSEG) * 8;
            mbar_wait(sbar + B_HDR, (seg / NSEG) & 1);
            const int4 desc = lds128(s + S_DESC);
            if (desc.y & F_END) break;
            TS(1);
            if (desc.y & (F_SEMI | F_FIN)) {
                const uint32_t tag = lds32(sb + OFF_TAG) | ((desc.y & F_FIN) ? 2 : 0);
                const int cnt = (desc.y & F_FIN) ? 1 : NM;
                const uint32_t* mail = g_mail + desc.x * (NM * REC);
                float M = NEG, W = 0.f, O[6] = {0.f, 0.f, 0.f, 0.f, 0.f, 0.f};
#pragma unroll 1
                for (int i0 = 0; i0 < cnt; i0 += 5, mail += 5 * REC) {
                    uint2 pk[15];
                    uint32_t ls[5], stale;
                    int it = 0;
                    do {
                        stale = 0;
#pragma unroll
                        for (int i = 0; i < 5; i++) {
                            ls[i] = 0xff7ffffcu | tag;
                            pk[3 * i] = pk[3 * i + 1] = pk[3 * i + 2] = make_uint2(tag, tag);
                            if (i0 + i < cnt) {
                                asm volatile("ld.relaxed.gpu.global.u32 %0, [%1];" : "=r"(ls[i]) : "l"(mail + i * REC + D) : "memory");
#pragma unroll
                                for (int k = 0; k < 3; k++)
                                    asm volatile("ld.relaxed.gpu.global.v2.u32 {%0,%1}, [%2];"
                                                 : "=r"(pk[3 * i + k].x), "=r"(pk[3 * i + k].y)
                                                 : "l"(mail + i * REC + k * 64 + lane * 2) : "memory");
                            }
                        }
#pragma unroll
                        for (int i = 0; i < 5; i++) stale |= ls[i] ^ tag;
#pragma unroll
                        for (int i = 0; i < 15; i++) stale |= (pk[i].x ^ tag) | (pk[i].y ^ tag);
                        if (++it > (1 << 22)) __trap();
                    } while (stale & 3);
                    float Mn = M;
#pragma unroll
                    for (int i = 0; i < 5; i++) Mn = fmaxf(Mn, __uint_as_float(ls[i]));
                    const float a = ex2(M - Mn);
                    M = Mn; W *= a;
#pragma unroll
                    for (int i = 0; i < 6; i++) O[i] *= a;
#pragma unroll
                    for (int i = 0; i < 5; i++) {
                        const float e = ex2(__uint_as_float(ls[i]) - M);
                        W += e;
#pragma unroll
                        for (int k = 0; k < 3; k++) {
                            O[2 * k] = fmaf(e, __uint_as_float(pk[3 * i + k].x), O[2 * k]);
                            O[2 * k + 1] = fmaf(e, __uint_as_float(pk[3 * i + k].y), O[2 * k + 1]);
                        }
                    }
                }
                const float inv = rcp(W);
#pragma unroll
                for (int k = 0; k < 3; k++) sts64(s + S_G + k * 256 + lane * 8, O[2 * k] * inv, O[2 * k + 1] * inv);
                if (lane == 0) sts32(s + S_G + D * 4, M + lg2(W));
            }
            __syncwarp();
            if (lane == 0) mbar_arrive(sbar + B_GD);
            TS(2);
        }
    } else if (w / NKW == 0) {
        const int g = lane >> 3, l = lane & 7, godd = g & 1, row = 2 * g + (w & 1);
        const uint32_t sgA = pin(godd ? 0x3f803f80u : 0xbf80bf80u), sgB = pin(godd ? 0xbf80bf80u : 0x3f803f80u);
        const uint32_t oKA = pin(sb + row * (D * 4) + l * 16 + godd * 384), oKB = pin(oKA - godd * 768 + 384);
        const uint32_t oCA = pin(sb + T_C + row * (D * 2) + l * 8 + godd * 192), oCB = pin(oCA - godd * 384 + 192);
        const uint32_t oL = pin(S_LG + row * 16 + (l >> 2) * 8 + (l & 1) * 4), oS = pin(S_SC + row * 2);
        const bool own = (l & 3) == g, hi = l & 4, keep = ((l ^ g) & 2) == 0;
        uint2 qr[3];
        uint32_t kslot = w >> 1, j = kslot, batch0 = 0, kph = 0;
        for (uint32_t seg = 0;; seg++) {
            const uint32_t s = sb + OFF_SEG + (seg % NSEG) * SEG_BYTES, sbar = bar + (seg % NSEG) * 8;
            mbar_wait(sbar + B_HDR, (seg / NSEG) & 1);
            const int4 desc = lds128(s + S_DESC);
            if (desc.y & F_END) break;
            const uint32_t nt = desc.y & F_NT, bsh = (desc.y & F_FIN) ? CFG_BF : CFG_BM;
            if (desc.y & F_FIRST) {
#pragma unroll
                for (int i = 0; i < 3; i++) {
                    const uint32_t oa = l * 8 + godd * 192 + i * 64, ob = oa + 192 - godd * 384;
                    const uint2 a = lds64(s + S_Q + oa), b = lds64(s + S_Q + ob);
                    const uint2 ca = lds64(sb + OFF_QT + oa), sa = lds64(sb + OFF_QT + QBYTES + oa);
                    qr[i].x = rope2(a.x, ca.x, b.x, sa.x, sgA);
                    qr[i].y = rope2(a.y, ca.y, b.y, sa.y, sgA);
                }
            }
            for (; j < nt; j += NKW / 2) {
                const uint32_t t = kslot * KSLOT;
                const uint32_t sc = s + oS + ((j << (desc.w & 255)) + (desc.w >> 8)) * (TR * 2);
                const uint32_t ks2 = lds16(sc) * 0x10001u, kz2 = lds16(sc + SCB) * 0x10001u;
                const uint32_t lgb = bar + B_LG + ((batch0 + (j >> bsh)) % NBAT) * 8;
                const uint32_t lgc = j == nt - 1 ? 4 - ((j << (2 - bsh)) & 3) : 4 >> bsh;
                mbar_wait(bar + B_FK + kslot * 8, kph);
                TS_ONCE(1); TS(3);
                float c[4] = {0.f, 0.f, 0.f, 0.f};
#pragma unroll
                for (int jj = 0; jj < NO_COMPUTE_K(3); jj++) {
                    const int4 xa = lds128(t + oKA + jj * 128), xb = lds128(t + oKB + jj * 128);
                    const uint2 ca = lds64(t + oCA + jj * 64), cb = lds64(t + oCB + jj * 64);
                    const uint2 sa = lds64(t + oCA + CBYTES + jj * 64), sbv = lds64(t + oCB + CBYTES + jj * 64);
                    const uint32_t a0 = bmul(bsub(i2bf2(xa.x, xa.y), kz2), ks2);
                    const uint32_t a1 = bmul(bsub(i2bf2(xa.z, xa.w), kz2), ks2);
                    const uint32_t b0 = bmul(bsub(i2bf2(xb.x, xb.y), kz2), ks2);
                    const uint32_t b1 = bmul(bsub(i2bf2(xb.z, xb.w), kz2), ks2);
                    mma_bf16(c, rope2(a0, ca.x, b0, sa.x, sgA), rope2(b0, cb.x, a0, sbv.x, sgB),
                             rope2(a1, ca.y, b1, sa.y, sgA), rope2(b1, cb.y, a1, sbv.y, sgB), qr[jj].x, qr[jj].y);
                }
                __syncwarp();
                if (lane == 0) mbar_arrive(bar + B_EK + kslot * 8);
                TS_ONCE(2);
                const float part = own ? (hi ? c[1] : c[0]) : (hi ? c[3] : c[2]);
                if (keep) sts32(s + oL + j * (TR * 16), part);
                __syncwarp();
                if (lane == 0) mbar_arrive(lgb, lgc);
                TS(4);
                kslot += NKW / 2;
                if (kslot >= NK) { kslot -= NK; kph ^= 1; }
            }
            j -= nt;
            batch0 += (nt + (1 << bsh) - 1) >> bsh;
            __syncwarp();
            if (lane == 0) mbar_arrive(sbar + B_SE);
        }
    } else {
        if (elect_one()) {
            uint64_t pol;
            asm volatile("createpolicy.fractional.L2::evict_first.b64 %0, 1.0;" : "=l"(pol));
            uint32_t kslot = 0, vslot = 0, seg = 0, kph = 1, vph = 1;
            uint32_t win = NV;
            int pend[LEAD];
#pragma unroll
            for (int i = 0; i < LEAD; i++) pend[i] = -1;
            auto push_v = [&](int tile) {
                if (pend[0] >= 0) {
                    const uint32_t b = bar + vslot * 8;
                    mbar_wait(b + B_EV, vph);
                    mbar_expect(b + B_FV, KBYTES);
                    bulk_stream(sb + OFF_V + vslot * KBYTES, p.qv + (size_t)pend[0] * (TR * D), KBYTES, b + B_FV, pol);
                    if (++vslot == NV) { vslot = 0; vph ^= 1; }
                }
#pragma unroll
                for (int i = 0; i + 1 < LEAD; i++) pend[i] = pend[i + 1];
                pend[LEAD - 1] = tile;
            };
            asm volatile("mbarrier.expect_tx.shared::cta.b64 [%0], %1;" ::"r"(bar + B_HDR), "r"(2 * QBYTES) : "memory");
            bulk_plain(sb + OFF_QT, p.qcos, QBYTES, bar + B_HDR);
            bulk_plain(sb + OFF_QT + QBYTES, p.qsin, QBYTES, bar + B_HDR);
            uint32_t c = blockIdx.x;
            TS(1);
            while (c < NCLAIM) {
                const Claim cl = decode_claim(c);
                uint32_t tile = cl.tile0 + cl.off;
                auto tiles = [&](int cnt) {
#pragma unroll 1
                    for (int j = 0; j < cnt; j++, tile += 1u << cl.sh) {
                        push_v(tile);
                        const uint32_t t = sb + kslot * KSLOT, b = bar + kslot * 8;
                        const uint32_t ro = (tile % TPH) * (TR * D);
                        mbar_wait(b + B_EK, kph);
                        mbar_expect(b + B_FK, KSLOT);
                        bulk_stream(t, p.qk + (size_t)tile * (TR * D), KBYTES, b + B_FK, pol);
                        bulk_plain(t + T_C, p.kcos + ro, CBYTES, b + B_FK);
                        bulk_plain(t + T_S, p.ksin + ro, CBYTES, b + B_FK);
                        TS_ONCE(2); TS(3);
                        if (++kslot == NK) { kslot = 0; kph ^= 1; }
                    }
                };
                int nt;
                for (int left = cl.ntiles;; left -= nt) {
                    nt = min(SEGT, left);
                    const bool first = left == cl.ntiles, last = left == nt;
                    const uint32_t s = sb + OFF_SEG + (seg % NSEG) * SEG_BYTES, b = bar + (seg % NSEG) * 8;
                    mbar_wait(b + B_SE, ((seg / NSEG) & 1) ^ 1);
                    sts128(s + S_DESC, cl.head,
                           nt | (first ? F_FIRST : 0) | (last ? F_LAST : 0) | (c >= C_F ? F_FIN : c >= C_S ? F_SEMI : 0),
                           cl.piece, cl.sh | cl.off << 8);
                    const uint32_t scb = nt * TR * 2 << cl.sh;
                    const uint32_t r = (tile - cl.off) * TR;
                    mbar_expect(b + B_HDR, 4 * scb + (first ? QBYTES : 0));
                    if (first) bulk_plain(s + S_Q, p.q + cl.head * D, QBYTES, b + B_HDR);
                    bulk_plain(s + S_SC, p.ks + r, scb, b + B_HDR);
                    bulk_plain(s + S_SC + SCB, p.kz + r, scb, b + B_HDR);
                    bulk_plain(s + S_SC + 2 * SCB, p.vs + r, scb, b + B_HDR);
                    bulk_plain(s + S_SC + 3 * SCB, p.vz + r, scb, b + B_HDR);
                    seg++;
                    tiles(last ? max(nt - LA, 0) : nt);
                    if (last) break;
                }
                if (c == blockIdx.x) mbar_wait(bar + B_GD, 0);
                const unsigned nx = atomicInc(&g_queue, NCLAIM - 1);
                tiles(min(nt, LA));
                if (nx == NCLAIM - 1) g_epoch = lds32(sb + OFF_TAG);
                c = gridDim.x + nx;
            }
            TS(4);
#pragma unroll 1
            for (int i = 0; i < LEAD; i++) push_v(-1);
            TS(5);
#pragma unroll 1
            for (int i = 0; i < NGW; i++, seg++) {
                const uint32_t s = sb + OFF_SEG + (seg % NSEG) * SEG_BYTES, b = bar + (seg % NSEG) * 8;
                mbar_wait(b + B_SE, ((seg / NSEG) & 1) ^ 1);
                sts128(s + S_DESC, 0, F_END, 0, 0);
                mbar_arrive(b + B_HDR);
            }
        }
    }
}

}

extern "C" void kernel_launch(void* const* d_in, const int* in_sizes, int n_in, void* d_out, int out_size) {
    (void)in_sizes; (void)n_in; (void)out_size;
    static int sms = 0;
    if (sms == 0) {
        int dev = 0;
        cudaGetDevice(&dev);
        cudaDeviceGetAttribute(&sms, cudaDevAttrMultiProcessorCount, dev);
        cudaFuncSetAttribute(kv_rope_decode_kernel, cudaFuncAttributeMaxDynamicSharedMemorySize, SMEM_BYTES);
    }
    Params p;
    p.q    = (const __nv_bfloat16*)d_in[0];
    p.qk   = (const int*)d_in[1];
    p.ks   = (const __nv_bfloat16*)d_in[2];
    p.kz   = (const __nv_bfloat16*)d_in[3];
    p.qv   = (const int*)d_in[4];
    p.vs   = (const __nv_bfloat16*)d_in[5];
    p.vz   = (const __nv_bfloat16*)d_in[6];
    p.qcos = (const __nv_bfloat16*)d_in[7];
    p.qsin = (const __nv_bfloat16*)d_in[8];
    p.kcos = (const __nv_bfloat16*)d_in[9];
    p.ksin = (const __nv_bfloat16*)d_in[10];
    p.out  = (__nv_bfloat16*)d_out;
    kv_rope_decode_kernel<<<sms, NTHREADS, SMEM_BYTES>>>(p);
}
```

```cpp
#include <cuda_runtime.h>
#include <cuda_bf16.h>
#include <stdint.h>

namespace {

constexpr int D      = 192;
constexpr int SKV    = 2048;
constexpr int NHEAD  = 256;
constexpr int TR     = 8;
constexpr int TPH    = SKV / TR;
constexpr int NKW    = 4;
constexpr int NVW    = 6;
constexpr int NB     = 6 / NVW;
constexpr int NGW    = 2;
constexpr int NK     = 8;
constexpr int NV     = 4;
constexpr int LEAD   = 5;
constexpr int NSEG   = 8;
constexpr int SEGT   = 16;
constexpr int NBAT   = 16;
constexpr int W_V = NKW, W_PROD = W_V + NVW, W_S = W_PROD + 1, W_G = W_S + 1, NWARPS = W_G + NGW;
constexpr int NTHREADS = NWARPS * 32 + 32;

constexpr int MAINP  = 16;
constexpr int PF0    = 3;
constexpr int GSH    = 2;
constexpr int LA     = 3;
__host__ __device__ constexpr int semi_size(int h) { return 16 - 2 * (h >> 6); }
__host__ __device__ constexpr int fin_size(int h) { return 8 - 2 * (h >> 6); }
constexpr int NM     = (TPH - semi_size(0) - fin_size(0) + MAINP - 1) / MAINP;
constexpr int C_S    = NHEAD * NM, C_F = C_S + NHEAD, NCLAIM = C_F + NHEAD;
constexpr bool sizes_ok(int h) { return h >= NHEAD || (semi_size(h) + fin_size(h) < TPH - (NM - 1) * MAINP && sizes_ok(h + 64)); }
static_assert(sizes_ok(0), "schedule");

constexpr int KBYTES = TR * D * 4;
constexpr int CBYTES = TR * D * 2;
constexpr int QBYTES = D * 2;
constexpr int T_C = KBYTES, T_S = T_C + CBYTES, KSLOT = T_S + CBYTES;
constexpr int SCB = SEGT * TR * 2 << GSH;
static_assert(GSH == 0 || MAINP == SEGT, "interleaved pieces are single segments");
constexpr int S_Q    = 0;
constexpr int S_SC   = S_Q + QBYTES;
constexpr int S_DESC = S_SC + 4 * SCB;
constexpr int S_BD   = S_DESC + 16;
constexpr int S_LG   = S_BD + SEGT * 8;
constexpr int S_PV   = S_LG + SEGT * TR * 16;
constexpr int S_G    = S_PV + SEGT * TR * 4;
constexpr int S_CF   = S_G + (D + 4) * 4;
constexpr int SEG_BYTES = (S_CF + 16 + 127) / 128 * 128;
constexpr int OFF_V = NK * KSLOT, OFF_SEG = OFF_V + NV * KBYTES, OFF_QT = OFF_SEG + NSEG * SEG_BYTES,
              OFF_TAG = OFF_QT + 2 * QBYTES, OFF_BAR = OFF_TAG + 16;
constexpr int B_FK = 0, B_PR = 128, B_HDR = 256, B_GD = 320, B_FC = 384, B_FV = 448, B_LG = 512,
              B_SE = 640, B_EV = 768, B_EK = 896;
constexpr int SMEM_BYTES = OFF_BAR + 1024;
static_assert(NK <= 16 && NV <= 8 && NSEG == 8 && NBAT == 16, "barrier layout");
static_assert(SMEM_BYTES <= 232448 && SMEM_BYTES > 232448 / 2, "one CTA per SM");
static_assert(NSEG % NGW == 0 && NK % (NKW / 2) == 0 && NB * NVW == 6 && LEAD >= 1, "cfg");
static_assert(LEAD + NV >= 4 && LEAD + NV < NBAT && LEAD < NSEG, "no ring can be lapped or starved");

__device__ unsigned int g_queue;
constexpr int REC = 200;
__device__ unsigned int g_epoch;
__device__ __align__(32) uint32_t g_mail[NHEAD * NM * REC];

__device__ __forceinline__ uint32_t smem_u32(const void* p) { return (uint32_t)__cvta_generic_to_shared(p); }
__device__ __forceinline__ uint32_t pin(uint32_t x) {
    return __shfl_sync(0xffffffffu, x, threadIdx.x & 31);
}
template <class T> __device__ __forceinline__ T* pin(T* p) {
    return (T*)__shfl_sync(0xffffffffu, (unsigned long long)p, threadIdx.x & 31);
}
__device__ __forceinline__ bool elect_one() {
    uint32_t pred;
    asm volatile("{\n.reg .pred p;\nelect.sync _|p, 0xffffffff;\nselp.u32 %0, 1, 0, p;\n}" : "=r"(pred));
    return pred;
}
__device__ __forceinline__ void mbar_init(uint32_t bar, uint32_t cnt) {
    asm volatile("mbarrier.init.shared::cta.b64 [%0], %1;" ::"r"(bar), "r"(cnt) : "memory");
}
__device__ __forceinline__ void mbar_expect(uint32_t bar, uint32_t bytes) {
    asm volatile("mbarrier.arrive.expect_tx.shared::cta.b64 _, [%0], %1;" ::"r"(bar), "r"(bytes) : "memory");
}
__device__ __forceinline__ void mbar_arrive(uint32_t bar) {
    asm volatile("mbarrier.arrive.shared::cta.b64 _, [%0];" ::"r"(bar) : "memory");
}
__device__ __forceinline__ void mbar_arrive(uint32_t bar, uint32_t cnt) {
    asm volatile("mbarrier.arrive.shared::cta.b64 _, [%0], %1;" ::"r"(bar), "r"(cnt) : "memory");
}
__device__ __forceinline__ bool mbar_test(uint32_t bar, uint32_t parity) {
    uint32_t ok;
    asm volatile("{\n.reg .pred p;\nmbarrier.test_wait.parity.shared::cta.b64 p, [%1], %2;\nselp.u32 %0, 1, 0, p;\n}"
                 : "=r"(ok) : "r"(bar), "r"(parity) : "memory");
    return ok;
}
__device__ __forceinline__ void mbar_wait(uint32_t bar, uint32_t parity) {
    asm volatile("{\n.reg .pred p;\n.reg .u32 n;\n"
                 "mbarrier.try_wait.parity.shared::cta.b64 p, [%0], %1;\n"
                 "@p bra DONE;\n"
                 "mov.u32 n, 0;\n"
                 "LOOP:\n"
                 "mbarrier.try_wait.parity.shared::cta.b64 p, [%0], %1;\n"
                 "@p bra DONE;\n"
                 "add.u32 n, n, 1;\n"
                 "setp.lt.u32 p, n, 0x400000;\n"
                 "@p bra LOOP;\n"
                 "trap;\n"
                 "DONE:\n}" ::"r"(bar), "r"(parity) : "memory");
}
__device__ __forceinline__ void bulk_stream(uint32_t dst, const void* src, uint32_t bytes, uint32_t bar, uint64_t pol) {
    asm volatile("cp.async.bulk.shared::cluster.global.mbarrier::complete_tx::bytes.L2::cache_hint [%0], [%1], %2, [%3], %4;"
                 ::"r"(dst), "l"(src), "r"(bytes), "r"(bar), "l"(pol) : "memory");
}
__device__ __forceinline__ void bulk_plain(uint32_t dst, const void* src, uint32_t bytes, uint32_t bar) {
    asm volatile("cp.async.bulk.shared::cluster.global.mbarrier::complete_tx::bytes [%0], [%1], %2, [%3];"
                 ::"r"(dst), "l"(src), "r"(bytes), "r"(bar) : "memory");
}
__device__ __forceinline__ void l2_prefetch(const void* src, uint32_t bytes, uint64_t pol) {
    asm volatile("cp.async.bulk.prefetch.L2.global.L2::cache_hint [%0], %1, %2;" ::"l"(src), "r"(bytes), "l"(pol) : "memory");
}
__device__ __forceinline__ void l2_prefetch(const void* src, uint32_t bytes) {
    asm volatile("cp.async.bulk.prefetch.L2.global [%0], %1;" ::"l"(src), "r"(bytes) : "memory");
}
__device__ __forceinline__ int4 lds128(uint32_t a) {
    int4 v;
    asm volatile("ld.shared.v4.s32 {%0,%1,%2,%3}, [%4];" : "=r"(v.x), "=r"(v.y), "=r"(v.z), "=r"(v.w) : "r"(a));
    return v;
}
__device__ __forceinline__ uint2 lds64(uint32_t a) {
    uint2 v;
    asm volatile("ld.shared.v2.u32 {%0,%1}, [%2];" : "=r"(v.x), "=r"(v.y) : "r"(a));
    return v;
}
__device__ __forceinline__ uint32_t lds32(uint32_t a) {
    uint32_t v;
    asm volatile("ld.shared.u32 %0, [%1];" : "=r"(v) : "r"(a));
    return v;
}
__device__ __forceinline__ uint32_t lds16(uint32_t a) {
    uint16_t v;
    asm volatile("ld.shared.u16 %0, [%1];" : "=h"(v) : "r"(a));
    return v;
}
__device__ __forceinline__ void sts32(uint32_t a, float x) {
    asm volatile("st.shared.f32 [%0], %1;" ::"r"(a), "f"(x) : "memory");
}
__device__ __forceinline__ void sts128(uint32_t a, uint32_t x, uint32_t y, uint32_t z, uint32_t w) {
    asm volatile("st.shared.v4.u32 [%0], {%1,%2,%3,%4};" ::"r"(a), "r"(x), "r"(y), "r"(z), "r"(w) : "memory");
}
__device__ __forceinline__ void sts64(uint32_t a, float x, float y) {
    asm volatile("st.shared.v2.f32 [%0], {%1,%2};" ::"r"(a), "f"(x), "f"(y) : "memory");
}
__device__ __forceinline__ float bf_lo(uint32_t v) { return __uint_as_float(v << 16); }
__device__ __forceinline__ float rbf(float x) {
    uint32_t d; asm("cvt.rn.bf16x2.f32 %0, %1, %2;" : "=r"(d) : "f"(x), "f"(0.f)); return __uint_as_float(d);
}
__device__ __forceinline__ float rcp(float x) {
    float y;
    asm("rcp.approx.ftz.f32 %0, %1;" : "=f"(y) : "f"(x));
    return y;
}
__device__ __forceinline__ float lg2(float x) {
    float y;
    asm("lg2.approx.ftz.f32 %0, %1;" : "=f"(y) : "f"(x));
    return y;
}
__device__ __forceinline__ float ex2(float x) {
    float y;
    asm("ex2.approx.ftz.f32 %0, %1;" : "=f"(y) : "f"(x));
    return y;
}
__device__ __forceinline__ uint32_t bmul(uint32_t a, uint32_t b) {
    uint32_t d; asm("mul.rn.bf16x2 %0, %1, %2;" : "=r"(d) : "r"(a), "r"(b)); return d;
}
__device__ __forceinline__ uint32_t bsub(uint32_t a, uint32_t b) {
    uint32_t d; asm("sub.rn.bf16x2 %0, %1, %2;" : "=r"(d) : "r"(a), "r"(b)); return d;
}
__device__ __forceinline__ uint32_t bfma(uint32_t a, uint32_t b, uint32_t c) {
    uint32_t d; asm("fma.rn.bf16x2 %0, %1, %2, %3;" : "=r"(d) : "r"(a), "r"(b), "r"(c)); return d;
}
__device__ __forceinline__ uint32_t i2bf2(int lo, int hi) {
    uint32_t d; asm("cvt.rn.bf16x2.f32 %0, %1, %2;" : "=r"(d) : "f"((float)hi), "f"((float)lo)); return d;
}
__device__ __forceinline__ uint32_t rope2(uint32_t x, uint32_t c, uint32_t y, uint32_t s, uint32_t sg) {
    return bfma(bmul(y, s), sg, bmul(x, c));
}
__device__ __forceinline__ void mma_bf16(float (&c)[4], uint32_t a0, uint32_t a1, uint32_t a2, uint32_t a3,
                                         uint32_t b0, uint32_t b1) {
    asm("mma.sync.aligned.m16n8k16.row.col.f32.bf16.bf16.f32 {%0,%1,%2,%3}, {%4,%5,%6,%7}, {%8,%9}, {%0,%1,%2,%3};"
        : "+f"(c[0]), "+f"(c[1]), "+f"(c[2]), "+f"(c[3])
        : "r"(a0), "r"(a1), "r"(a2), "r"(a3), "r"(b0), "r"(b1));
}
__device__ __forceinline__ void mail_put(uint32_t* p, float x, uint32_t tag) {
    asm volatile("st.relaxed.gpu.global.u32 [%0], %1;" ::"l"(p), "r"((__float_as_uint(x) & ~3u) | tag) : "memory");
}

struct Claim { uint32_t head, tile0, piece, sh, off; int ntiles; };

__device__ __forceinline__ Claim decode_claim(uint32_t c) {
    Claim cl;
    cl.sh = cl.off = 0;
    if (c < C_S) {
        cl.head = c / NM; cl.piece = c - cl.head * NM; cl.tile0 = cl.head * TPH + cl.piece * MAINP;
        cl.ntiles = cl.piece < NM - 1 ? MAINP : TPH - (NM - 1) * MAINP - semi_size(cl.head) - fin_size(cl.head);
        if (cl.piece < ((NM - 1) >> GSH << GSH)) {
            cl.sh = GSH; cl.off = cl.piece & ((1 << GSH) - 1); cl.tile0 -= cl.off * MAINP;
        }
    } else {
        cl.head = (c - C_S) % NHEAD; cl.piece = 0;
        cl.ntiles = fin_size(cl.head); cl.tile0 = (cl.head + 1) * TPH - cl.ntiles;
        if (c < C_F) { cl.ntiles = semi_size(cl.head); cl.tile0 -= cl.ntiles; }
    }
    return cl;
}

struct Params {
    const int* qk; const __nv_bfloat16* kcos; const __nv_bfloat16* ksin; const int* qv;
    const __nv_bfloat16* ks; const __nv_bfloat16* kz; const __nv_bfloat16* vs; const __nv_bfloat16* vz;
    const __nv_bfloat16* q; const __nv_bfloat16* qcos; const __nv_bfloat16* qsin;
    __nv_bfloat16* out;
};

constexpr float NEG = -3.0e38f;
constexpr float LOG2E = 1.4426950408889634f;
constexpr int F_NT = 31, F_FIRST = 32, F_LAST = 64, F_SEMI = 128, F_FIN = 256, F_SEGEND = 512, F_END = 1024;
static_assert(NHEAD * NM * REC < (1 << 20), "batch descriptor");

__global__ void __launch_bounds__(NTHREADS, 1)
kv_rope_decode_kernel(const Params p) {
    extern __shared__ __align__(128) unsigned char smem[];
    if (threadIdx.x >= NWARPS * 32 && elect_one()) {
        l2_prefetch(p.kcos + (blockIdx.x % (TPH / 2)) * (2 * TR * D), 2 * CBYTES);
        l2_prefetch(p.ksin + (blockIdx.x % (TPH / 2)) * (2 * TR * D), 2 * CBYTES);
        uint64_t pol;
        asm volatile("createpolicy.fractional.L2::evict_first.b64 %0, 1.0;" : "=l"(pol));
        const uint32_t h = blockIdx.x / NM, pc = blockIdx.x - h * NM;
        const uint32_t off = pc < ((NM - 1) >> GSH << GSH) ? pc & ((1 << GSH) - 1) : 0;
        l2_prefetch(p.qk + (size_t)(h * TPH + (pc - off) * MAINP + off * PF0) * (TR * D), PF0 * KBYTES, pol);
    }
    const int w = __shfl_sync(0xffffffffu, threadIdx.x >> 5, 0), lane = threadIdx.x & 31;
    if (w == NWARPS) return;
    const uint32_t sb = __shfl_sync(0xffffffffu, smem_u32(smem), 0);
    const uint32_t bar = sb + OFF_BAR;

    const int grp = w - (w > W_PROD);
    if (grp < 8 && w != W_PROD && elect_one()) {
        const uint32_t cnt = grp == 4 ? 8 : grp == 5 ? NKW + NVW : grp == 6 ? NVW : grp == 7 ? 2 : 1;
#pragma unroll
        for (int i = 0; i < 16; i++) mbar_init(bar + grp * 128 + i * 8, cnt);
        asm volatile("fence.mbarrier_init.release.cluster;" ::: "memory");
    }
    asm volatile("bar.sync 0, %0;" ::"n"(NWARPS * 32) : "memory");

    if ((unsigned)(w - W_V) < NVW) {
        const int v = w - W_V, g = lane >> 3, l = lane & 7;
        const bool up = lane & 16, up2 = lane & 8;
        const uint32_t oV = pin(sb + OFF_V + g * (2 * D * 4) + v * (NB * 128) + l * 16), oP = pin(S_PV + g * 8);
        const uint32_t col = pin(v * (NB * 32) + l * 4 + (up ? 2 : 0) + (up2 ? 1 : 0));
        __nv_bfloat16* const outp = pin(p.out + col);
        uint32_t* const mailp = pin(g_mail + col);
        float acc[4 * NB];
#pragma unroll
        for (int i = 0; i < 4 * NB; i++) acc[i] = 0.f;
        uint32_t vslot = 0, seg = 0, vph = 0;
        uint32_t s = sb + OFF_SEG, t0 = 0;
        mbar_wait(bar + B_PR, 0);
        uint2 bd = lds64(s + S_BD);
        uint2 pv = lds64(s + oP);
        bool ready = false;
        int4 x0[NB], x1[NB];
        auto load_tile = [&]() {
            const uint32_t t = oV + vslot * KBYTES;
            if (!ready) mbar_wait(bar + B_FV + vslot * 8, vph);
#pragma unroll
            for (int j = 0; j < NB; j++) {
                x0[j] = lds128(t + j * 128);
                x1[j] = lds128(t + 768 + j * 128);
            }
            __syncwarp();
            if (lane == 0) mbar_arrive(bar + B_EV + vslot * 8);
            if (++vslot == NV) { vslot = 0; vph ^= 1; }
            ready = mbar_test(bar + B_FV + vslot * 8, vph);
        };
        auto fma_tile = [&]() {
            const float pv0 = __uint_as_float(pv.x), pv1 = __uint_as_float(pv.y);
#pragma unroll
            for (int j = 0; j < NB; j++) {
                acc[j * 4 + 0] = fmaf(pv1, (float)x1[j].x, fmaf(pv0, (float)x0[j].x, acc[j * 4 + 0]));
                acc[j * 4 + 1] = fmaf(pv1, (float)x1[j].y, fmaf(pv0, (float)x0[j].y, acc[j * 4 + 1]));
                acc[j * 4 + 2] = fmaf(pv1, (float)x1[j].z, fmaf(pv0, (float)x0[j].z, acc[j * 4 + 2]));
                acc[j * 4 + 3] = fmaf(pv1, (float)x1[j].w, fmaf(pv0, (float)x0[j].w, acc[j * 4 + 3]));
            }
        };
        for (uint32_t batch = 1; !(bd.y & F_END); batch++) {
            const uint32_t n = bd.y & F_NT, sbar = bar + (seg % NSEG) * 8;
            const bool segend = bd.y & F_SEGEND;
            const uint32_t seg2 = seg + segend, t2 = segend ? 0 : t0 + n;
            const uint32_t s2 = sb + OFF_SEG + (seg2 % NSEG) * SEG_BYTES;
#pragma unroll
            for (int i = 0; i < 4 * NB; i++) acc[i] *= __uint_as_float(bd.x);
#pragma unroll 1
            for (uint32_t i = 1; i < n; i++) {
                load_tile();
                const uint2 pn = lds64(s + oP + (t0 + i) * (TR * 4));
                fma_tile();
                pv = pn;
            }
            load_tile();
            const bool early = mbar_test(sbar + B_FC, (seg / NSEG) & 1);
            const bool next = mbar_test(bar + B_PR + (batch % NBAT) * 8, (batch / NBAT) & 1);
            fma_tile();
            int4 cf;
            uint32_t gv[NB];
            uint2 bn, pn;
            if (early) {
                cf = lds128(s + S_CF);
#pragma unroll
                for (int j = 0; j < NB; j++) gv[j] = lds32(s + S_G + (col + j * 32) * 4);
            }
            if (bd.y & F_LAST) {
                float o[NB];
#pragma unroll
                for (int j = 0; j < NB; j++) {
                    const float u0 = (up ? acc[j * 4 + 2] : acc[j * 4 + 0]) + __shfl_xor_sync(0xffffffffu, up ? acc[j * 4 + 0] : acc[j * 4 + 2], 16);
                    const float u1 = (up ? acc[j * 4 + 3] : acc[j * 4 + 1]) + __shfl_xor_sync(0xffffffffu, up ? acc[j * 4 + 1] : acc[j * 4 + 3], 16);
                    o[j] = (up2 ? u1 : u0) + __shfl_xor_sync(0xffffffffu, up2 ? u0 : u1, 8);
                }
                if (!early) {
                    mbar_wait(sbar + B_FC, (seg / NSEG) & 1);
                    cf = lds128(s + S_CF);
#pragma unroll
                    for (int j = 0; j < NB; j++) gv[j] = lds32(s + S_G + (col + j * 32) * 4);
                }
#pragma unroll
                for (int j = 0; j < NB; j++) {
                    const float gj = (bd.y & (F_SEMI | F_FIN)) ? __uint_as_float(gv[j]) : 0.f;
                    o[j] = fmaf(o[j], __int_as_float(cf.x), fmaf(gj, __int_as_float(cf.y), __int_as_float(cf.z)));
                }
                if (bd.y & F_FIN) {
#pragma unroll
                    for (int j = 0; j < NB; j++) {
                        const __nv_bfloat16 r = __float2bfloat16_rn(o[j]);
                        asm volatile("st.global.b16 [%0], %1;" ::"l"(outp + (bd.y >> 12) + j * 32), "h"(*(const uint16_t*)&r) : "memory");
                    }
                } else {
#pragma unroll
                    for (int j = 0; j < NB; j++) mail_put(mailp + (bd.y >> 12) + j * 32, o[j], cf.w & 3);
                    if (col < REC - D) mail_put(mailp + (bd.y >> 12) + D, __int_as_float(cf.w), cf.w & 3);
                }
#pragma unroll
                for (int i = 0; i < 4 * NB; i++) acc[i] = 0.f;
            }
            if (next) {
                bn = lds64(s2 + S_BD + t2 * 8);
                pn = lds64(s2 + oP + t2 * (TR * 4));
            }
            if (segend) {
                if (!(bd.y & F_LAST)) mbar_wait(sbar + B_FC, (seg / NSEG) & 1);
                __syncwarp();
                if (lane == 0) mbar_arrive(sbar + B_SE);
            }
            if (!next) {
                mbar_wait(bar + B_PR + (batch % NBAT) * 8, (batch / NBAT) & 1);
                bn = lds64(s2 + S_BD + t2 * 8);
                pn = lds64(s2 + oP + t2 * (TR * 4));
            }
            bd = bn; pv = pn; s = s2; t0 = t2; seg = seg2;
        }
    } else if (w == W_S) {
        float m = NEG, lsum = 0.f, corr = 0.f;
        uint32_t batch = 0;
        for (uint32_t seg = 0;; seg++) {
            const uint32_t s = sb + OFF_SEG + (seg % NSEG) * SEG_BYTES, sbar = bar + (seg % NSEG) * 8;
            const uint32_t sph = (seg / NSEG) & 1;
            mbar_wait(sbar + B_HDR, sph);
            const int4 desc = lds128(s + S_DESC);
            if (desc.y & F_END) {
                if (lane == 0) {
                    sts64(s + S_BD, 0.f, __uint_as_float(F_END));
                    mbar_arrive(bar + B_PR + (batch % NBAT) * 8);
                }
                break;
            }
            if (desc.y & F_FIRST) { m = NEG; lsum = 0.f; corr = 0.f; }
            const uint32_t index = (desc.y & F_FIN) ? desc.x * D : (desc.x * NM + desc.z) * REC;
            const int nt = desc.y & F_NT;
#pragma unroll 1
            for (int t0 = 0; t0 < nt; t0 += 4, batch++) {
                const int n = min(4, nt - t0);
                const bool valid = lane < n * TR;
                const uint32_t tl = t0 + (valid ? lane >> 3 : 0), row = tl * TR + (lane & 7);
                const uint32_t sc = s + S_SC + (((tl << (desc.w & 255)) + (desc.w >> 8)) * TR + (lane & 7)) * 2;
                const float vs = bf_lo(lds16(sc + 2 * SCB)), vz = bf_lo(lds16(sc + 3 * SCB));
                mbar_wait(bar + B_LG + (batch % NBAT) * 8, (batch / NBAT) & 1);
                const int4 part = lds128(s + S_LG + row * 16);
                const float dot = (__int_as_float(part.x) + __int_as_float(part.y)) + (__int_as_float(part.z) + __int_as_float(part.w));
                const float sv = rbf(rbf(dot) * 0.07216878364870322f) * LOG2E;
                int key = __float_as_int(fmaxf(m, sv));
                key ^= (key >> 31) & 0x7fffffff;
                key = __reduce_max_sync(0xffffffffu, key);
                const float mn = __int_as_float(key ^ ((key >> 31) & 0x7fffffff));
                const float alpha = ex2(m - mn), pr = ex2(sv - mn), pv = pr * vs;
                m = mn;
                sts32(s + S_PV + row * 4, pv);
                if (lane == 0)
                    sts64(s + S_BD + t0 * 8, alpha,
                          __uint_as_float(n | (t0 + n < nt ? 0 : index << 12 | F_SEGEND | (desc.y & (F_LAST | F_SEMI | F_FIN)))));
                __syncwarp();
                if (lane == 0) mbar_arrive(bar + B_PR + (batch % NBAT) * 8);
                lsum = fmaf(lsum, alpha, valid ? pr : 0.f);
                corr = fmaf(corr, alpha, valid ? pv * vz : 0.f);
            }
            float L = lsum, C = corr;
            if (desc.y & F_LAST) {
#pragma unroll
                for (int o = 16; o > 0; o >>= 1) {
                    L += __shfl_xor_sync(0xffffffffu, L, o);
                    C += __shfl_xor_sync(0xffffffffu, C, o);
                }
            }
            mbar_wait(sbar + B_GD, sph);
            if (desc.y & F_LAST) {
                const uint32_t tag = lds32(sb + OFF_TAG) | ((desc.y & F_SEMI) ? 2 : 0);
                const float gl = (desc.y & (F_SEMI | F_FIN)) ? __uint_as_float(lds32(s + S_G + D * 4)) : -3.4e38f;
                const float M = fmaxf(m, gl), e = ex2(m - M), a = ex2(gl - M);
                const float W = fmaf(L, e, a), inv = rcp(W);
                if (lane == 0)
                    sts128(s + S_CF, __float_as_uint(e * inv), __float_as_uint(a * inv), __float_as_uint(-C * e * inv),
                           (__float_as_uint(M + lg2(W)) & ~3u) | tag);
            }
            __syncwarp();
            if (lane == 0) mbar_arrive(sbar + B_FC);
        }
    } else if ((unsigned)(w - W_G) < NGW) {
        if (w == W_G) {
            if (lane == 0) sts32(sb + OFF_TAG, __uint_as_float(~*(volatile unsigned int*)&g_epoch & 1));
        } else {
            mbar_wait(bar + B_GD, 0);
        }
        for (uint32_t seg = w - W_G;; seg += NGW) {
            const uint32_t s = sb + OFF_SEG + (seg % NSEG) * SEG_BYTES, sbar = bar + (seg % NSEG) * 8;
            mbar_wait(sbar + B_HDR, (seg / NSEG) & 1);
            const int4 desc = lds128(s + S_DESC);
            if (desc.y & F_END) break;
            if (desc.y & (F_SEMI | F_FIN)) {
                const uint32_t tag = lds32(sb + OFF_TAG) | ((desc.y & F_FIN) ? 2 : 0);
                const int cnt = (desc.y & F_FIN) ? 1 : NM;
                const uint32_t* mail = g_mail + desc.x * (NM * REC);
                float M = NEG, W = 0.f, O[6] = {0.f, 0.f, 0.f, 0.f, 0.f, 0.f};
#pragma unroll 1
                for (int i0 = 0; i0 < cnt; i0 += 5, mail += 5 * REC) {
                    uint2 pk[15];
                    uint32_t ls[5], stale;
                    int it = 0;
                    do {
                        stale = 0;
#pragma unroll
                        for (int i = 0; i < 5; i++) {
                            ls[i] = 0xff7ffffcu | tag;
                            pk[3 * i] = pk[3 * i + 1] = pk[3 * i + 2] = make_uint2(tag, tag);
                            if (i0 + i < cnt) {
                                asm volatile("ld.relaxed.gpu.global.u32 %0, [%1];" : "=r"(ls[i]) : "l"(mail + i * REC + D) : "memory");
#pragma unroll
                                for (int k = 0; k < 3; k++)
                                    asm volatile("ld.relaxed.gpu.global.v2.u32 {%0,%1}, [%2];"
                                                 : "=r"(pk[3 * i + k].x), "=r"(pk[3 * i + k].y)
                                                 : "l"(mail + i * REC + k * 64 + lane * 2) : "memory");
                            }
                        }
#pragma unroll
                        for (int i = 0; i < 5; i++) stale |= ls[i] ^= tag;
#pragma unroll
                        for (int i = 0; i < 15; i++) stale |= (pk[i].x ^= tag) | (pk[i].y ^= tag);
                        if (++it > (1 << 22)) __trap();
                    } while (stale & 3);
                    float Mn = M;
#pragma unroll
                    for (int i = 0; i < 5; i++) Mn = fmaxf(Mn, __uint_as_float(ls[i]));
                    const float a = ex2(M - Mn);
                    M = Mn; W *= a;
#pragma unroll
                    for (int i = 0; i < 6; i++) O[i] *= a;
#pragma unroll
                    for (int i = 0; i < 5; i++) {
                        const float e = ex2(__uint_as_float(ls[i]) - M);
                        W += e;
#pragma unroll
                        for (int k = 0; k < 3; k++) {
                            O[2 * k] = fmaf(e, __uint_as_float(pk[3 * i + k].x), O[2 * k]);
                            O[2 * k + 1] = fmaf(e, __uint_as_float(pk[3 * i + k].y), O[2 * k + 1]);
                        }
                    }
                }
                const float inv = rcp(W);
#pragma unroll
                for (int k = 0; k < 3; k++) sts64(s + S_G + k * 256 + lane * 8, O[2 * k] * inv, O[2 * k + 1] * inv);
                if (lane == 0) sts32(s + S_G + D * 4, M + lg2(W));
            }
            __syncwarp();
            if (lane == 0) mbar_arrive(sbar + B_GD);
        }
    } else if (w / NKW == 0) {
        const int g = lane >> 3, l = lane & 7, godd = g & 1, row = 2 * g + (w & 1);
        const uint32_t sgA = pin(godd ? 0x3f803f80u : 0xbf80bf80u), sgB = pin(godd ? 0xbf80bf80u : 0x3f803f80u);
        const uint32_t oKA = pin(sb + row * (D * 4) + l * 16 + godd * 384), oKB = pin(oKA - godd * 768 + 384);
        const uint32_t oCA = pin(sb + T_C + row * (D * 2) + l * 8 + godd * 192), oCB = pin(oCA - godd * 384 + 192);
        const uint32_t oL = pin(S_LG + row * 16 + (l >> 2) * 8 + (l & 1) * 4), oS = pin(S_SC + row * 2);
        const bool own = (l & 3) == g, hi = l & 4, keep = ((l ^ g) & 2) == 0;
        uint2 qr[3];
        uint32_t kslot = w >> 1, j = kslot, batch0 = 0, kph = 0;
        for (uint32_t seg = 0;; seg++) {
            const uint32_t s = sb + OFF_SEG + (seg % NSEG) * SEG_BYTES, sbar = bar + (seg % NSEG) * 8;
            mbar_wait(sbar + B_HDR, (seg / NSEG) & 1);
            const int4 desc = lds128(s + S_DESC);
            if (desc.y & F_END) break;
            const uint32_t nt = desc.y & F_NT;
            if (desc.y & F_FIRST) {
#pragma unroll
                for (int i = 0; i < 3; i++) {
                    const uint32_t oa = l * 8 + godd * 192 + i * 64, ob = oa + 192 - godd * 384;
                    const uint2 a = lds64(s + S_Q + oa), b = lds64(s + S_Q + ob);
                    const uint2 ca = lds64(sb + OFF_QT + oa), sa = lds64(sb + OFF_QT + QBYTES + oa);
                    qr[i].x = rope2(a.x, ca.x, b.x, sa.x, sgA);
                    qr[i].y = rope2(a.y, ca.y, b.y, sa.y, sgA);
                }
            }
            for (; j < nt; j += NKW / 2) {
                const uint32_t t = kslot * KSLOT;
                const uint32_t sc = s + oS + ((j << (desc.w & 255)) + (desc.w >> 8)) * (TR * 2);
                const uint32_t ks2 = lds16(sc) * 0x10001u, kz2 = lds16(sc + SCB) * 0x10001u;
                const uint32_t lgb = bar + B_LG + ((batch0 + (j >> 2)) % NBAT) * 8;
                const uint32_t lgc = j == nt - 1 ? 4 - (j & 3) : 1;
                mbar_wait(bar + B_FK + kslot * 8, kph);
                float c[4] = {0.f, 0.f, 0.f, 0.f};
#pragma unroll
                for (int jj = 0; jj < 3; jj++) {
                    const int4 xa = lds128(t + oKA + jj * 128), xb = lds128(t + oKB + jj * 128);
                    const uint2 ca = lds64(t + oCA + jj * 64), cb = lds64(t + oCB + jj * 64);
                    const uint2 sa = lds64(t + oCA + CBYTES + jj * 64), sbv = lds64(t + oCB + CBYTES + jj * 64);
                    const uint32_t a0 = bmul(bsub(i2bf2(xa.x, xa.y), kz2), ks2);
                    const uint32_t a1 = bmul(bsub(i2bf2(xa.z, xa.w), kz2), ks2);
                    const uint32_t b0 = bmul(bsub(i2bf2(xb.x, xb.y), kz2), ks2);
                    const uint32_t b1 = bmul(bsub(i2bf2(xb.z, xb.w), kz2), ks2);
                    mma_bf16(c, rope2(a0, ca.x, b0, sa.x, sgA), rope2(b0, cb.x, a0, sbv.x, sgB),
                             rope2(a1, ca.y, b1, sa.y, sgA), rope2(b1, cb.y, a1, sbv.y, sgB), qr[jj].x, qr[jj].y);
                }
                __syncwarp();
                if (lane == 0) mbar_arrive(bar + B_EK + kslot * 8);
                const float part = own ? (hi ? c[1] : c[0]) : (hi ? c[3] : c[2]);
                if (keep) sts32(s + oL + j * (TR * 16), part);
                __syncwarp();
                if (lane == 0) mbar_arrive(lgb, lgc);
                kslot += NKW / 2;
                if (kslot >= NK) { kslot -= NK; kph ^= 1; }
            }
            j -= nt;
            batch0 += (nt + 3) >> 2;
            __syncwarp();
            if (lane == 0) mbar_arrive(sbar + B_SE);
        }
    } else {
        if (elect_one()) {
            uint64_t pol;
            asm volatile("createpolicy.fractional.L2::evict_first.b64 %0, 1.0;" : "=l"(pol));
            uint32_t kslot = 0, vslot = 0, seg = 0, kph = 1, vph = 1;
            int pend[LEAD];
#pragma unroll
            for (int i = 0; i < LEAD; i++) pend[i] = -1;
            auto push_v = [&](int tile) {
                if (pend[0] >= 0) {
                    const uint32_t b = bar + vslot * 8;
                    mbar_wait(b + B_EV, vph);
                    mbar_expect(b + B_FV, KBYTES);
                    bulk_stream(sb + OFF_V + vslot * KBYTES, p.qv + (size_t)pend[0] * (TR * D), KBYTES, b + B_FV, pol);
                    if (++vslot == NV) { vslot = 0; vph ^= 1; }
                }
#pragma unroll
                for (int i = 0; i + 1 < LEAD; i++) pend[i] = pend[i + 1];
                pend[LEAD - 1] = tile;
            };
            asm volatile("mbarrier.expect_tx.shared::cta.b64 [%0], %1;" ::"r"(bar + B_HDR), "r"(2 * QBYTES) : "memory");
            bulk_plain(sb + OFF_QT, p.qcos, QBYTES, bar + B_HDR);
            bulk_plain(sb + OFF_QT + QBYTES, p.qsin, QBYTES, bar + B_HDR);
            uint32_t c = blockIdx.x;
            while (c < NCLAIM) {
                const Claim cl = decode_claim(c);
                uint32_t tile = cl.tile0 + cl.off;
                auto tiles = [&](int cnt) {
#pragma unroll 1
                    for (int j = 0; j < cnt; j++, tile += 1u << cl.sh) {
                        push_v(tile);
                        const uint32_t t = sb + kslot * KSLOT, b = bar + kslot * 8;
                        const uint32_t ro = (tile % TPH) * (TR * D);
                        mbar_wait(b + B_EK, kph);
                        mbar_expect(b + B_FK, KSLOT);
                        bulk_stream(t, p.qk + (size_t)tile * (TR * D), KBYTES, b + B_FK, pol);
                        bulk_plain(t + T_C, p.kcos + ro, CBYTES, b + B_FK);
                        bulk_plain(t + T_S, p.ksin + ro, CBYTES, b + B_FK);
                        if (++kslot == NK) { kslot = 0; kph ^= 1; }
                    }
                };
                int nt;
                for (int left = cl.ntiles;; left -= nt) {
                    nt = min(SEGT, left);
                    const bool first = left == cl.ntiles, last = left == nt;
                    const uint32_t s = sb + OFF_SEG + (seg % NSEG) * SEG_BYTES, b = bar + (seg % NSEG) * 8;
                    mbar_wait(b + B_SE, ((seg / NSEG) & 1) ^ 1);
                    sts128(s + S_DESC, cl.head,
                           nt | (first ? F_FIRST : 0) | (last ? F_LAST : 0) | (c >= C_F ? F_FIN : c >= C_S ? F_SEMI : 0),
                           cl.piece, cl.sh | cl.off << 8);
                    const uint32_t scb = nt * TR * 2 << cl.sh;
                    const uint32_t r = (tile - cl.off) * TR;
                    mbar_expect(b + B_HDR, 4 * scb + (first ? QBYTES : 0));
                    if (first) bulk_plain(s + S_Q, p.q + cl.head * D, QBYTES, b + B_HDR);
                    bulk_plain(s + S_SC, p.ks + r, scb, b + B_HDR);
                    bulk_plain(s + S_SC + SCB, p.kz + r, scb, b + B_HDR);
                    bulk_plain(s + S_SC + 2 * SCB, p.vs + r, scb, b + B_HDR);
                    bulk_plain(s + S_SC + 3 * SCB, p.vz + r, scb, b + B_HDR);
                    seg++;
                    tiles(last ? max(nt - LA, 0) : nt);
                    if (last) break;
                }
                if (c == blockIdx.x) mbar_wait(bar + B_GD, 0);
                const unsigned nx = atomicInc(&g_queue, NCLAIM - 1);
                tiles(min(nt, LA));
                if (nx == NCLAIM - 1) g_epoch = lds32(sb + OFF_TAG);
                c = gridDim.x + nx;
            }
#pragma unroll 1
            for (int i = 0; i < LEAD; i++) push_v(-1);
#pragma unroll 1
            for (int i = 0; i < NGW; i++, seg++) {
                const uint32_t s = sb + OFF_SEG + (seg % NSEG) * SEG_BYTES, b = bar + (seg % NSEG) * 8;
                mbar_wait(b + B_SE, ((seg / NSEG) & 1) ^ 1);
                sts128(s + S_DESC, 0, F_END, 0, 0);
                mbar_arrive(b + B_HDR);
            }
        }
    }
}

}

extern "C" void kernel_launch(void* const* d_in, const int* in_sizes, int n_in, void* d_out, int out_size) {
    (void)in_sizes; (void)n_in; (void)out_size;
    static int sms = 0;
    if (sms == 0) {
        int dev = 0;
        cudaGetDevice(&dev);
        cudaDeviceGetAttribute(&sms, cudaDevAttrMultiProcessorCount, dev);
        cudaFuncSetAttribute(kv_rope_decode_kernel, cudaFuncAttributeMaxDynamicSharedMemorySize, SMEM_BYTES);
    }
    Params p;
    p.q    = (const __nv_bfloat16*)d_in[0];
    p.qk   = (const int*)d_in[1];
    p.ks   = (const __nv_bfloat16*)d_in[2];
    p.kz   = (const __nv_bfloat16*)d_in[3];
    p.qv   = (const int*)d_in[4];
    p.vs   = (const __nv_bfloat16*)d_in[5];
    p.vz   = (const __nv_bfloat16*)d_in[6];
    p.qcos = (const __nv_bfloat16*)d_in[7];
    p.qsin = (const __nv_bfloat16*)d_in[8];
    p.kcos = (const __nv_bfloat16*)d_in[9];
    p.ksin = (const __nv_bfloat16*)d_in[10];
    p.out  = (__nv_bfloat16*)d_out;
    kv_rope_decode_kernel<<<sms, NTHREADS, SMEM_BYTES>>>(p);
}
```

```cpp
#include <cuda_runtime.h>
#include <cuda_bf16.h>
#include <stdint.h>

namespace {

constexpr int D      = 192;
constexpr int SKV    = 2048;
constexpr int NHEAD  = 256;
constexpr int TR     = 8;
constexpr int TPH    = SKV / TR;
constexpr int NKW    = 4;
constexpr int NVW    = 6;
constexpr int NB     = 6 / NVW;
constexpr int NGW    = 2;
constexpr int NK     = 8;
constexpr int NV     = 4;
constexpr int LEAD   = 5;
constexpr int NSEG   = 8;
constexpr int SEGT   = 16;
constexpr int NBAT   = 16;
constexpr int W_V = NKW, W_PROD = W_V + NVW, W_S = W_PROD + 1, W_G = W_S + 1, W_SCH = W_G + NGW, NWARPS = W_SCH + 1;
constexpr int NTHREADS = NWARPS * 32 + 32;

constexpr int MAINP  = 16;
constexpr int PF0    = 3;
constexpr int GSH    = 2;
constexpr int LA     = 3;
__host__ __device__ constexpr int semi_size(int h) { return 14 - 2 * (h >> 6); }
__host__ __device__ constexpr int fin_size(int h) { return h < 64 ? 10 : 16 >> (h >> 6); }
constexpr int NM     = (TPH - semi_size(0) - fin_size(0) + MAINP - 1) / MAINP;
constexpr int C_S    = NHEAD * NM, C_F = C_S + NHEAD, NCLAIM = C_F + NHEAD;
constexpr bool sizes_ok(int h) { return h >= NHEAD || (semi_size(h) + fin_size(h) < TPH - (NM - 1) * MAINP && sizes_ok(h + 64)); }
static_assert(sizes_ok(0), "schedule");

constexpr int KBYTES = TR * D * 4;
constexpr int CBYTES = TR * D * 2;
constexpr int QBYTES = D * 2;
constexpr int T_C = KBYTES, T_S = T_C + CBYTES, KSLOT = T_S + CBYTES;
constexpr int SCB = SEGT * TR * 2 << GSH;
static_assert(GSH == 0 || MAINP == SEGT, "interleaved pieces are single segments");
constexpr int S_Q    = 0;
constexpr int S_SC   = S_Q + QBYTES;
constexpr int S_DESC = S_SC + 4 * SCB;
constexpr int S_BD   = S_DESC + 16;
constexpr int S_LG   = S_BD + SEGT * 8;
constexpr int S_PV   = S_LG + SEGT * TR * 16;
constexpr int S_G    = S_PV + SEGT * TR * 4;
constexpr int S_CF   = S_G + (D + 4) * 4;
constexpr int SEG_BYTES = (S_CF + 16 + 127) / 128 * 128;
constexpr int OFF_V = NK * KSLOT, OFF_SEG = OFF_V + NV * KBYTES, OFF_QT = OFF_SEG + NSEG * SEG_BYTES,
              OFF_TAG = OFF_QT + 2 * QBYTES, OFF_BAR = OFF_TAG + 16;
constexpr int B_FK = 0, B_DS = 64, B_PR = 128, B_HDR = 256, B_GD = 320, B_FC = 384, B_FV = 448, B_GO = 504,
              B_LG = 512, B_SE = 640, B_EV = 768, B_EK = 896;
constexpr int SMEM_BYTES = OFF_BAR + 1024;
static_assert(NK <= 8 && NV <= 7 && W_PROD >= 8 && NSEG == 8 && NBAT == 16, "barrier layout");
static_assert(SMEM_BYTES <= 232448 && SMEM_BYTES > 232448 / 2, "one CTA per SM");
static_assert(NSEG % NGW == 0 && NK % (NKW / 2) == 0 && NB * NVW == 6 && LEAD >= 1, "cfg");
static_assert(LEAD + NV >= 4 && LEAD + NV < NBAT && LEAD < NSEG, "no ring can be lapped or starved");

__device__ unsigned int g_queue;
constexpr int REC = 200;
__device__ unsigned int g_epoch;
__device__ __align__(32) uint32_t g_mail[NHEAD * NM * REC];

__device__ __forceinline__ uint32_t smem_u32(const void* p) { return (uint32_t)__cvta_generic_to_shared(p); }
__device__ __forceinline__ uint32_t pin(uint32_t x) {
    return __shfl_sync(0xffffffffu, x, threadIdx.x & 31);
}
template <class T> __device__ __forceinline__ T* pin(T* p) {
    return (T*)__shfl_sync(0xffffffffu, (unsigned long long)p, threadIdx.x & 31);
}
__device__ __forceinline__ bool elect_one() {
    uint32_t pred;
    asm volatile("{\n.reg .pred p;\nelect.sync _|p, 0xffffffff;\nselp.u32 %0, 1, 0, p;\n}" : "=r"(pred));
    return pred;
}
__device__ __forceinline__ void mbar_init(uint32_t bar, uint32_t cnt) {
    asm volatile("mbarrier.init.shared::cta.b64 [%0], %1;" ::"r"(bar), "r"(cnt) : "memory");
}
__device__ __forceinline__ void mbar_expect(uint32_t bar, uint32_t bytes) {
    asm volatile("mbarrier.arrive.expect_tx.shared::cta.b64 _, [%0], %1;" ::"r"(bar), "r"(bytes) : "memory");
}
__device__ __forceinline__ void mbar_arrive(uint32_t bar) {
    asm volatile("mbarrier.arrive.shared::cta.b64 _, [%0];" ::"r"(bar) : "memory");
}
__device__ __forceinline__ void mbar_arrive(uint32_t bar, uint32_t cnt) {
    asm volatile("mbarrier.arrive.shared::cta.b64 _, [%0], %1;" ::"r"(bar), "r"(cnt) : "memory");
}
__device__ __forceinline__ bool mbar_test(uint32_t bar, uint32_t parity) {
    uint32_t ok;
    asm volatile("{\n.reg .pred p;\nmbarrier.test_wait.parity.shared::cta.b64 p, [%1], %2;\nselp.u32 %0, 1, 0, p;\n}"
                 : "=r"(ok) : "r"(bar), "r"(parity) : "memory");
    return ok;
}
__device__ __forceinline__ void mbar_wait(uint32_t bar, uint32_t parity) {
    asm volatile("{\n.reg .pred p;\n.reg .u32 n;\n"
                 "mbarrier.try_wait.parity.shared::cta.b64 p, [%0], %1;\n"
                 "@p bra DONE;\n"
                 "mov.u32 n, 0;\n"
                 "LOOP:\n"
                 "mbarrier.try_wait.parity.shared::cta.b64 p, [%0], %1;\n"
                 "@p bra DONE;\n"
                 "add.u32 n, n, 1;\n"
                 "setp.lt.u32 p, n, 0x400000;\n"
                 "@p bra LOOP;\n"
                 "trap;\n"
                 "DONE:\n}" ::"r"(bar), "r"(parity) : "memory");
}
__device__ __forceinline__ void bulk_stream(uint32_t dst, const void* src, uint32_t bytes, uint32_t bar, uint64_t pol) {
    asm volatile("cp.async.bulk.shared::cluster.global.mbarrier::complete_tx::bytes.L2::cache_hint [%0], [%1], %2, [%3], %4;"
                 ::"r"(dst), "l"(src), "r"(bytes), "r"(bar), "l"(pol) : "memory");
}
__device__ __forceinline__ void bulk_plain(uint32_t dst, const void* src, uint32_t bytes, uint32_t bar) {
    asm volatile("cp.async.bulk.shared::cluster.global.mbarrier::complete_tx::bytes [%0], [%1], %2, [%3];"
                 ::"r"(dst), "l"(src), "r"(bytes), "r"(bar) : "memory");
}
__device__ __forceinline__ void l2_prefetch(const void* src, uint32_t bytes, uint64_t pol) {
    asm volatile("cp.async.bulk.prefetch.L2.global.L2::cache_hint [%0], %1, %2;" ::"l"(src), "r"(bytes), "l"(pol) : "memory");
}
__device__ __forceinline__ void l2_prefetch(const void* src, uint32_t bytes) {
    asm volatile("cp.async.bulk.prefetch.L2.global [%0], %1;" ::"l"(src), "r"(bytes) : "memory");
}
__device__ __forceinline__ int4 lds128(uint32_t a) {
    int4 v;
    asm volatile("ld.shared.v4.s32 {%0,%1,%2,%3}, [%4];" : "=r"(v.x), "=r"(v.y), "=r"(v.z), "=r"(v.w) : "r"(a));
    return v;
}
__device__ __forceinline__ uint2 lds64(uint32_t a) {
    uint2 v;
    asm volatile("ld.shared.v2.u32 {%0,%1}, [%2];" : "=r"(v.x), "=r"(v.y) : "r"(a));
    return v;
}
__device__ __forceinline__ uint32_t lds32(uint32_t a) {
    uint32_t v;
    asm volatile("ld.shared.u32 %0, [%1];" : "=r"(v) : "r"(a));
    return v;
}
__device__ __forceinline__ uint32_t lds16(uint32_t a) {
    uint16_t v;
    asm volatile("ld.shared.u16 %0, [%1];" : "=h"(v) : "r"(a));
    return v;
}
__device__ __forceinline__ void sts32(uint32_t a, float x) {
    asm volatile("st.shared.f32 [%0], %1;" ::"r"(a), "f"(x) : "memory");
}
__device__ __forceinline__ void sts128(uint32_t a, uint32_t x, uint32_t y, uint32_t z, uint32_t w) {
    asm volatile("st.shared.v4.u32 [%0], {%1,%2,%3,%4};" ::"r"(a), "r"(x), "r"(y), "r"(z), "r"(w) : "memory");
}
__device__ __forceinline__ void sts64(uint32_t a, float x, float y) {
    asm volatile("st.shared.v2.f32 [%0], {%1,%2};" ::"r"(a), "f"(x), "f"(y) : "memory");
}
__device__ __forceinline__ float bf_lo(uint32_t v) { return __uint_as_float(v << 16); }
__device__ __forceinline__ float rbf(float x) {
    uint32_t d; asm("cvt.rn.bf16x2.f32 %0, %1, %2;" : "=r"(d) : "f"(x), "f"(0.f)); return __uint_as_float(d);
}
__device__ __forceinline__ float rcp(float x) {
    float y;
    asm("rcp.approx.ftz.f32 %0, %1;" : "=f"(y) : "f"(x));
    return y;
}
__device__ __forceinline__ float lg2(float x) {
    float y;
    asm("lg2.approx.ftz.f32 %0, %1;" : "=f"(y) : "f"(x));
    return y;
}
__device__ __forceinline__ float ex2(float x) {
    float y;
    asm("ex2.approx.ftz.f32 %0, %1;" : "=f"(y) : "f"(x));
    return y;
}
__device__ __forceinline__ uint32_t bmul(uint32_t a, uint32_t b) {
    uint32_t d; asm("mul.rn.bf16x2 %0, %1, %2;" : "=r"(d) : "r"(a), "r"(b)); return d;
}
__device__ __forceinline__ uint32_t bsub(uint32_t a, uint32_t b) {
    uint32_t d; asm("sub.rn.bf16x2 %0, %1, %2;" : "=r"(d) : "r"(a), "r"(b)); return d;
}
__device__ __forceinline__ uint32_t bfma(uint32_t a, uint32_t b, uint32_t c) {
    uint32_t d; asm("fma.rn.bf16x2 %0, %1, %2, %3;" : "=r"(d) : "r"(a), "r"(b), "r"(c)); return d;
}
__device__ __forceinline__ uint32_t i2bf2(int lo, int hi) {
    uint32_t d; asm("cvt.rn.bf16x2.f32 %0, %1, %2;" : "=r"(d) : "f"((float)hi), "f"((float)lo)); return d;
}
__device__ __forceinline__ uint32_t rope2(uint32_t x, uint32_t c, uint32_t y, uint32_t s, uint32_t sg) {
    return bfma(bmul(y, s), sg, bmul(x, c));
}
__device__ __forceinline__ void mma_bf16(float (&c)[4], uint32_t a0, uint32_t a1, uint32_t a2, uint32_t a3,
                                         uint32_t b0, uint32_t b1) {
    asm("mma.sync.aligned.m16n8k16.row.col.f32.bf16.bf16.f32 {%0,%1,%2,%3}, {%4,%5,%6,%7}, {%8,%9}, {%0,%1,%2,%3};"
        : "+f"(c[0]), "+f"(c[1]), "+f"(c[2]), "+f"(c[3])
        : "r"(a0), "r"(a1), "r"(a2), "r"(a3), "r"(b0), "r"(b1));
}
__device__ __forceinline__ void mail_put(uint32_t* p, float x, uint32_t tag) {
    asm volatile("st.relaxed.gpu.global.u32 [%0], %1;" ::"l"(p), "r"((__float_as_uint(x) & ~3u) | tag) : "memory");
}

struct Claim { uint32_t head, tile0, piece, sh, off; int ntiles; };

__device__ __forceinline__ Claim decode_claim(uint32_t c) {
    Claim cl;
    cl.sh = cl.off = 0;
    if (c < C_S) {
        cl.head = c / NM; cl.piece = c - cl.head * NM; cl.tile0 = cl.head * TPH + cl.piece * MAINP;
        cl.ntiles = cl.piece < NM - 1 ? MAINP : TPH - (NM - 1) * MAINP - semi_size(cl.head) - fin_size(cl.head);
        if (cl.piece < ((NM - 1) >> GSH << GSH)) {
            cl.sh = GSH; cl.off = cl.piece & ((1 << GSH) - 1); cl.tile0 -= cl.off * MAINP;
        }
    } else {
        cl.head = (c - C_S) % NHEAD; cl.piece = 0;
        cl.ntiles = fin_size(cl.head); cl.tile0 = (cl.head + 1) * TPH - cl.ntiles;
        if (c < C_F) { cl.ntiles = semi_size(cl.head); cl.tile0 -= cl.ntiles; }
    }
    return cl;
}

struct Params {
    const int* qk; const __nv_bfloat16* kcos; const __nv_bfloat16* ksin; const int* qv;
    const __nv_bfloat16* ks; const __nv_bfloat16* kz; const __nv_bfloat16* vs; const __nv_bfloat16* vz;
    const __nv_bfloat16* q; const __nv_bfloat16* qcos; const __nv_bfloat16* qsin;
    __nv_bfloat16* out;
};

constexpr float NEG = -3.0e38f;
constexpr float LOG2E = 1.4426950408889634f;
constexpr int F_NT = 31, F_FIRST = 32, F_LAST = 64, F_SEMI = 128, F_FIN = 256, F_SEGEND = 512, F_END = 1024;
static_assert(NHEAD * NM * REC < (1 << 20), "batch descriptor");

__global__ void __launch_bounds__(NTHREADS, 1)
kv_rope_decode_kernel(const Params p) {
    extern __shared__ __align__(128) unsigned char smem[];
    if (threadIdx.x >= NWARPS * 32 && elect_one()) {
        l2_prefetch(p.kcos + (blockIdx.x % (TPH / 2)) * (2 * TR * D), 2 * CBYTES);
        l2_prefetch(p.ksin + (blockIdx.x % (TPH / 2)) * (2 * TR * D), 2 * CBYTES);
        uint64_t pol;
        asm volatile("createpolicy.fractional.L2::evict_first.b64 %0, 1.0;" : "=l"(pol));
        const uint32_t h = blockIdx.x / NM, pc = blockIdx.x - h * NM;
        const uint32_t off = pc < ((NM - 1) >> GSH << GSH) ? pc & ((1 << GSH) - 1) : 0;
        l2_prefetch(p.qk + (size_t)(h * TPH + (pc - off) * MAINP + off * PF0) * (TR * D), PF0 * KBYTES, pol);
    }
    const int w = __shfl_sync(0xffffffffu, threadIdx.x >> 5, 0), lane = threadIdx.x & 31;
    if (w == NWARPS) return;
    const uint32_t sb = __shfl_sync(0xffffffffu, smem_u32(smem), 0);
    const uint32_t bar = sb + OFF_BAR;

    if (w < 8 && elect_one()) {
        const uint32_t cnt = w == 4 ? 8 : w == 5 ? NKW + NVW : w == 6 ? NVW : w == 7 ? 2 : 1;
#pragma unroll
        for (int i = 0; i < 16; i++) mbar_init(bar + w * 128 + i * 8, cnt);
        asm volatile("fence.mbarrier_init.release.cluster;" ::: "memory");
    }
    asm volatile("bar.sync 0, %0;" ::"n"(NWARPS * 32) : "memory");

    if ((unsigned)(w - W_V) < NVW) {
        const int v = w - W_V, g = lane >> 3, l = lane & 7;
        const bool up = lane & 16, up2 = lane & 8;
        const uint32_t oV = pin(sb + OFF_V + g * (2 * D * 4) + v * (NB * 128) + l * 16), oP = pin(S_PV + g * 8);
        const uint32_t col = pin(v * (NB * 32) + l * 4 + (up ? 2 : 0) + (up2 ? 1 : 0));
        __nv_bfloat16* const outp = pin(p.out + col);
        uint32_t* const mailp = pin(g_mail + col);
        float acc[4 * NB];
#pragma unroll
        for (int i = 0; i < 4 * NB; i++) acc[i] = 0.f;
        uint32_t vslot = 0, seg = 0, vph = 0;
        uint32_t s = sb + OFF_SEG, t0 = 0;
        mbar_wait(bar + B_PR, 0);
        uint2 bd = lds64(s + S_BD);
        uint2 pv = lds64(s + oP);
        bool ready = false;
        int4 x0[NB], x1[NB];
        auto load_tile = [&]() {
            const uint32_t t = oV + vslot * KBYTES;
            if (!ready) mbar_wait(bar + B_FV + vslot * 8, vph);
#pragma unroll
            for (int j = 0; j < NB; j++) {
                x0[j] = lds128(t + j * 128);
                x1[j] = lds128(t + 768 + j * 128);
            }
            __syncwarp();
            if (lane == 0) mbar_arrive(bar + B_EV + vslot * 8);
            if (++vslot == NV) { vslot = 0; vph ^= 1; }
            ready = mbar_test(bar + B_FV + vslot * 8, vph);
        };
        auto fma_tile = [&]() {
            const float pv0 = __uint_as_float(pv.x), pv1 = __uint_as_float(pv.y);
#pragma unroll
            for (int j = 0; j < NB; j++) {
                acc[j * 4 + 0] = fmaf(pv1, (float)x1[j].x, fmaf(pv0, (float)x0[j].x, acc[j * 4 + 0]));
                acc[j * 4 + 1] = fmaf(pv1, (float)x1[j].y, fmaf(pv0, (float)x0[j].y, acc[j * 4 + 1]));
                acc[j * 4 + 2] = fmaf(pv1, (float)x1[j].z, fmaf(pv0, (float)x0[j].z, acc[j * 4 + 2]));
                acc[j * 4 + 3] = fmaf(pv1, (float)x1[j].w, fmaf(pv0, (float)x0[j].w, acc[j * 4 + 3]));
            }
        };
        for (uint32_t batch = 1; !(bd.y & F_END); batch++) {
            const uint32_t n = bd.y & F_NT, sbar = bar + (seg % NSEG) * 8;
            const bool segend = bd.y & F_SEGEND;
            const uint32_t seg2 = seg + segend, t2 = segend ? 0 : t0 + n;
            const uint32_t s2 = sb + OFF_SEG + (seg2 % NSEG) * SEG_BYTES;
#pragma unroll
            for (int i = 0; i < 4 * NB; i++) acc[i] *= __uint_as_float(bd.x);
#pragma unroll 1
            for (uint32_t i = 1; i < n; i++) {
                load_tile();
                const uint2 pn = lds64(s + oP + (t0 + i) * (TR * 4));
                fma_tile();
                pv = pn;
            }
            load_tile();
            const bool early = mbar_test(sbar + B_FC, (seg / NSEG) & 1);
            const bool next = mbar_test(bar + B_PR + (batch % NBAT) * 8, (batch / NBAT) & 1);
            fma_tile();
            int4 cf;
            uint32_t gv[NB];
            uint2 bn, pn;
            if (early) {
                cf = lds128(s + S_CF);
#pragma unroll
                for (int j = 0; j < NB; j++) gv[j] = lds32(s + S_G + (col + j * 32) * 4);
            }
            if (bd.y & F_LAST) {
                float o[NB];
#pragma unroll
                for (int j = 0; j < NB; j++) {
                    const float u0 = (up ? acc[j * 4 + 2] : acc[j * 4 + 0]) + __shfl_xor_sync(0xffffffffu, up ? acc[j * 4 + 0] : acc[j * 4 + 2], 16);
                    const float u1 = (up ? acc[j * 4 + 3] : acc[j * 4 + 1]) + __shfl_xor_sync(0xffffffffu, up ? acc[j * 4 + 1] : acc[j * 4 + 3], 16);
                    o[j] = (up2 ? u1 : u0) + __shfl_xor_sync(0xffffffffu, up2 ? u0 : u1, 8);
                }
                if (!early) {
                    mbar_wait(sbar + B_FC, (seg / NSEG) & 1);
                    cf = lds128(s + S_CF);
#pragma unroll
                    for (int j = 0; j < NB; j++) gv[j] = lds32(s + S_G + (col + j * 32) * 4);
                }
#pragma unroll
                for (int j = 0; j < NB; j++) {
                    const float gj = (bd.y & (F_SEMI | F_FIN)) ? __uint_as_float(gv[j]) : 0.f;
                    o[j] = fmaf(o[j], __int_as_float(cf.x), fmaf(gj, __int_as_float(cf.y), __int_as_float(cf.z)));
                }
                if (bd.y & F_FIN) {
#pragma unroll
                    for (int j = 0; j < NB; j++) {
                        const __nv_bfloat16 r = __float2bfloat16_rn(o[j]);
                        asm volatile("st.global.b16 [%0], %1;" ::"l"(outp + (bd.y >> 12) + j * 32), "h"(*(const uint16_t*)&r) : "memory");
                    }
                } else {
#pragma unroll
                    for (int j = 0; j < NB; j++) mail_put(mailp + (bd.y >> 12) + j * 32, o[j], cf.w & 3);
                    if (col < REC - D) mail_put(mailp + (bd.y >> 12) + D, __int_as_float(cf.w), cf.w & 3);
                }
#pragma unroll
                for (int i = 0; i < 4 * NB; i++) acc[i] = 0.f;
            }
            if (next) {
                bn = lds64(s2 + S_BD + t2 * 8);
                pn = lds64(s2 + oP + t2 * (TR * 4));
            }
            if (segend) {
                if (!(bd.y & F_LAST)) mbar_wait(sbar + B_FC, (seg / NSEG) & 1);
                __syncwarp();
                if (lane == 0) mbar_arrive(sbar + B_SE);
            }
            if (!next) {
                mbar_wait(bar + B_PR + (batch % NBAT) * 8, (batch / NBAT) & 1);
                bn = lds64(s2 + S_BD + t2 * 8);
                pn = lds64(s2 + oP + t2 * (TR * 4));
            }
            bd = bn; pv = pn; s = s2; t0 = t2; seg = seg2;
        }
    } else if (w == W_S) {
        float m = NEG, lsum = 0.f, corr = 0.f;
        uint32_t batch = 0;
        for (uint32_t seg = 0;; seg++) {
            const uint32_t s = sb + OFF_SEG + (seg % NSEG) * SEG_BYTES, sbar = bar + (seg % NSEG) * 8;
            const uint32_t sph = (seg / NSEG) & 1;
            mbar_wait(sbar + B_HDR, sph);
            const int4 desc = lds128(s + S_DESC);
            if (desc.y & F_END) {
                if (lane == 0) {
                    sts64(s + S_BD, 0.f, __uint_as_float(F_END));
                    mbar_arrive(bar + B_PR + (batch % NBAT) * 8);
                }
                break;
            }
            if (desc.y & F_FIRST) { m = NEG; lsum = 0.f; corr = 0.f; }
            const uint32_t head = (uint32_t)desc.x / TPH, index = (desc.y & F_FIN) ? head * D : (head * NM + desc.z) * REC;
            const int nt = desc.y & F_NT;
#pragma unroll 1
            for (int t0 = 0; t0 < nt; t0 += 4, batch++) {
                const int n = min(4, nt - t0);
                const bool valid = lane < n * TR;
                const uint32_t tl = t0 + (valid ? lane >> 3 : 0), row = tl * TR + (lane & 7);
                const uint32_t sc = s + S_SC + (((tl << (desc.w & 255)) + (desc.w >> 8)) * TR + (lane & 7)) * 2;
                const float vs = bf_lo(lds16(sc + 2 * SCB)), vz = bf_lo(lds16(sc + 3 * SCB));
                mbar_wait(bar + B_LG + (batch % NBAT) * 8, (batch / NBAT) & 1);
                const int4 part = lds128(s + S_LG + row * 16);
                const float dot = (__int_as_float(part.x) + __int_as_float(part.y)) + (__int_as_float(part.z) + __int_as_float(part.w));
                const float sv = rbf(rbf(dot) * 0.07216878364870322f) * LOG2E;
                int key = __float_as_int(fmaxf(m, sv));
                key ^= (key >> 31) & 0x7fffffff;
                key = __reduce_max_sync(0xffffffffu, key);
                const float mn = __int_as_float(key ^ ((key >> 31) & 0x7fffffff));
                const float alpha = ex2(m - mn), pr = ex2(sv - mn), pv = pr * vs;
                m = mn;
                sts32(s + S_PV + row * 4, pv);
                if (lane == 0)
                    sts64(s + S_BD + t0 * 8, alpha,
                          __uint_as_float(n | (t0 + n < nt ? 0 : index << 12 | F_SEGEND | (desc.y & (F_LAST | F_SEMI | F_FIN)))));
                __syncwarp();
                if (lane == 0) mbar_arrive(bar + B_PR + (batch % NBAT) * 8);
                lsum = fmaf(lsum, alpha, valid ? pr : 0.f);
                corr = fmaf(corr, alpha, valid ? pv * vz : 0.f);
            }
            float L = lsum, C = corr;
            if (desc.y & F_LAST) {
#pragma unroll
                for (int o = 16; o > 0; o >>= 1) {
                    L += __shfl_xor_sync(0xffffffffu, L, o);
                    C += __shfl_xor_sync(0xffffffffu, C, o);
                }
            }
            mbar_wait(sbar + B_GD, sph);
            if (desc.y & F_LAST) {
                const uint32_t tag = lds32(sb + OFF_TAG) | ((desc.y & F_SEMI) ? 2 : 0);
                const float gl = (desc.y & (F_SEMI | F_FIN)) ? __uint_as_float(lds32(s + S_G + D * 4)) : -3.4e38f;
                const float M = fmaxf(m, gl), e = ex2(m - M), a = ex2(gl - M);
                const float W = fmaf(L, e, a), inv = rcp(W);
                if (lane == 0)
                    sts128(s + S_CF, __float_as_uint(e * inv), __float_as_uint(a * inv), __float_as_uint(-C * e * inv),
                           (__float_as_uint(M + lg2(W)) & ~3u) | tag);
            }
            __syncwarp();
            if (lane == 0) mbar_arrive(sbar + B_FC);
        }
    } else if ((unsigned)(w - W_G) < NGW) {
        if (w == W_G) {
            if (lane == 0) sts32(sb + OFF_TAG, __uint_as_float(~*(volatile unsigned int*)&g_epoch & 1));
        } else {
            mbar_wait(bar + B_GD, 0);
        }
        for (uint32_t seg = w - W_G;; seg += NGW) {
            const uint32_t s = sb + OFF_SEG + (seg % NSEG) * SEG_BYTES, sbar = bar + (seg % NSEG) * 8;
            mbar_wait(sbar + B_HDR, (seg / NSEG) & 1);
            const int4 desc = lds128(s + S_DESC);
            if (desc.y & F_END) break;
            if (desc.y & (F_SEMI | F_FIN)) {
                const uint32_t tag = lds32(sb + OFF_TAG) | ((desc.y & F_FIN) ? 2 : 0);
                const int cnt = (desc.y & F_FIN) ? 1 : NM;
                const uint32_t* mail = g_mail + (uint32_t)desc.x / TPH * (NM * REC);
                float M = NEG, W = 0.f, O[6] = {0.f, 0.f, 0.f, 0.f, 0.f, 0.f};
#pragma unroll 1
                for (int i0 = 0; i0 < cnt; i0 += 5, mail += 5 * REC) {
                    uint2 pk[15];
                    uint32_t ls[5], stale;
                    int it = 0;
                    do {
                        stale = 0;
#pragma unroll
                        for (int i = 0; i < 5; i++) {
                            ls[i] = 0xff7ffffcu | tag;
                            pk[3 * i] = pk[3 * i + 1] = pk[3 * i + 2] = make_uint2(tag, tag);
                            if (i0 + i < cnt) {
                                asm volatile("ld.relaxed.gpu.global.u32 %0, [%1];" : "=r"(ls[i]) : "l"(mail + i * REC + D) : "memory");
#pragma unroll
                                for (int k = 0; k < 3; k++)
                                    asm volatile("ld.relaxed.gpu.global.v2.u32 {%0,%1}, [%2];"
                                                 : "=r"(pk[3 * i + k].x), "=r"(pk[3 * i + k].y)
                                                 : "l"(mail + i * REC + k * 64 + lane * 2) : "memory");
                            }
                        }
#pragma unroll
                        for (int i = 0; i < 5; i++) stale |= ls[i] ^= tag;
#pragma unroll
                        for (int i = 0; i < 15; i++) stale |= (pk[i].x ^= tag) | (pk[i].y ^= tag);
                        if (++it > (1 << 22)) __trap();
                    } while (stale & 3);
                    float Mn = M;
#pragma unroll
                    for (int i = 0; i < 5; i++) Mn = fmaxf(Mn, __uint_as_float(ls[i]));
                    const float a = ex2(M - Mn);
                    M = Mn; W *= a;
#pragma unroll
                    for (int i = 0; i < 6; i++) O[i] *= a;
#pragma unroll
                    for (int i = 0; i < 5; i++) {
                        const float e = ex2(__uint_as_float(ls[i]) - M);
                        W += e;
#pragma unroll
                        for (int k = 0; k < 3; k++) {
                            O[2 * k] = fmaf(e, __uint_as_float(pk[3 * i + k].x), O[2 * k]);
                            O[2 * k + 1] = fmaf(e, __uint_as_float(pk[3 * i + k].y), O[2 * k + 1]);
                        }
                    }
                }
                const float inv = rcp(W);
#pragma unroll
                for (int k = 0; k < 3; k++) sts64(s + S_G + k * 256 + lane * 8, O[2 * k] * inv, O[2 * k + 1] * inv);
                if (lane == 0) sts32(s + S_G + D * 4, M + lg2(W));
            }
            __syncwarp();
            if (lane == 0) mbar_arrive(sbar + B_GD);
        }
    } else if (w / NKW == 0) {
        const int g = lane >> 3, l = lane & 7, godd = g & 1, row = 2 * g + (w & 1);
        const uint32_t sgA = pin(godd ? 0x3f803f80u : 0xbf80bf80u), sgB = pin(godd ? 0xbf80bf80u : 0x3f803f80u);
        const uint32_t oKA = pin(sb + row * (D * 4) + l * 16 + godd * 384), oKB = pin(oKA - godd * 768 + 384);
        const uint32_t oCA = pin(sb + T_C + row * (D * 2) + l * 8 + godd * 192), oCB = pin(oCA - godd * 384 + 192);
        const uint32_t oL = pin(S_LG + row * 16 + (l >> 2) * 8 + (l & 1) * 4), oS = pin(S_SC + row * 2);
        const bool own = (l & 3) == g, hi = l & 4, keep = ((l ^ g) & 2) == 0;
        uint2 qr[3];
        uint32_t kslot = w >> 1, j = kslot, batch0 = 0, kph = 0;
        for (uint32_t seg = 0;; seg++) {
            const uint32_t s = sb + OFF_SEG + (seg % NSEG) * SEG_BYTES, sbar = bar + (seg % NSEG) * 8;
            mbar_wait(sbar + B_HDR, (seg / NSEG) & 1);
            const int4 desc = lds128(s + S_DESC);
            if (desc.y & F_END) break;
            const uint32_t nt = desc.y & F_NT;
            if (desc.y & F_FIRST) {
#pragma unroll
                for (int i = 0; i < 3; i++) {
                    const uint32_t oa = l * 8 + godd * 192 + i * 64, ob = oa + 192 - godd * 384;
                    const uint2 a = lds64(s + S_Q + oa), b = lds64(s + S_Q + ob);
                    const uint2 ca = lds64(sb + OFF_QT + oa), sa = lds64(sb + OFF_QT + QBYTES + oa);
                    qr[i].x = rope2(a.x, ca.x, b.x, sa.x, sgA);
                    qr[i].y = rope2(a.y, ca.y, b.y, sa.y, sgA);
                }
            }
            for (; j < nt; j += NKW / 2) {
                const uint32_t t = kslot * KSLOT;
                const uint32_t sc = s + oS + ((j << (desc.w & 255)) + (desc.w >> 8)) * (TR * 2);
                const uint32_t ks2 = lds16(sc) * 0x10001u, kz2 = lds16(sc + SCB) * 0x10001u;
                const uint32_t lgb = bar + B_LG + ((batch0 + (j >> 2)) % NBAT) * 8;
                const uint32_t lgc = j == nt - 1 ? 4 - (j & 3) : 1;
                mbar_wait(bar + B_FK + kslot * 8, kph);
                float c[4] = {0.f, 0.f, 0.f, 0.f};
#pragma unroll
                for (int jj = 0; jj < 3; jj++) {
                    const int4 xa = lds128(t + oKA + jj * 128), xb = lds128(t + oKB + jj * 128);
                    const uint2 ca = lds64(t + oCA + jj * 64), cb = lds64(t + oCB + jj * 64);
                    const uint2 sa = lds64(t + oCA + CBYTES + jj * 64), sbv = lds64(t + oCB + CBYTES + jj * 64);
                    const uint32_t a0 = bmul(bsub(i2bf2(xa.x, xa.y), kz2), ks2);
                    const uint32_t a1 = bmul(bsub(i2bf2(xa.z, xa.w), kz2), ks2);
                    const uint32_t b0 = bmul(bsub(i2bf2(xb.x, xb.y), kz2), ks2);
                    const uint32_t b1 = bmul(bsub(i2bf2(xb.z, xb.w), kz2), ks2);
                    mma_bf16(c, rope2(a0, ca.x, b0, sa.x, sgA), rope2(b0, cb.x, a0, sbv.x, sgB),
                             rope2(a1, ca.y, b1, sa.y, sgA), rope2(b1, cb.y, a1, sbv.y, sgB), qr[jj].x, qr[jj].y);
                }
                __syncwarp();
                if (lane == 0) mbar_arrive(bar + B_EK + kslot * 8);
                const float part = own ? (hi ? c[1] : c[0]) : (hi ? c[3] : c[2]);
                if (keep) sts32(s + oL + j * (TR * 16), part);
                __syncwarp();
                if (lane == 0) mbar_arrive(lgb, lgc);
                kslot += NKW / 2;
                if (kslot >= NK) { kslot -= NK; kph ^= 1; }
            }
            j -= nt;
            batch0 += (nt + 3) >> 2;
            __syncwarp();
            if (lane == 0) mbar_arrive(sbar + B_SE);
        }
    } else if (w == W_SCH) {
        if (elect_one()) {
            asm volatile("mbarrier.expect_tx.shared::cta.b64 [%0], %1;" ::"r"(bar + B_HDR), "r"(2 * QBYTES) : "memory");
            uint32_t seg = 0, c = blockIdx.x;
            while (c < NCLAIM) {
                const Claim cl = decode_claim(c);
                uint32_t tile = cl.tile0;
#pragma unroll 1
                for (int left = cl.ntiles; left > 0; left -= SEGT, tile += SEGT) {
                    const int nt = min(SEGT, left);
                    const bool first = left == cl.ntiles, last = left == nt;
                    const uint32_t s = sb + OFF_SEG + (seg % NSEG) * SEG_BYTES, b = bar + (seg % NSEG) * 8;
                    mbar_wait(b + B_SE, ((seg / NSEG) & 1) ^ 1);
                    sts128(s + S_DESC, tile + cl.off,
                           nt | (first ? F_FIRST : 0) | (last ? F_LAST : 0) | (c >= C_F ? F_FIN : c >= C_S ? F_SEMI : 0),
                           cl.piece, cl.sh | cl.off << 8);
                    mbar_arrive(b + B_DS);
                    const uint32_t scb = nt * TR * 2 << cl.sh;
                    const uint32_t r = tile * TR;
                    mbar_expect(b + B_HDR, 4 * scb + (first ? QBYTES : 0));
                    if (first) bulk_plain(s + S_Q, p.q + cl.head * D, QBYTES, b + B_HDR);
                    bulk_plain(s + S_SC, p.ks + r, scb, b + B_HDR);
                    bulk_plain(s + S_SC + SCB, p.kz + r, scb, b + B_HDR);
                    bulk_plain(s + S_SC + 2 * SCB, p.vs + r, scb, b + B_HDR);
                    bulk_plain(s + S_SC + 3 * SCB, p.vz + r, scb, b + B_HDR);
                    if (seg == 0) {
                        bulk_plain(sb + OFF_QT, p.qcos, QBYTES, bar + B_HDR);
                        bulk_plain(sb + OFF_QT + QBYTES, p.qsin, QBYTES, bar + B_HDR);
                        mbar_wait(bar + B_GD, 0);
                    }
                    mbar_wait(bar + B_GO, seg & 1);
                    seg++;
                }
                const unsigned nx = atomicInc(&g_queue, NCLAIM - 1);
                if (nx == NCLAIM - 1) g_epoch = lds32(sb + OFF_TAG);
                c = gridDim.x + nx;
            }
#pragma unroll 1
            for (int i = 0; i < NGW; i++, seg++) {
                const uint32_t s = sb + OFF_SEG + (seg % NSEG) * SEG_BYTES, b = bar + (seg % NSEG) * 8;
                mbar_wait(b + B_SE, ((seg / NSEG) & 1) ^ 1);
                sts128(s + S_DESC, 0, F_END, 0, 0);
                mbar_arrive(b + B_DS);
                mbar_arrive(b + B_HDR);
            }
        }
    } else {
        if (elect_one()) {
            uint64_t pol;
            asm volatile("createpolicy.fractional.L2::evict_first.b64 %0, 1.0;" : "=l"(pol));
            uint32_t kslot = 0, vslot = 0, kph = 1, vph = 1;
            int pend[LEAD];
#pragma unroll
            for (int i = 0; i < LEAD; i++) pend[i] = -1;
            auto issue_v = [&]() {
                if (pend[0] >= 0) {
                    const uint32_t b = bar + vslot * 8;
                    mbar_wait(b + B_EV, vph);
                    mbar_expect(b + B_FV, KBYTES);
                    bulk_stream(sb + OFF_V + vslot * KBYTES, p.qv + (size_t)pend[0] * (TR * D), KBYTES, b + B_FV, pol);
                    if (++vslot == NV) { vslot = 0; vph ^= 1; }
                }
#pragma unroll
                for (int i = 0; i + 1 < LEAD; i++) pend[i] = pend[i + 1];
                pend[LEAD - 1] = -1;
            };
            for (uint32_t seg = 0;; seg++) {
                mbar_wait(bar + B_DS + (seg % NSEG) * 8, (seg / NSEG) & 1);
                const int4 desc = lds128(sb + OFF_SEG + (seg % NSEG) * SEG_BYTES + S_DESC);
                if (desc.y & F_END) break;
                uint32_t tile = desc.x;
                const int nt = desc.y & F_NT;
#pragma unroll 1
                for (int left = nt; left > 0; left--, tile += 1u << (desc.w & 255)) {
                    if (left == min(nt, LA)) mbar_arrive(bar + B_GO);
                    const uint32_t t = sb + kslot * KSLOT, b = bar + kslot * 8;
                    const uint32_t ro = (tile % TPH) * (TR * D);
                    mbar_wait(b + B_EK, kph);
                    mbar_expect(b + B_FK, KSLOT);
                    bulk_stream(t, p.qk + (size_t)tile * (TR * D), KBYTES, b + B_FK, pol);
                    bulk_plain(t + T_C, p.kcos + ro, CBYTES, b + B_FK);
                    bulk_plain(t + T_S, p.ksin + ro, CBYTES, b + B_FK);
                    if (++kslot == NK) { kslot = 0; kph ^= 1; }
                    pend[LEAD - 1] = tile;
                    issue_v();
                }
            }
#pragma unroll 1
            for (int i = 1; i < LEAD; i++) issue_v();
        }
    }
}

}

extern "C" void kernel_launch(void* const* d_in, const int* in_sizes, int n_in, void* d_out, int out_size) {
    (void)in_sizes; (void)n_in; (void)out_size;
    static int sms = 0;
    if (sms == 0) {
        int dev = 0;
        cudaGetDevice(&dev);
        cudaDeviceGetAttribute(&sms, cudaDevAttrMultiProcessorCount, dev);
        cudaFuncSetAttribute(kv_rope_decode_kernel, cudaFuncAttributeMaxDynamicSharedMemorySize, SMEM_BYTES);
    }
    Params p;
    p.q    = (const __nv_bfloat16*)d_in[0];
    p.qk   = (const int*)d_in[1];
    p.ks   = (const __nv_bfloat16*)d_in[2];
    p.kz   = (const __nv_bfloat16*)d_in[3];
    p.qv   = (const int*)d_in[4];
    p.vs   = (const __nv_bfloat16*)d_in[5];
    p.vz   = (const __nv_bfloat16*)d_in[6];
    p.qcos = (const __nv_bfloat16*)d_in[7];
    p.qsin = (const __nv_bfloat16*)d_in[8];
    p.kcos = (const __nv_bfloat16*)d_in[9];
    p.ksin = (const __nv_bfloat16*)d_in[10];
    p.out  = (__nv_bfloat16*)d_out;
    kv_rope_decode_kernel<<<sms, NTHREADS, SMEM_BYTES>>>(p);
}
```

```cpp
#include <cuda_runtime.h>
#include <cuda_bf16.h>
#include <stdint.h>

namespace {

constexpr int D      = 192;
constexpr int SKV    = 2048;
constexpr int NHEAD  = 256;
constexpr int TR     = 8;
constexpr int TPH    = SKV / TR;
constexpr int NKW    = 4;
constexpr int NVW    = 6;
constexpr int NB     = 6 / NVW;
constexpr int NGW    = 2;
constexpr int NK     = 8;
constexpr int NV     = 4;
constexpr int LEAD   = 5;
constexpr int NSEG   = 8;
constexpr int SEGT   = 16;
constexpr int NBAT   = 16;
constexpr int W_V = NKW, W_PROD = W_V + NVW, W_S = W_PROD + 1, W_G = W_S + 1, W_SCH = W_G + NGW, NWARPS = W_SCH + 1;
constexpr int NTHREADS = NWARPS * 32 + 32;

constexpr int MAINP  = 16;
constexpr int PF0    = 3;
constexpr int GSH    = 2;
constexpr int LA     = 3;
__host__ __device__ constexpr int semi_size(int h) { return h < 128 ? 12 - (h >> 6) * 2 : 8; }
__host__ __device__ constexpr int fin_size(int h) { return h < 64 ? 10 : 16 >> (h >> 6); }
constexpr int NM     = TPH / MAINP;
constexpr int C_S    = NHEAD * NM, C_F = C_S + NHEAD, NCLAIM = C_F + NHEAD;

constexpr int KBYTES = TR * D * 4;
constexpr int CBYTES = TR * D * 2;
constexpr int QBYTES = D * 2;
constexpr int T_C = KBYTES, T_S = T_C + CBYTES, KSLOT = T_S + CBYTES;
constexpr int SCB = SEGT * TR * 2 << GSH;
static_assert(MAINP <= SEGT && semi_size(0) <= SEGT && fin_size(0) <= SEGT && GSH >= 1, "a piece fills one segment slot");
constexpr int S_Q    = 0;
constexpr int S_SC   = S_Q + QBYTES;
constexpr int S_DESC = S_SC + 4 * SCB;
constexpr int S_BD   = S_DESC + 16;
constexpr int S_LG   = S_BD + SEGT * 8;
constexpr int S_PV   = S_LG + SEGT * TR * 16;
constexpr int S_G    = S_PV + SEGT * TR * 4;
constexpr int S_CF   = S_G + (D + 4) * 4;
constexpr int SEG_BYTES = (S_CF + 16 + 127) / 128 * 128;
constexpr int OFF_V = NK * KSLOT, OFF_SEG = OFF_V + NV * KBYTES, OFF_QT = OFF_SEG + NSEG * SEG_BYTES,
              OFF_TAG = OFF_QT + 2 * QBYTES, OFF_BAR = OFF_TAG + 16;
constexpr int B_FK = 0, B_DS = 64, B_PR = 128, B_HDR = 256, B_GD = 320, B_FC = 384, B_FV = 448, B_GO = 504,
              B_LG = 512, B_SE = 640, B_EV = 768, B_EK = 896;
constexpr int SMEM_BYTES = OFF_BAR + 1024;
static_assert(NK <= 8 && NV <= 7 && W_PROD >= 8 && NSEG == 8 && NBAT == 16, "barrier layout");
static_assert(SMEM_BYTES <= 232448 && SMEM_BYTES > 232448 / 2, "one CTA per SM");
static_assert(NSEG % NGW == 0 && NK % (NKW / 2) == 0 && NB * NVW == 6 && LEAD >= 1, "cfg");
static_assert(LEAD + NV >= 4 && LEAD + NV < NBAT && LEAD < NSEG, "no ring can be lapped or starved");

__device__ unsigned int g_queue;
constexpr int REC = 200, GB = 4;
__device__ unsigned int g_epoch;
__device__ __align__(32) uint32_t g_mail[NHEAD * NM * REC];

__device__ __forceinline__ uint32_t smem_u32(const void* p) { return (uint32_t)__cvta_generic_to_shared(p); }
__device__ __forceinline__ uint32_t pin(uint32_t x) {
    return __shfl_sync(0xffffffffu, x, threadIdx.x & 31);
}
template <class T> __device__ __forceinline__ T* pin(T* p) {
    return (T*)__shfl_sync(0xffffffffu, (unsigned long long)p, threadIdx.x & 31);
}
__device__ __forceinline__ bool elect_one() {
    uint32_t pred;
    asm volatile("{\n.reg .pred p;\nelect.sync _|p, 0xffffffff;\nselp.u32 %0, 1, 0, p;\n}" : "=r"(pred));
    return pred;
}
__device__ __forceinline__ void mbar_init(uint32_t bar, uint32_t cnt) {
    asm volatile("mbarrier.init.shared::cta.b64 [%0], %1;" ::"r"(bar), "r"(cnt) : "memory");
}
__device__ __forceinline__ void mbar_expect(uint32_t bar, uint32_t bytes) {
    asm volatile("mbarrier.arrive.expect_tx.shared::cta.b64 _, [%0], %1;" ::"r"(bar), "r"(bytes) : "memory");
}
__device__ __forceinline__ void mbar_arrive(uint32_t bar) {
    asm volatile("mbarrier.arrive.shared::cta.b64 _, [%0];" ::"r"(bar) : "memory");
}
__device__ __forceinline__ void mbar_arrive(uint32_t bar, uint32_t cnt) {
    asm volatile("mbarrier.arrive.shared::cta.b64 _, [%0], %1;" ::"r"(bar), "r"(cnt) : "memory");
}
__device__ __forceinline__ bool mbar_test(uint32_t bar, uint32_t parity) {
    uint32_t ok;
    asm volatile("{\n.reg .pred p;\nmbarrier.test_wait.parity.shared::cta.b64 p, [%1], %2;\nselp.u32 %0, 1, 0, p;\n}"
                 : "=r"(ok) : "r"(bar), "r"(parity) : "memory");
    return ok;
}
__device__ __forceinline__ void mbar_wait(uint32_t bar, uint32_t parity) {
    asm volatile("{\n.reg .pred p;\n.reg .u32 n;\n"
                 "mbarrier.try_wait.parity.shared::cta.b64 p, [%0], %1;\n"
                 "@p bra DONE;\n"
                 "mov.u32 n, 0;\n"
                 "LOOP:\n"
                 "mbarrier.try_wait.parity.shared::cta.b64 p, [%0], %1;\n"
                 "@p bra DONE;\n"
                 "add.u32 n, n, 1;\n"
                 "setp.lt.u32 p, n, 0x400000;\n"
                 "@p bra LOOP;\n"
                 "trap;\n"
                 "DONE:\n}" ::"r"(bar), "r"(parity) : "memory");
}
__device__ __forceinline__ void bulk_stream(uint32_t dst, const void* src, uint32_t bytes, uint32_t bar, uint64_t pol) {
    asm volatile("cp.async.bulk.shared::cluster.global.mbarrier::complete_tx::bytes.L2::cache_hint [%0], [%1], %2, [%3], %4;"
                 ::"r"(dst), "l"(src), "r"(bytes), "r"(bar), "l"(pol) : "memory");
}
__device__ __forceinline__ void bulk_plain(uint32_t dst, const void* src, uint32_t bytes, uint32_t bar) {
    asm volatile("cp.async.bulk.shared::cluster.global.mbarrier::complete_tx::bytes [%0], [%1], %2, [%3];"
                 ::"r"(dst), "l"(src), "r"(bytes), "r"(bar) : "memory");
}
__device__ __forceinline__ void l2_prefetch(const void* src, uint32_t bytes, uint64_t pol) {
    asm volatile("cp.async.bulk.prefetch.L2.global.L2::cache_hint [%0], %1, %2;" ::"l"(src), "r"(bytes), "l"(pol) : "memory");
}
__device__ __forceinline__ void l2_prefetch(const void* src, uint32_t bytes) {
    asm volatile("cp.async.bulk.prefetch.L2.global [%0], %1;" ::"l"(src), "r"(bytes) : "memory");
}
__device__ __forceinline__ int4 lds128(uint32_t a) {
    int4 v;
    asm volatile("ld.shared.v4.s32 {%0,%1,%2,%3}, [%4];" : "=r"(v.x), "=r"(v.y), "=r"(v.z), "=r"(v.w) : "r"(a));
    return v;
}
__device__ __forceinline__ uint2 lds64(uint32_t a) {
    uint2 v;
    asm volatile("ld.shared.v2.u32 {%0,%1}, [%2];" : "=r"(v.x), "=r"(v.y) : "r"(a));
    return v;
}
__device__ __forceinline__ uint32_t lds32(uint32_t a) {
    uint32_t v;
    asm volatile("ld.shared.u32 %0, [%1];" : "=r"(v) : "r"(a));
    return v;
}
__device__ __forceinline__ uint32_t lds16(uint32_t a) {
    uint16_t v;
    asm volatile("ld.shared.u16 %0, [%1];" : "=h"(v) : "r"(a));
    return v;
}
__device__ __forceinline__ void sts32(uint32_t a, float x) {
    asm volatile("st.shared.f32 [%0], %1;" ::"r"(a), "f"(x) : "memory");
}
__device__ __forceinline__ void sts128(uint32_t a, uint32_t x, uint32_t y, uint32_t z, uint32_t w) {
    asm volatile("st.shared.v4.u32 [%0], {%1,%2,%3,%4};" ::"r"(a), "r"(x), "r"(y), "r"(z), "r"(w) : "memory");
}
__device__ __forceinline__ void sts64(uint32_t a, float x, float y) {
    asm volatile("st.shared.v2.f32 [%0], {%1,%2};" ::"r"(a), "f"(x), "f"(y) : "memory");
}
__device__ __forceinline__ float bf_lo(uint32_t v) { return __uint_as_float(v << 16); }
__device__ __forceinline__ float rbf(float x) {
    uint32_t d; asm("cvt.rn.bf16x2.f32 %0, %1, %2;" : "=r"(d) : "f"(x), "f"(0.f)); return __uint_as_float(d);
}
__device__ __forceinline__ float rcp(float x) {
    float y;
    asm("rcp.approx.ftz.f32 %0, %1;" : "=f"(y) : "f"(x));
    return y;
}
__device__ __forceinline__ float lg2(float x) {
    float y;
    asm("lg2.approx.ftz.f32 %0, %1;" : "=f"(y) : "f"(x));
    return y;
}
__device__ __forceinline__ float ex2(float x) {
    float y;
    asm("ex2.approx.ftz.f32 %0, %1;" : "=f"(y) : "f"(x));
    return y;
}
__device__ __forceinline__ uint32_t bmul(uint32_t a, uint32_t b) {
    uint32_t d; asm("mul.rn.bf16x2 %0, %1, %2;" : "=r"(d) : "r"(a), "r"(b)); return d;
}
__device__ __forceinline__ uint32_t bsub(uint32_t a, uint32_t b) {
    uint32_t d; asm("sub.rn.bf16x2 %0, %1, %2;" : "=r"(d) : "r"(a), "r"(b)); return d;
}
__device__ __forceinline__ uint32_t bfma(uint32_t a, uint32_t b, uint32_t c) {
    uint32_t d; asm("fma.rn.bf16x2 %0, %1, %2, %3;" : "=r"(d) : "r"(a), "r"(b), "r"(c)); return d;
}
__device__ __forceinline__ uint32_t i2bf2(int lo, int hi) {
    uint32_t d; asm("cvt.rn.bf16x2.f32 %0, %1, %2;" : "=r"(d) : "f"((float)hi), "f"((float)lo)); return d;
}
__device__ __forceinline__ uint32_t rope2(uint32_t x, uint32_t c, uint32_t y, uint32_t s, uint32_t sg) {
    return bfma(bmul(y, s), sg, bmul(x, c));
}
__device__ __forceinline__ void mma_bf16(float (&c)[4], uint32_t a0, uint32_t a1, uint32_t a2, uint32_t a3,
                                         uint32_t b0, uint32_t b1) {
    asm("mma.sync.aligned.m16n8k16.row.col.f32.bf16.bf16.f32 {%0,%1,%2,%3}, {%4,%5,%6,%7}, {%8,%9}, {%0,%1,%2,%3};"
        : "+f"(c[0]), "+f"(c[1]), "+f"(c[2]), "+f"(c[3])
        : "r"(a0), "r"(a1), "r"(a2), "r"(a3), "r"(b0), "r"(b1));
}
__device__ __forceinline__ void mail_put(uint32_t* p, float x, uint32_t tag) {
    asm volatile("st.relaxed.gpu.global.u32 [%0], %1;" ::"l"(p), "r"((__float_as_uint(x) & ~3u) | tag) : "memory");
}

struct Claim { uint32_t head, tile0, piece, sh, off; int ntiles; };

__device__ __forceinline__ Claim decode_claim(uint32_t c) {
    Claim cl;
    cl.sh = cl.off = 0;
    if (c < C_S) {
        cl.head = c / NM; cl.piece = c % NM; cl.sh = GSH; cl.off = c % (1 << GSH); cl.tile0 = (c - cl.off) * MAINP;
        cl.ntiles = MAINP;
        if (cl.piece >= NM - (1 << GSH))
            cl.ntiles -= (semi_size(cl.head) + fin_size(cl.head) + cl.off) >> GSH;
    } else {
        cl.head = (c - C_S) % NHEAD; cl.piece = 0;
        cl.ntiles = fin_size(cl.head); cl.tile0 = (cl.head + 1) * TPH - cl.ntiles;
        if (c < C_F) { cl.ntiles = semi_size(cl.head); cl.tile0 -= cl.ntiles; }
    }
    return cl;
}

struct Params {
    const int* qk; const __nv_bfloat16* kcos; const __nv_bfloat16* ksin; const int* qv;
    const __nv_bfloat16* ks; const __nv_bfloat16* kz; const __nv_bfloat16* vs; const __nv_bfloat16* vz;
    const __nv_bfloat16* q; const __nv_bfloat16* qcos; const __nv_bfloat16* qsin;
    __nv_bfloat16* out;
};

constexpr float NEG = -3.0e38f;
constexpr float LOG2E = 1.4426950408889634f;
constexpr int F_NT = 31, F_LAST = 64, F_SEMI = 128, F_FIN = 256, F_END = 512;
static_assert(NHEAD * NM * REC < (1 << 20), "batch descriptor");

__global__ void __launch_bounds__(NTHREADS, 1)
kv_rope_decode_kernel(const Params p) {
    extern __shared__ __align__(128) unsigned char smem[];
    if (threadIdx.x >= NWARPS * 32 && elect_one()) {
        l2_prefetch(p.kcos + (blockIdx.x % (TPH / 2)) * (2 * TR * D), 2 * CBYTES);
        l2_prefetch(p.ksin + (blockIdx.x % (TPH / 2)) * (2 * TR * D), 2 * CBYTES);
        uint64_t pol;
        asm volatile("createpolicy.fractional.L2::evict_first.b64 %0, 1.0;" : "=l"(pol));
        const uint32_t off = blockIdx.x % (1 << GSH);
        l2_prefetch(p.qk + (size_t)((blockIdx.x - off) * MAINP + off * PF0) * (TR * D), PF0 * KBYTES, pol);
    }
    const int w = __shfl_sync(0xffffffffu, threadIdx.x >> 5, 0), lane = threadIdx.x & 31;
    if (w == NWARPS) return;
    const uint32_t sb = __shfl_sync(0xffffffffu, smem_u32(smem), 0);
    const uint32_t bar = sb + OFF_BAR;

    if (w < 8 && elect_one()) {
        const uint32_t cnt = w == 4 ? 8 : w == 5 ? NKW + NVW : w == 6 ? NVW : w == 7 ? 2 : 1;
#pragma unroll
        for (int i = 0; i < 16; i++) mbar_init(bar + w * 128 + i * 8, cnt);
        asm volatile("fence.mbarrier_init.release.cluster;" ::: "memory");
    }
    asm volatile("bar.sync 0, %0;" ::"n"(NWARPS * 32) : "memory");

    if ((unsigned)(w - W_V) < NVW) {
        const int v = w - W_V, g = lane >> 3, l = lane & 7;
        const bool up = lane & 16, up2 = lane & 8;
        const uint32_t oV = pin(sb + OFF_V + g * (2 * D * 4) + v * (NB * 128) + l * 16), oP = pin(S_PV + g * 8);
        const uint32_t col = pin(v * (NB * 32) + l * 4 + (up ? 2 : 0) + (up2 ? 1 : 0));
        __nv_bfloat16* const outp = pin(p.out + col);
        uint32_t* const mailp = pin(g_mail + col);
        float acc[4 * NB];
#pragma unroll
        for (int i = 0; i < 4 * NB; i++) acc[i] = 0.f;
        uint32_t vslot = 0, seg = 0, vph = 0;
        uint32_t s = sb + OFF_SEG, t0 = 0;
        mbar_wait(bar + B_PR, 0);
        uint2 bd = lds64(s + S_BD);
        uint2 pv = lds64(s + oP);
        bool ready = false;
        int4 x0[NB], x1[NB];
        auto load_tile = [&]() {
            const uint32_t t = oV + vslot * KBYTES;
            if (!ready) mbar_wait(bar + B_FV + vslot * 8, vph);
#pragma unroll
            for (int j = 0; j < NB; j++) {
                x0[j] = lds128(t + j * 128);
                x1[j] = lds128(t + 768 + j * 128);
            }
            __syncwarp();
            if (lane == 0) mbar_arrive(bar + B_EV + vslot * 8);
            if (++vslot == NV) { vslot = 0; vph ^= 1; }
            ready = mbar_test(bar + B_FV + vslot * 8, vph);
        };
        auto fma_tile = [&]() {
            const float pv0 = __uint_as_float(pv.x), pv1 = __uint_as_float(pv.y);
#pragma unroll
            for (int j = 0; j < NB; j++) {
                acc[j * 4 + 0] = fmaf(pv1, (float)x1[j].x, fmaf(pv0, (float)x0[j].x, acc[j * 4 + 0]));
                acc[j * 4 + 1] = fmaf(pv1, (float)x1[j].y, fmaf(pv0, (float)x0[j].y, acc[j * 4 + 1]));
                acc[j * 4 + 2] = fmaf(pv1, (float)x1[j].z, fmaf(pv0, (float)x0[j].z, acc[j * 4 + 2]));
                acc[j * 4 + 3] = fmaf(pv1, (float)x1[j].w, fmaf(pv0, (float)x0[j].w, acc[j * 4 + 3]));
            }
        };
        for (uint32_t batch = 1; !(bd.y & F_END); batch++) {
            const uint32_t n = bd.y & F_NT, sbar = bar + (seg % NSEG) * 8;
            const bool last = bd.y & F_LAST;
            const uint32_t seg2 = seg + last, t2 = last ? 0 : t0 + n;
            const uint32_t s2 = sb + OFF_SEG + (seg2 % NSEG) * SEG_BYTES;
#pragma unroll
            for (int i = 0; i < 4 * NB; i++) acc[i] *= __uint_as_float(bd.x);
#pragma unroll 1
            for (uint32_t i = 1; i < n; i++) {
                load_tile();
                const uint2 pn = lds64(s + oP + (t0 + i) * (TR * 4));
                fma_tile();
                pv = pn;
            }
            load_tile();
            const bool early = mbar_test(sbar + B_FC, (seg / NSEG) & 1);
            const bool next = mbar_test(bar + B_PR + (batch % NBAT) * 8, (batch / NBAT) & 1);
            fma_tile();
            int4 cf;
            uint32_t gv[NB];
            uint2 bn, pn;
            if (early) {
                cf = lds128(s + S_CF);
#pragma unroll
                for (int j = 0; j < NB; j++) gv[j] = lds32(s + S_G + (col + j * 32) * 4);
            }
            if (last) {
                float o[NB];
#pragma unroll
                for (int j = 0; j < NB; j++) {
                    const float u0 = (up ? acc[j * 4 + 2] : acc[j * 4 + 0]) + __shfl_xor_sync(0xffffffffu, up ? acc[j * 4 + 0] : acc[j * 4 + 2], 16);
                    const float u1 = (up ? acc[j * 4 + 3] : acc[j * 4 + 1]) + __shfl_xor_sync(0xffffffffu, up ? acc[j * 4 + 1] : acc[j * 4 + 3], 16);
                    o[j] = (up2 ? u1 : u0) + __shfl_xor_sync(0xffffffffu, up2 ? u0 : u1, 8);
                }
                if (!early) {
                    mbar_wait(sbar + B_FC, (seg / NSEG) & 1);
                    cf = lds128(s + S_CF);
#pragma unroll
                    for (int j = 0; j < NB; j++) gv[j] = lds32(s + S_G + (col + j * 32) * 4);
                }
#pragma unroll
                for (int j = 0; j < NB; j++) {
                    const float gj = (bd.y & (F_SEMI | F_FIN)) ? __uint_as_float(gv[j]) : 0.f;
                    o[j] = fmaf(o[j], __int_as_float(cf.x), fmaf(gj, __int_as_float(cf.y), __int_as_float(cf.z)));
                }
                if (bd.y & F_FIN) {
#pragma unroll
                    for (int j = 0; j < NB; j++) {
                        const __nv_bfloat16 r = __float2bfloat16_rn(o[j]);
                        asm volatile("st.global.b16 [%0], %1;" ::"l"(outp + (bd.y >> 12) + j * 32), "h"(*(const uint16_t*)&r) : "memory");
                    }
                } else {
#pragma unroll
                    for (int j = 0; j < NB; j++) mail_put(mailp + (bd.y >> 12) + j * 32, o[j], cf.w & 3);
                    if (col < REC - D) mail_put(mailp + (bd.y >> 12) + D, __int_as_float(cf.w), cf.w & 3);
                }
#pragma unroll
                for (int i = 0; i < 4 * NB; i++) acc[i] = 0.f;
            }
            if (next) {
                bn = lds64(s2 + S_BD + t2 * 8);
                pn = lds64(s2 + oP + t2 * (TR * 4));
            }
            if (last) {
                __syncwarp();
                if (lane == 0) mbar_arrive(sbar + B_SE);
            }
            if (!next) {
                mbar_wait(bar + B_PR + (batch % NBAT) * 8, (batch / NBAT) & 1);
                bn = lds64(s2 + S_BD + t2 * 8);
                pn = lds64(s2 + oP + t2 * (TR * 4));
            }
            bd = bn; pv = pn; s = s2; t0 = t2; seg = seg2;
        }
    } else if (w == W_S) {
        uint32_t batch = 0;
        for (uint32_t seg = 0;; seg++) {
            const uint32_t s = sb + OFF_SEG + (seg % NSEG) * SEG_BYTES, sbar = bar + (seg % NSEG) * 8;
            const uint32_t sph = (seg / NSEG) & 1;
            mbar_wait(sbar + B_HDR, sph);
            const int4 desc = lds128(s + S_DESC);
            if (desc.y & F_END) {
                if (lane == 0) {
                    sts64(s + S_BD, 0.f, __uint_as_float(F_END));
                    mbar_arrive(bar + B_PR + (batch % NBAT) * 8);
                }
                break;
            }
            float m = NEG, L = 0.f, C = 0.f;
            const uint32_t head = (uint32_t)desc.x / TPH, index = (desc.y & F_FIN) ? head * D : (head * NM + desc.z) * REC;
            const int nt = desc.y & F_NT;
#pragma unroll 1
            for (int t0 = 0; t0 < nt; t0 += 4, batch++) {
                const int n = min(4, nt - t0);
                const bool valid = lane < n * TR;
                const uint32_t tl = t0 + (valid ? lane >> 3 : 0), row = tl * TR + (lane & 7);
                const uint32_t sc = s + S_SC + (((tl << (desc.w & 255)) + (desc.w >> 8)) * TR + (lane & 7)) * 2;
                const float vs = bf_lo(lds16(sc + 2 * SCB)), vz = bf_lo(lds16(sc + 3 * SCB));
                mbar_wait(bar + B_LG + (batch % NBAT) * 8, (batch / NBAT) & 1);
                const int4 part = lds128(s + S_LG + row * 16);
                const float dot = (__int_as_float(part.x) + __int_as_float(part.y)) + (__int_as_float(part.z) + __int_as_float(part.w));
                const float sv = rbf(rbf(dot) * 0.07216878364870322f) * LOG2E;
                int key = __float_as_int(fmaxf(m, sv));
                key ^= (key >> 31) & 0x7fffffff;
                key = __reduce_max_sync(0xffffffffu, key);
                const float mn = __int_as_float(key ^ ((key >> 31) & 0x7fffffff));
                const float alpha = ex2(m - mn), pr = ex2(sv - mn), pv = pr * vs;
                m = mn;
                sts32(s + S_PV + row * 4, pv);
                if (lane == 0)
                    sts64(s + S_BD + t0 * 8, alpha,
                          __uint_as_float(n | (t0 + n < nt ? 0 : index << 12 | F_LAST | (desc.y & (F_SEMI | F_FIN)))));
                __syncwarp();
                if (lane == 0) mbar_arrive(bar + B_PR + (batch % NBAT) * 8);
                L = fmaf(L, alpha, valid ? pr : 0.f);
                C = fmaf(C, alpha, valid ? pv * vz : 0.f);
            }
#pragma unroll
            for (int o = 16; o > 0; o >>= 1) {
                L += __shfl_xor_sync(0xffffffffu, L, o);
                C += __shfl_xor_sync(0xffffffffu, C, o);
            }
            mbar_wait(sbar + B_GD, sph);
            const uint32_t tag = lds32(sb + OFF_TAG) | ((desc.y & F_SEMI) ? 2 : 0);
            const float gl = (desc.y & (F_SEMI | F_FIN)) ? __uint_as_float(lds32(s + S_G + D * 4)) : -3.4e38f;
            const float M = fmaxf(m, gl), e = ex2(m - M), a = ex2(gl - M);
            const float W = fmaf(L, e, a), inv = rcp(W);
            if (lane == 0)
                sts128(s + S_CF, __float_as_uint(e * inv), __float_as_uint(a * inv), __float_as_uint(-C * e * inv),
                       (__float_as_uint(M + lg2(W)) & ~3u) | tag);
            __syncwarp();
            if (lane == 0) mbar_arrive(sbar + B_FC);
        }
    } else if ((unsigned)(w - W_G) < NGW) {
        if (w == W_G) {
            if (lane == 0) sts32(sb + OFF_TAG, __uint_as_float(~*(volatile unsigned int*)&g_epoch & 1));
        } else {
            mbar_wait(bar + B_GD, 0);
        }
        for (uint32_t seg = w - W_G;; seg += NGW) {
            const uint32_t s = sb + OFF_SEG + (seg % NSEG) * SEG_BYTES, sbar = bar + (seg % NSEG) * 8;
            mbar_wait(sbar + B_HDR, (seg / NSEG) & 1);
            const int4 desc = lds128(s + S_DESC);
            if (desc.y & F_END) break;
            if (desc.y & (F_SEMI | F_FIN)) {
                const uint32_t tag = lds32(sb + OFF_TAG) | ((desc.y & F_FIN) ? 2 : 0);
                const int cnt = (desc.y & F_FIN) ? 1 : NM;
                const uint32_t* mail = g_mail + (uint32_t)desc.x / TPH * (NM * REC);
                float M = NEG, W = 0.f, O[6] = {0.f, 0.f, 0.f, 0.f, 0.f, 0.f};
#pragma unroll 1
                for (int i0 = 0; i0 < cnt; i0 += GB, mail += GB * REC) {
                    uint2 pk[3 * GB];
                    uint32_t ls[GB], stale;
                    int it = 0;
                    do {
                        stale = 0;
#pragma unroll
                        for (int i = 0; i < GB; i++) {
                            ls[i] = 0xff7ffffcu | tag;
                            pk[3 * i] = pk[3 * i + 1] = pk[3 * i + 2] = make_uint2(tag, tag);
                            if (i0 + i < cnt) {
                                asm volatile("ld.relaxed.gpu.global.u32 %0, [%1];" : "=r"(ls[i]) : "l"(mail + i * REC + D) : "memory");
#pragma unroll
                                for (int k = 0; k < 3; k++)
                                    asm volatile("ld.relaxed.gpu.global.v2.u32 {%0,%1}, [%2];"
                                                 : "=r"(pk[3 * i + k].x), "=r"(pk[3 * i + k].y)
                                                 : "l"(mail + i * REC + k * 64 + lane * 2) : "memory");
                            }
                        }
#pragma unroll
                        for (int i = 0; i < GB; i++) stale |= ls[i] ^= tag;
#pragma unroll
                        for (int i = 0; i < 3 * GB; i++) stale |= (pk[i].x ^= tag) | (pk[i].y ^= tag);
                        if (++it > (1 << 22)) __trap();
                    } while (stale & 3);
                    float Mn = M;
#pragma unroll
                    for (int i = 0; i < GB; i++) Mn = fmaxf(Mn, __uint_as_float(ls[i]));
                    const float a = ex2(M - Mn);
                    M = Mn; W *= a;
#pragma unroll
                    for (int i = 0; i < 6; i++) O[i] *= a;
#pragma unroll
                    for (int i = 0; i < GB; i++) {
                        const float e = ex2(__uint_as_float(ls[i]) - M);
                        W += e;
#pragma unroll
                        for (int k = 0; k < 3; k++) {
                            O[2 * k] = fmaf(e, __uint_as_float(pk[3 * i + k].x), O[2 * k]);
                            O[2 * k + 1] = fmaf(e, __uint_as_float(pk[3 * i + k].y), O[2 * k + 1]);
                        }
                    }
                }
                const float inv = rcp(W);
#pragma unroll
                for (int k = 0; k < 3; k++) sts64(s + S_G + k * 256 + lane * 8, O[2 * k] * inv, O[2 * k + 1] * inv);
                if (lane == 0) sts32(s + S_G + D * 4, M + lg2(W));
            }
            __syncwarp();
            if (lane == 0) mbar_arrive(sbar + B_GD);
        }
    } else if (w / NKW == 0) {
        const int g = lane >> 3, l = lane & 7, godd = g & 1, row = 2 * g + (w & 1);
        const uint32_t sgA = pin(godd ? 0x3f803f80u : 0xbf80bf80u), sgB = pin(godd ? 0xbf80bf80u : 0x3f803f80u);
        const uint32_t oKA = pin(sb + row * (D * 4) + l * 16 + godd * 384), oKB = pin(oKA - godd * 768 + 384);
        const uint32_t oCA = pin(sb + T_C + row * (D * 2) + l * 8 + godd * 192), oCB = pin(oCA - godd * 384 + 192);
        const uint32_t oL = pin(S_LG + row * 16 + (l >> 2) * 8 + (l & 1) * 4), oS = pin(S_SC + row * 2);
        const bool own = (l & 3) == g, hi = l & 4, keep = ((l ^ g) & 2) == 0;
        uint32_t kslot = w >> 1, j = kslot, batch0 = 0, kph = 0;
        for (uint32_t seg = 0;; seg++) {
            const uint32_t s = sb + OFF_SEG + (seg % NSEG) * SEG_BYTES, sbar = bar + (seg % NSEG) * 8;
            mbar_wait(sbar + B_HDR, (seg / NSEG) & 1);
            const int4 desc = lds128(s + S_DESC);
            if (desc.y & F_END) break;
            const uint32_t nt = desc.y & F_NT;
            uint2 qr[3];
#pragma unroll
            for (int i = 0; i < 3; i++) {
                const uint32_t oa = l * 8 + godd * 192 + i * 64, ob = oa + 192 - godd * 384;
                const uint2 a = lds64(s + S_Q + oa), b = lds64(s + S_Q + ob);
                const uint2 ca = lds64(sb + OFF_QT + oa), sa = lds64(sb + OFF_QT + QBYTES + oa);
                qr[i].x = rope2(a.x, ca.x, b.x, sa.x, sgA);
                qr[i].y = rope2(a.y, ca.y, b.y, sa.y, sgA);
            }
            for (; j < nt; j += NKW / 2) {
                const uint32_t t = kslot * KSLOT;
                const uint32_t sc = s + oS + ((j << (desc.w & 255)) + (desc.w >> 8)) * (TR * 2);
                const uint32_t ks2 = lds16(sc) * 0x10001u, kz2 = lds16(sc + SCB) * 0x10001u;
                const uint32_t lgb = bar + B_LG + ((batch0 + (j >> 2)) % NBAT) * 8;
                const uint32_t lgc = j == nt - 1 ? 4 - (j & 3) : 1;
                mbar_wait(bar + B_FK + kslot * 8, kph);
                float c[4] = {0.f, 0.f, 0.f, 0.f};
#pragma unroll
                for (int jj = 0; jj < 3; jj++) {
                    const int4 xa = lds128(t + oKA + jj * 128), xb = lds128(t + oKB + jj * 128);
                    const uint2 ca = lds64(t + oCA + jj * 64), cb = lds64(t + oCB + jj * 64);
                    const uint2 sa = lds64(t + oCA + CBYTES + jj * 64), sbv = lds64(t + oCB + CBYTES + jj * 64);
                    const uint32_t a0 = bmul(bsub(i2bf2(xa.x, xa.y), kz2), ks2);
                    const uint32_t a1 = bmul(bsub(i2bf2(xa.z, xa.w), kz2), ks2);
                    const uint32_t b0 = bmul(bsub(i2bf2(xb.x, xb.y), kz2), ks2);
                    const uint32_t b1 = bmul(bsub(i2bf2(xb.z, xb.w), kz2), ks2);
                    mma_bf16(c, rope2(a0, ca.x, b0, sa.x, sgA), rope2(b0, cb.x, a0, sbv.x, sgB),
                             rope2(a1, ca.y, b1, sa.y, sgA), rope2(b1, cb.y, a1, sbv.y, sgB), qr[jj].x, qr[jj].y);
                }
                __syncwarp();
                if (lane == 0) mbar_arrive(bar + B_EK + kslot * 8);
                const float part = own ? (hi ? c[1] : c[0]) : (hi ? c[3] : c[2]);
                if (keep) sts32(s + oL + j * (TR * 16), part);
                __syncwarp();
                if (lane == 0) mbar_arrive(lgb, lgc);
                kslot += NKW / 2;
                if (kslot >= NK) { kslot -= NK; kph ^= 1; }
            }
            j -= nt;
            batch0 += (nt + 3) >> 2;
            __syncwarp();
            if (lane == 0) mbar_arrive(sbar + B_SE);
        }
    } else if (w == W_SCH) {
        if (elect_one()) {
            asm volatile("mbarrier.expect_tx.shared::cta.b64 [%0], %1;" ::"r"(bar + B_HDR), "r"(2 * QBYTES) : "memory");
            uint32_t seg = 0, c = blockIdx.x;
            while (c < NCLAIM) {
                const Claim cl = decode_claim(c);
                const uint32_t s = sb + OFF_SEG + (seg % NSEG) * SEG_BYTES, b = bar + (seg % NSEG) * 8;
                mbar_wait(b + B_SE, ((seg / NSEG) & 1) ^ 1);
                sts128(s + S_DESC, cl.tile0 + cl.off, cl.ntiles | (c >= C_F ? F_FIN : c >= C_S ? F_SEMI : 0), cl.piece,
                       cl.sh | cl.off << 8);
                mbar_arrive(b + B_DS);
                const uint32_t scb = cl.ntiles * TR * 2 << cl.sh, r = cl.tile0 * TR;
                mbar_expect(b + B_HDR, 4 * scb + QBYTES);
                bulk_plain(s + S_Q, p.q + cl.head * D, QBYTES, b + B_HDR);
                bulk_plain(s + S_SC, p.ks + r, scb, b + B_HDR);
                bulk_plain(s + S_SC + SCB, p.kz + r, scb, b + B_HDR);
                bulk_plain(s + S_SC + 2 * SCB, p.vs + r, scb, b + B_HDR);
                bulk_plain(s + S_SC + 3 * SCB, p.vz + r, scb, b + B_HDR);
                if (seg == 0) {
                    bulk_plain(sb + OFF_QT, p.qcos, QBYTES, bar + B_HDR);
                    bulk_plain(sb + OFF_QT + QBYTES, p.qsin, QBYTES, bar + B_HDR);
                    mbar_wait(bar + B_GD, 0);
                }
                mbar_wait(bar + B_GO, seg & 1);
                seg++;
                const unsigned nx = atomicInc(&g_queue, NCLAIM - 1);
                if (nx == NCLAIM - 1) g_epoch = lds32(sb + OFF_TAG);
                c = gridDim.x + nx;
            }
#pragma unroll 1
            for (int i = 0; i < NGW; i++, seg++) {
                const uint32_t s = sb + OFF_SEG + (seg % NSEG) * SEG_BYTES, b = bar + (seg % NSEG) * 8;
                mbar_wait(b + B_SE, ((seg / NSEG) & 1) ^ 1);
                sts128(s + S_DESC, 0, F_END, 0, 0);
                mbar_arrive(b + B_DS);
                mbar_arrive(b + B_HDR);
            }
        }
    } else {
        if (elect_one()) {
            uint64_t pol;
            asm volatile("createpolicy.fractional.L2::evict_first.b64 %0, 1.0;" : "=l"(pol));
            uint32_t kslot = 0, vslot = 0, kph = 1, vph = 1;
            int pend[LEAD];
#pragma unroll
            for (int i = 0; i < LEAD; i++) pend[i] = -1;
            auto issue_v = [&]() {
                if (pend[0] >= 0) {
                    const uint32_t b = bar + vslot * 8;
                    mbar_wait(b + B_EV, vph);
                    mbar_expect(b + B_FV, KBYTES);
                    bulk_stream(sb + OFF_V + vslot * KBYTES, p.qv + (size_t)pend[0] * (TR * D), KBYTES, b + B_FV, pol);
                    if (++vslot == NV) { vslot = 0; vph ^= 1; }
                }
#pragma unroll
                for (int i = 0; i + 1 < LEAD; i++) pend[i] = pend[i + 1];
                pend[LEAD - 1] = -1;
            };
            for (uint32_t seg = 0;; seg++) {
                mbar_wait(bar + B_DS + (seg % NSEG) * 8, (seg / NSEG) & 1);
                const int4 desc = lds128(sb + OFF_SEG + (seg % NSEG) * SEG_BYTES + S_DESC);
                if (desc.y & F_END) break;
                uint32_t tile = desc.x;
                const int nt = desc.y & F_NT;
#pragma unroll 1
                for (int left = nt; left > 0; left--, tile += 1u << (desc.w & 255)) {
                    if (left == min(nt, LA)) mbar_arrive(bar + B_GO);
                    const uint32_t t = sb + kslot * KSLOT, b = bar + kslot * 8;
                    const uint32_t ro = (tile % TPH) * (TR * D);
                    mbar_wait(b + B_EK, kph);
                    mbar_expect(b + B_FK, KSLOT);
                    bulk_stream(t, p.qk + (size_t)tile * (TR * D), KBYTES, b + B_FK, pol);
                    bulk_plain(t + T_C, p.kcos + ro, CBYTES, b + B_FK);
                    bulk_plain(t + T_S, p.ksin + ro, CBYTES, b + B_FK);
                    if (++kslot == NK) { kslot = 0; kph ^= 1; }
                    pend[LEAD - 1] = tile;
                    issue_v();
                }
            }
#pragma unroll 1
            for (int i = 1; i < LEAD; i++) issue_v();
        }
    }
}

}

extern "C" void kernel_launch(void* const* d_in, const int* in_sizes, int n_in, void* d_out, int out_size) {
    (void)in_sizes; (void)n_in; (void)out_size;
    static int sms = 0;
    if (sms == 0) {
        int dev = 0;
        cudaGetDevice(&dev);
        cudaDeviceGetAttribute(&sms, cudaDevAttrMultiProcessorCount, dev);
        cudaFuncSetAttribute(kv_rope_decode_kernel, cudaFuncAttributeMaxDynamicSharedMemorySize, SMEM_BYTES);
    }
    Params p;
    p.q    = (const __nv_bfloat16*)d_in[0];
    p.qk   = (const int*)d_in[1];
    p.ks   = (const __nv_bfloat16*)d_in[2];
    p.kz   = (const __nv_bfloat16*)d_in[3];
    p.qv   = (const int*)d_in[4];
    p.vs   = (const __nv_bfloat16*)d_in[5];
    p.vz   = (const __nv_bfloat16*)d_in[6];
    p.qcos = (const __nv_bfloat16*)d_in[7];
    p.qsin = (const __nv_bfloat16*)d_in[8];
    p.kcos = (const __nv_bfloat16*)d_in[9];
    p.ksin = (const __nv_bfloat16*)d_in[10];
    p.out  = (__nv_bfloat16*)d_out;
    kv_rope_decode_kernel<<<sms, NTHREADS, SMEM_BYTES>>>(p);
}
```

```cpp
#include <cuda_runtime.h>
#include <cuda_bf16.h>
#include <stdint.h>

namespace {

constexpr int D      = 192;
constexpr int SKV    = 2048;
constexpr int NHEAD  = 256;
constexpr int TR     = 8;
constexpr int TPH    = SKV / TR;
constexpr int NKW    = 4;
constexpr int NVW    = 6;
constexpr int NB     = 6 / NVW;
constexpr int NGW    = 2;
constexpr int NK     = 8;
constexpr int NV     = 4;
constexpr int LEAD   = 5;
constexpr int NSEG   = 8;
constexpr int SEGT   = 16;
constexpr int NBAT   = 16;
constexpr int W_V = NKW, W_PROD = W_V + NVW, W_S = W_PROD + 1, W_G = W_S + 1, W_SCH = W_G + NGW, NWARPS = W_SCH + 1;
constexpr int NTHREADS = 32 + NWARPS * 32;

constexpr int MAINP  = 16;
constexpr int PF0    = 3;
constexpr int GSH    = 2;
__host__ __device__ constexpr int semi_size(uint32_t h) { return (0x88ccu >> (h / 64 * 4)) & 15; }
__host__ __device__ constexpr int fin_size(uint32_t h) { return (0x248cu >> (h / 64 * 4)) & 15; }
constexpr int NM     = TPH / MAINP;
constexpr int C_S    = NHEAD * NM, C_F = C_S + NHEAD, NCLAIM = C_F + NHEAD;

constexpr int KBYTES = TR * D * 4;
constexpr int CBYTES = TR * D * 2;
constexpr int QBYTES = D * 2;
constexpr int T_C = KBYTES, T_S = T_C + CBYTES, KSLOT = T_S + CBYTES;
constexpr int SCB = SEGT * TR * 2 << GSH;
static_assert(MAINP <= SEGT && semi_size(0) <= SEGT && fin_size(0) <= SEGT && GSH >= 1, "a piece fills one segment slot");
constexpr int S_Q    = 0;
constexpr int S_SC   = S_Q + QBYTES;
constexpr int S_DESC = S_SC + 4 * SCB;
constexpr int S_BD   = S_DESC + 16;
constexpr int S_LG   = S_BD + SEGT * 8;
constexpr int S_PV   = S_LG + SEGT * TR * 16;
constexpr int S_G    = S_PV + SEGT * TR * 4;
constexpr int S_CF   = S_G + (D + 4) * 4;
constexpr int SEG_BYTES = (S_CF + 16 + 127) / 128 * 128;
constexpr int OFF_V = NK * KSLOT, OFF_SEG = OFF_V + NV * KBYTES, OFF_QT = OFF_SEG + NSEG * SEG_BYTES,
              OFF_TAG = OFF_QT + 2 * QBYTES, OFF_BAR = OFF_TAG + 16;
constexpr int B_FK = 0, B_DS = 64, B_PR = 128, B_HDR = 256, B_GD = 320, B_FC = 384, B_FV = 448, B_GO = 504,
              B_LG = 512, B_SE = 640, B_EV = 768, B_EK = 896;
constexpr int SMEM_BYTES = OFF_BAR + 1024;
static_assert(NK <= 8 && NV <= 7 && W_PROD >= 8 && NSEG == 8 && NBAT == 16, "barrier layout");
static_assert(SMEM_BYTES <= 232448 && SMEM_BYTES > 232448 / 2, "one CTA per SM");
static_assert(NSEG % NGW == 0 && NK % (NKW / 2) == 0 && NB * NVW == 6 && LEAD >= 1, "cfg");
static_assert(LEAD + NV >= 4 && LEAD + NV < NBAT && LEAD < NSEG, "no ring can be lapped or starved");

__device__ unsigned int g_queue;
constexpr int REC = 200, GB = 4;
__device__ unsigned int g_epoch;
__device__ __align__(32) uint32_t g_mail[NHEAD * NM * REC];

__device__ __forceinline__ uint32_t smem_u32(const void* p) { return (uint32_t)__cvta_generic_to_shared(p); }
__device__ __forceinline__ uint32_t pin(uint32_t x) {
    return __shfl_sync(0xffffffffu, x, threadIdx.x & 31);
}
template <class T> __device__ __forceinline__ T* pin(T* p) {
    return (T*)__shfl_sync(0xffffffffu, (unsigned long long)p, threadIdx.x & 31);
}
__device__ __forceinline__ bool elect_one() {
    uint32_t pred;
    asm volatile("{\n.reg .pred p;\nelect.sync _|p, 0xffffffff;\nselp.u32 %0, 1, 0, p;\n}" : "=r"(pred));
    return pred;
}
__device__ __forceinline__ void mbar_init(uint32_t bar, uint32_t cnt) {
    asm volatile("mbarrier.init.shared::cta.b64 [%0], %1;" ::"r"(bar), "r"(cnt) : "memory");
}
__device__ __forceinline__ void mbar_expect(uint32_t bar, uint32_t bytes) {
    asm volatile("mbarrier.arrive.expect_tx.shared::cta.b64 _, [%0], %1;" ::"r"(bar), "r"(bytes) : "memory");
}
__device__ __forceinline__ void mbar_arrive(uint32_t bar) {
    asm volatile("mbarrier.arrive.shared::cta.b64 _, [%0];" ::"r"(bar) : "memory");
}
__device__ __forceinline__ void mbar_arrive(uint32_t bar, uint32_t cnt) {
    asm volatile("mbarrier.arrive.shared::cta.b64 _, [%0], %1;" ::"r"(bar), "r"(cnt) : "memory");
}
__device__ __forceinline__ bool mbar_test(uint32_t bar, uint32_t parity) {
    uint32_t ok;
    asm volatile("{\n.reg .pred p;\nmbarrier.test_wait.parity.shared::cta.b64 p, [%1], %2;\nselp.u32 %0, 1, 0, p;\n}"
                 : "=r"(ok) : "r"(bar), "r"(parity) : "memory");
    return ok;
}
__device__ __forceinline__ void mbar_wait(uint32_t bar, uint32_t parity) {
    asm volatile("{\n.reg .pred p;\n.reg .u32 n;\n"
                 "mbarrier.try_wait.parity.shared::cta.b64 p, [%0], %1;\n"
                 "@p bra DONE;\n"
                 "mov.u32 n, 0;\n"
                 "LOOP:\n"
                 "mbarrier.try_wait.parity.shared::cta.b64 p, [%0], %1;\n"
                 "@p bra DONE;\n"
                 "add.u32 n, n, 1;\n"
                 "setp.lt.u32 p, n, 0x400000;\n"
                 "@p bra LOOP;\n"
                 "trap;\n"
                 "DONE:\n}" ::"r"(bar), "r"(parity) : "memory");
}
__device__ __forceinline__ void bulk_stream(uint32_t dst, const void* src, uint32_t bytes, uint32_t bar, uint64_t pol) {
    asm volatile("cp.async.bulk.shared::cluster.global.mbarrier::complete_tx::bytes.L2::cache_hint [%0], [%1], %2, [%3], %4;"
                 ::"r"(dst), "l"(src), "r"(bytes), "r"(bar), "l"(pol) : "memory");
}
__device__ __forceinline__ void bulk_plain(uint32_t dst, const void* src, uint32_t bytes, uint32_t bar) {
    asm volatile("cp.async.bulk.shared::cluster.global.mbarrier::complete_tx::bytes [%0], [%1], %2, [%3];"
                 ::"r"(dst), "l"(src), "r"(bytes), "r"(bar) : "memory");
}
__device__ __forceinline__ void l2_prefetch(const void* src, uint32_t bytes, uint64_t pol) {
    asm volatile("cp.async.bulk.prefetch.L2.global.L2::cache_hint [%0], %1, %2;" ::"l"(src), "r"(bytes), "l"(pol) : "memory");
}
__device__ __forceinline__ void l2_prefetch(const void* src, uint32_t bytes) {
    asm volatile("cp.async.bulk.prefetch.L2.global [%0], %1;" ::"l"(src), "r"(bytes) : "memory");
}
__device__ __forceinline__ int4 lds128(uint32_t a) {
    int4 v;
    asm volatile("ld.shared.v4.s32 {%0,%1,%2,%3}, [%4];" : "=r"(v.x), "=r"(v.y), "=r"(v.z), "=r"(v.w) : "r"(a));
    return v;
}
__device__ __forceinline__ uint2 lds64(uint32_t a) {
    uint2 v;
    asm volatile("ld.shared.v2.u32 {%0,%1}, [%2];" : "=r"(v.x), "=r"(v.y) : "r"(a));
    return v;
}
__device__ __forceinline__ uint32_t lds32(uint32_t a) {
    uint32_t v;
    asm volatile("ld.shared.u32 %0, [%1];" : "=r"(v) : "r"(a));
    return v;
}
__device__ __forceinline__ uint32_t lds16(uint32_t a) {
    uint16_t v;
    asm volatile("ld.shared.u16 %0, [%1];" : "=h"(v) : "r"(a));
    return v;
}
__device__ __forceinline__ void sts32(uint32_t a, float x) {
    asm volatile("st.shared.f32 [%0], %1;" ::"r"(a), "f"(x) : "memory");
}
__device__ __forceinline__ void sts128(uint32_t a, uint32_t x, uint32_t y, uint32_t z, uint32_t w) {
    asm volatile("st.shared.v4.u32 [%0], {%1,%2,%3,%4};" ::"r"(a), "r"(x), "r"(y), "r"(z), "r"(w) : "memory");
}
__device__ __forceinline__ void sts64(uint32_t a, float x, float y) {
    asm volatile("st.shared.v2.f32 [%0], {%1,%2};" ::"r"(a), "f"(x), "f"(y) : "memory");
}
__device__ __forceinline__ float bf_lo(uint32_t v) { return __uint_as_float(v << 16); }
__device__ __forceinline__ float rbf(float x) {
    uint32_t d; asm("cvt.rn.bf16x2.f32 %0, %1, %2;" : "=r"(d) : "f"(x), "f"(0.f)); return __uint_as_float(d);
}
__device__ __forceinline__ float rcp(float x) {
    float y;
    asm("rcp.approx.ftz.f32 %0, %1;" : "=f"(y) : "f"(x));
    return y;
}
__device__ __forceinline__ float lg2(float x) {
    float y;
    asm("lg2.approx.ftz.f32 %0, %1;" : "=f"(y) : "f"(x));
    return y;
}
__device__ __forceinline__ float ex2(float x) {
    float y;
    asm("ex2.approx.ftz.f32 %0, %1;" : "=f"(y) : "f"(x));
    return y;
}
__device__ __forceinline__ uint32_t bmul(uint32_t a, uint32_t b) {
    uint32_t d; asm("mul.rn.bf16x2 %0, %1, %2;" : "=r"(d) : "r"(a), "r"(b)); return d;
}
__device__ __forceinline__ uint32_t bsub(uint32_t a, uint32_t b) {
    uint32_t d; asm("sub.rn.bf16x2 %0, %1, %2;" : "=r"(d) : "r"(a), "r"(b)); return d;
}
__device__ __forceinline__ uint32_t bfma(uint32_t a, uint32_t b, uint32_t c) {
    uint32_t d; asm("fma.rn.bf16x2 %0, %1, %2, %3;" : "=r"(d) : "r"(a), "r"(b), "r"(c)); return d;
}
__device__ __forceinline__ uint32_t i2bf2(int lo, int hi) {
    uint32_t d; asm("cvt.rn.bf16x2.f32 %0, %1, %2;" : "=r"(d) : "f"((float)hi), "f"((float)lo)); return d;
}
__device__ __forceinline__ uint32_t rope2(uint32_t x, uint32_t c, uint32_t y, uint32_t s, uint32_t sg) {
    return bfma(bmul(y, s), sg, bmul(x, c));
}
__device__ __forceinline__ void mma_bf16(float (&c)[4], uint32_t a0, uint32_t a1, uint32_t a2, uint32_t a3,
                                         uint32_t b0, uint32_t b1) {
    asm("mma.sync.aligned.m16n8k16.row.col.f32.bf16.bf16.f32 {%0,%1,%2,%3}, {%4,%5,%6,%7}, {%8,%9}, {%0,%1,%2,%3};"
        : "+f"(c[0]), "+f"(c[1]), "+f"(c[2]), "+f"(c[3])
        : "r"(a0), "r"(a1), "r"(a2), "r"(a3), "r"(b0), "r"(b1));
}
__device__ __forceinline__ void mail_put(uint32_t* p, float x, uint32_t tag) {
    asm volatile("st.relaxed.gpu.global.u32 [%0], %1;" ::"l"(p), "r"((__float_as_uint(x) & ~3u) | tag) : "memory");
}

struct Claim { uint32_t head, tile0, piece, sh, off; int ntiles; };

__device__ __forceinline__ Claim decode_claim(uint32_t c) {
    Claim cl;
    cl.sh = cl.off = 0;
    if (c < C_S) {
        cl.head = c / NM; cl.piece = c % NM; cl.sh = GSH; cl.off = c % (1 << GSH); cl.tile0 = (c - cl.off) * MAINP;
        cl.ntiles = MAINP;
        if (cl.piece >= NM - (1 << GSH))
            cl.ntiles -= (semi_size(cl.head) + fin_size(cl.head) + cl.off) >> GSH;
    } else {
        cl.head = (c - C_S) % NHEAD; cl.piece = 0;
        cl.ntiles = fin_size(cl.head); cl.tile0 = (cl.head + 1) * TPH - cl.ntiles;
        if (c < C_F) { cl.ntiles = semi_size(cl.head); cl.tile0 -= cl.ntiles; }
    }
    return cl;
}

struct Params {
    const int* qk; const __nv_bfloat16* kcos; const __nv_bfloat16* ksin; const int* qv;
    const __nv_bfloat16* ks; const __nv_bfloat16* kz; const __nv_bfloat16* vs; const __nv_bfloat16* vz;
    const __nv_bfloat16* q; const __nv_bfloat16* qcos; const __nv_bfloat16* qsin;
    __nv_bfloat16* out;
};

constexpr float NEG = -3.0e38f;
constexpr float LOG2E = 1.4426950408889634f;
constexpr int F_NT = 31, F_LAST = 64, F_SEMI = 128, F_FIN = 256, F_END = 512;
static_assert(NHEAD * NM * REC < (1 << 20), "batch descriptor");

__global__ void __launch_bounds__(NTHREADS, 1)
kv_rope_decode_kernel(const Params p) {
    extern __shared__ __align__(128) unsigned char smem[];
    if (threadIdx.x < 32 && elect_one()) {
        l2_prefetch(p.kcos + (blockIdx.x % (TPH / 2)) * (2 * TR * D), 2 * CBYTES);
        l2_prefetch(p.ksin + (blockIdx.x % (TPH / 2)) * (2 * TR * D), 2 * CBYTES);
        uint64_t pol;
        asm volatile("createpolicy.fractional.L2::evict_first.b64 %0, 1.0;" : "=l"(pol));
        const uint32_t off = blockIdx.x % (1 << GSH);
        l2_prefetch(p.qk + (size_t)((blockIdx.x - off) * MAINP + off * PF0) * (TR * D), PF0 * KBYTES, pol);
    }
    const int w = __shfl_sync(0xffffffffu, (threadIdx.x >> 5) - 1, 0), lane = threadIdx.x & 31;
    if (w < 0) return;
    const uint32_t sb = __shfl_sync(0xffffffffu, smem_u32(smem), 0);
    const uint32_t bar = sb + OFF_BAR;

    if (w < 8 && elect_one()) {
        const uint32_t cnt = w == 4 ? 8 : w == 5 ? NKW + NVW : w == 6 ? NVW : w == 7 ? 2 : 1;
#pragma unroll
        for (int i = 0; i < 16; i++) mbar_init(bar + w * 128 + i * 8, cnt);
        asm volatile("fence.mbarrier_init.release.cluster;" ::: "memory");
    }
    asm volatile("bar.sync 0, %0;" ::"n"(NWARPS * 32) : "memory");

    if ((unsigned)(w - W_V) < NVW) {
        const int v = w - W_V, g = lane >> 3, l = lane & 7;
        const bool up = lane & 16, up2 = lane & 8;
        const uint32_t oV = pin(sb + OFF_V + g * (2 * D * 4) + v * (NB * 128) + l * 16), oP = pin(S_PV + g * 8);
        const uint32_t col = pin(v * (NB * 32) + l * 4 + (up ? 2 : 0) + (up2 ? 1 : 0));
        __nv_bfloat16* const outp = pin(p.out + col);
        uint32_t* const mailp = pin(g_mail + col);
        float acc[4 * NB];
#pragma unroll
        for (int i = 0; i < 4 * NB; i++) acc[i] = 0.f;
        uint32_t vslot = 0, seg = 0, vph = 0;
        uint32_t s = sb + OFF_SEG, t0 = 0;
        mbar_wait(bar + B_PR, 0);
        uint2 bd = lds64(s + S_BD);
        uint2 pv = lds64(s + oP);
        bool ready = false;
        int4 x0[NB], x1[NB];
        auto load_tile = [&]() {
            const uint32_t t = oV + vslot * KBYTES;
            if (!ready) mbar_wait(bar + B_FV + vslot * 8, vph);
#pragma unroll
            for (int j = 0; j < NB; j++) {
                x0[j] = lds128(t + j * 128);
                x1[j] = lds128(t + 768 + j * 128);
            }
            __syncwarp();
            if (lane == 0) mbar_arrive(bar + B_EV + vslot * 8);
            if (++vslot == NV) { vslot = 0; vph ^= 1; }
            ready = mbar_test(bar + B_FV + vslot * 8, vph);
        };
        auto fma_tile = [&]() {
            const float pv0 = __uint_as_float(pv.x), pv1 = __uint_as_float(pv.y);
#pragma unroll
            for (int j = 0; j < NB; j++) {
                acc[j * 4 + 0] = fmaf(pv1, (float)x1[j].x, fmaf(pv0, (float)x0[j].x, acc[j * 4 + 0]));
                acc[j * 4 + 1] = fmaf(pv1, (float)x1[j].y, fmaf(pv0, (float)x0[j].y, acc[j * 4 + 1]));
                acc[j * 4 + 2] = fmaf(pv1, (float)x1[j].z, fmaf(pv0, (float)x0[j].z, acc[j * 4 + 2]));
                acc[j * 4 + 3] = fmaf(pv1, (float)x1[j].w, fmaf(pv0, (float)x0[j].w, acc[j * 4 + 3]));
            }
        };
        for (uint32_t batch = 1; !(bd.y & F_END); batch++) {
            const uint32_t n = bd.y & F_NT, sbar = bar + (seg % NSEG) * 8;
            const bool last = bd.y & F_LAST;
            const uint32_t seg2 = seg + last, t2 = last ? 0 : t0 + n;
            const uint32_t s2 = sb + OFF_SEG + (seg2 % NSEG) * SEG_BYTES;
#pragma unroll
            for (int i = 0; i < 4 * NB; i++) acc[i] *= __uint_as_float(bd.x);
#pragma unroll 1
            for (uint32_t i = 1; i < n; i++) {
                load_tile();
                const uint2 pn = lds64(s + oP + (t0 + i) * (TR * 4));
                fma_tile();
                pv = pn;
            }
            load_tile();
            const bool early = mbar_test(sbar + B_FC, (seg / NSEG) & 1);
            const bool next = mbar_test(bar + B_PR + (batch % NBAT) * 8, (batch / NBAT) & 1);
            fma_tile();
            int4 cf;
            uint32_t gv[NB];
            uint2 bn, pn;
            if (early) {
                cf = lds128(s + S_CF);
#pragma unroll
                for (int j = 0; j < NB; j++) gv[j] = lds32(s + S_G + (col + j * 32) * 4);
            }
            if (last) {
                float o[NB];
#pragma unroll
                for (int j = 0; j < NB; j++) {
                    const float u0 = (up ? acc[j * 4 + 2] : acc[j * 4 + 0]) + __shfl_xor_sync(0xffffffffu, up ? acc[j * 4 + 0] : acc[j * 4 + 2], 16);
                    const float u1 = (up ? acc[j * 4 + 3] : acc[j * 4 + 1]) + __shfl_xor_sync(0xffffffffu, up ? acc[j * 4 + 1] : acc[j * 4 + 3], 16);
                    o[j] = (up2 ? u1 : u0) + __shfl_xor_sync(0xffffffffu, up2 ? u0 : u1, 8);
                }
                if (!early) {
                    mbar_wait(sbar + B_FC, (seg / NSEG) & 1);
                    cf = lds128(s + S_CF);
#pragma unroll
                    for (int j = 0; j < NB; j++) gv[j] = lds32(s + S_G + (col + j * 32) * 4);
                }
#pragma unroll
                for (int j = 0; j < NB; j++) {
                    const float gj = (bd.y & (F_SEMI | F_FIN)) ? __uint_as_float(gv[j]) : 0.f;
                    o[j] = fmaf(o[j], __int_as_float(cf.x), fmaf(gj, __int_as_float(cf.y), __int_as_float(cf.z)));
                }
                if (bd.y & F_FIN) {
#pragma unroll
                    for (int j = 0; j < NB; j++) {
                        const __nv_bfloat16 r = __float2bfloat16_rn(o[j]);
                        asm volatile("st.global.b16 [%0], %1;" ::"l"(outp + (bd.y >> 12) + j * 32), "h"(*(const uint16_t*)&r) : "memory");
                    }
                } else {
#pragma unroll
                    for (int j = 0; j < NB; j++) mail_put(mailp + (bd.y >> 12) + j * 32, o[j], cf.w & 3);
                    if (col < REC - D) mail_put(mailp + (bd.y >> 12) + D, __int_as_float(cf.w), cf.w & 3);
                }
#pragma unroll
                for (int i = 0; i < 4 * NB; i++) acc[i] = 0.f;
            }
            if (next) {
                bn = lds64(s2 + S_BD + t2 * 8);
                pn = lds64(s2 + oP + t2 * (TR * 4));
            }
            if (last) {
                __syncwarp();
                if (lane == 0) mbar_arrive(sbar + B_SE);
            }
            if (!next) {
                mbar_wait(bar + B_PR + (batch % NBAT) * 8, (batch / NBAT) & 1);
                bn = lds64(s2 + S_BD + t2 * 8);
                pn = lds64(s2 + oP + t2 * (TR * 4));
            }
            bd = bn; pv = pn; s = s2; t0 = t2; seg = seg2;
        }
    } else if (w == W_S) {
        uint32_t batch = 0;
        for (uint32_t seg = 0;; seg++) {
            const uint32_t s = sb + OFF_SEG + (seg % NSEG) * SEG_BYTES, sbar = bar + (seg % NSEG) * 8;
            const uint32_t sph = (seg / NSEG) & 1;
            mbar_wait(sbar + B_HDR, sph);
            const int4 desc = lds128(s + S_DESC);
            if (desc.y & F_END) {
                if (lane == 0) {
                    sts64(s + S_BD, 0.f, __uint_as_float(F_END));
                    mbar_arrive(bar + B_PR + (batch % NBAT) * 8);
                }
                break;
            }
            float m = NEG, L = 0.f, C = 0.f;
            const uint32_t head = (uint32_t)desc.x / TPH, index = (desc.y & F_FIN) ? head * D : (head * NM + desc.z) * REC;
            const int nt = desc.y & F_NT;
#pragma unroll 1
            for (int t0 = 0; t0 < nt; t0 += 4, batch++) {
                const int n = min(4, nt - t0);
                const bool valid = lane < n * TR;
                const uint32_t tl = t0 + (valid ? lane >> 3 : 0), row = tl * TR + (lane & 7);
                const uint32_t sc = s + S_SC + (((tl << (desc.w & 255)) + (desc.w >> 8)) * TR + (lane & 7)) * 2;
                const float vs = bf_lo(lds16(sc + 2 * SCB)), vz = bf_lo(lds16(sc + 3 * SCB));
                mbar_wait(bar + B_LG + (batch % NBAT) * 8, (batch / NBAT) & 1);
                const int4 part = lds128(s + S_LG + row * 16);
                const float dot = (__int_as_float(part.x) + __int_as_float(part.y)) + (__int_as_float(part.z) + __int_as_float(part.w));
                const float sv = rbf(rbf(dot) * 0.07216878364870322f) * LOG2E;
                int key = __float_as_int(fmaxf(m, sv));
                key ^= (key >> 31) & 0x7fffffff;
                key = __reduce_max_sync(0xffffffffu, key);
                const float mn = __int_as_float(key ^ ((key >> 31) & 0x7fffffff));
                const float alpha = ex2(m - mn), pr = ex2(sv - mn), pv = pr * vs;
                m = mn;
                sts32(s + S_PV + row * 4, pv);
                if (lane == 0)
                    sts64(s + S_BD + t0 * 8, alpha,
                          __uint_as_float(n | (t0 + n < nt ? 0 : index << 12 | F_LAST | (desc.y & (F_SEMI | F_FIN)))));
                __syncwarp();
                if (lane == 0) mbar_arrive(bar + B_PR + (batch % NBAT) * 8);
                L = fmaf(L, alpha, valid ? pr : 0.f);
                C = fmaf(C, alpha, valid ? pv * vz : 0.f);
            }
#pragma unroll
            for (int o = 16; o > 0; o >>= 1) {
                L += __shfl_xor_sync(0xffffffffu, L, o);
                C += __shfl_xor_sync(0xffffffffu, C, o);
            }
            mbar_wait(sbar + B_GD, sph);
            const uint32_t tag = lds32(sb + OFF_TAG) | ((desc.y & F_SEMI) ? 2 : 0);
            const float gl = (desc.y & (F_SEMI | F_FIN)) ? __uint_as_float(lds32(s + S_G + D * 4)) : -3.4e38f;
            const float M = fmaxf(m, gl), e = ex2(m - M), a = ex2(gl - M);
            const float W = fmaf(L, e, a), inv = rcp(W);
            if (lane == 0)
                sts128(s + S_CF, __float_as_uint(e * inv), __float_as_uint(a * inv), __float_as_uint(-C * e * inv),
                       (__float_as_uint(M + lg2(W)) & ~3u) | tag);
            __syncwarp();
            if (lane == 0) mbar_arrive(sbar + B_FC);
        }
    } else if ((unsigned)(w - W_G) < NGW) {
        if (w == W_G) {
            if (lane == 0) sts32(sb + OFF_TAG, __uint_as_float(~*(volatile unsigned int*)&g_epoch & 1));
        } else {
            mbar_wait(bar + B_GD, 0);
        }
        for (uint32_t seg = w - W_G;; seg += NGW) {
            const uint32_t s = sb + OFF_SEG + (seg % NSEG) * SEG_BYTES, sbar = bar + (seg % NSEG) * 8;
            mbar_wait(sbar + B_HDR, (seg / NSEG) & 1);
            const int4 desc = lds128(s + S_DESC);
            if (desc.y & F_END) break;
            if (desc.y & (F_SEMI | F_FIN)) {
                const uint32_t tag = lds32(sb + OFF_TAG) | ((desc.y & F_FIN) ? 2 : 0);
                const int cnt = (desc.y & F_FIN) ? 1 : NM;
                const uint32_t* mail = g_mail + (uint32_t)desc.x / TPH * (NM * REC);
                float M = NEG, W = 0.f, O[6] = {0.f, 0.f, 0.f, 0.f, 0.f, 0.f};
#pragma unroll 1
                for (int i0 = 0; i0 < cnt; i0 += GB, mail += GB * REC) {
                    uint2 pk[3 * GB];
                    uint32_t ls[GB], stale;
                    int it = 0;
                    do {
                        stale = 0;
#pragma unroll
                        for (int i = 0; i < GB; i++) {
                            ls[i] = 0xff7ffffcu | tag;
                            pk[3 * i] = pk[3 * i + 1] = pk[3 * i + 2] = make_uint2(tag, tag);
                            if (i0 + i < cnt) {
                                asm volatile("ld.relaxed.gpu.global.u32 %0, [%1];" : "=r"(ls[i]) : "l"(mail + i * REC + D) : "memory");
#pragma unroll
                                for (int k = 0; k < 3; k++)
                                    asm volatile("ld.relaxed.gpu.global.v2.u32 {%0,%1}, [%2];"
                                                 : "=r"(pk[3 * i + k].x), "=r"(pk[3 * i + k].y)
                                                 : "l"(mail + i * REC + k * 64 + lane * 2) : "memory");
                            }
                        }
#pragma unroll
                        for (int i = 0; i < GB; i++) stale |= ls[i] ^= tag;
#pragma unroll
                        for (int i = 0; i < 3 * GB; i++) stale |= (pk[i].x ^= tag) | (pk[i].y ^= tag);
                        if (++it > (1 << 22)) __trap();
                    } while (stale & 3);
                    float Mn = M;
#pragma unroll
                    for (int i = 0; i < GB; i++) Mn = fmaxf(Mn, __uint_as_float(ls[i]));
                    const float a = ex2(M - Mn);
                    M = Mn; W *= a;
#pragma unroll
                    for (int i = 0; i < 6; i++) O[i] *= a;
#pragma unroll
                    for (int i = 0; i < GB; i++) {
                        const float e = ex2(__uint_as_float(ls[i]) - M);
                        W += e;
#pragma unroll
                        for (int k = 0; k < 3; k++) {
                            O[2 * k] = fmaf(e, __uint_as_float(pk[3 * i + k].x), O[2 * k]);
                            O[2 * k + 1] = fmaf(e, __uint_as_float(pk[3 * i + k].y), O[2 * k + 1]);
                        }
                    }
                }
                const float inv = rcp(W);
#pragma unroll
                for (int k = 0; k < 3; k++) sts64(s + S_G + k * 256 + lane * 8, O[2 * k] * inv, O[2 * k + 1] * inv);
                if (lane == 0) sts32(s + S_G + D * 4, M + lg2(W));
            }
            __syncwarp();
            if (lane == 0) mbar_arrive(sbar + B_GD);
        }
    } else if (w / NKW == 0) {
        const int g = lane >> 3, l = lane & 7, godd = g & 1, row = 2 * g + (w & 1);
        const uint32_t sgA = pin(godd ? 0x3f803f80u : 0xbf80bf80u), sgB = pin(godd ? 0xbf80bf80u : 0x3f803f80u);
        const uint32_t oKA = pin(sb + row * (D * 4) + l * 16 + godd * 384), oKB = pin(oKA - godd * 768 + 384);
        const uint32_t oCA = pin(sb + T_C + row * (D * 2) + l * 8 + godd * 192), oCB = pin(oCA - godd * 384 + 192);
        const uint32_t oL = pin(S_LG + row * 16 + (l >> 2) * 8 + (l & 1) * 4), oS = pin(S_SC + row * 2);
        const bool own = (l & 3) == g, hi = l & 4, keep = ((l ^ g) & 2) == 0;
        uint32_t kslot = w >> 1, j = kslot, batch0 = 0, kph = 0;
        for (uint32_t seg = 0;; seg++) {
            const uint32_t s = sb + OFF_SEG + (seg % NSEG) * SEG_BYTES, sbar = bar + (seg % NSEG) * 8;
            mbar_wait(sbar + B_HDR, (seg / NSEG) & 1);
            const int4 desc = lds128(s + S_DESC);
            if (desc.y & F_END) break;
            const uint32_t nt = desc.y & F_NT;
            uint2 qr[3];
#pragma unroll
            for (int i = 0; i < 3; i++) {
                const uint32_t oa = l * 8 + godd * 192 + i * 64, ob = oa + 192 - godd * 384;
                const uint2 a = lds64(s + S_Q + oa), b = lds64(s + S_Q + ob);
                const uint2 ca = lds64(sb + OFF_QT + oa), sa = lds64(sb + OFF_QT + QBYTES + oa);
                qr[i].x = rope2(a.x, ca.x, b.x, sa.x, sgA);
                qr[i].y = rope2(a.y, ca.y, b.y, sa.y, sgA);
            }
            for (; j < nt; j += NKW / 2) {
                const uint32_t t = kslot * KSLOT;
                const uint32_t sc = s + oS + ((j << (desc.w & 255)) + (desc.w >> 8)) * (TR * 2);
                const uint32_t ks2 = lds16(sc) * 0x10001u, kz2 = lds16(sc + SCB) * 0x10001u;
                const uint32_t lgb = bar + B_LG + ((batch0 + (j >> 2)) % NBAT) * 8;
                const uint32_t lgc = j == nt - 1 ? 4 - (j & 3) : 1;
                mbar_wait(bar + B_FK + kslot * 8, kph);
                float c[4] = {0.f, 0.f, 0.f, 0.f};
#pragma unroll
                for (int jj = 0; jj < 3; jj++) {
                    const int4 xa = lds128(t + oKA + jj * 128), xb = lds128(t + oKB + jj * 128);
                    const uint2 ca = lds64(t + oCA + jj * 64), cb = lds64(t + oCB + jj * 64);
                    const uint2 sa = lds64(t + oCA + CBYTES + jj * 64), sbv = lds64(t + oCB + CBYTES + jj * 64);
                    const uint32_t a0 = bmul(bsub(i2bf2(xa.x, xa.y), kz2), ks2);
                    const uint32_t a1 = bmul(bsub(i2bf2(xa.z, xa.w), kz2), ks2);
                    const uint32_t b0 = bmul(bsub(i2bf2(xb.x, xb.y), kz2), ks2);
                    const uint32_t b1 = bmul(bsub(i2bf2(xb.z, xb.w), kz2), ks2);
                    mma_bf16(c, rope2(a0, ca.x, b0, sa.x, sgA), rope2(b0, cb.x, a0, sbv.x, sgB),
                             rope2(a1, ca.y, b1, sa.y, sgA), rope2(b1, cb.y, a1, sbv.y, sgB), qr[jj].x, qr[jj].y);
                }
                __syncwarp();
                if (lane == 0) mbar_arrive(bar + B_EK + kslot * 8);
                const float part = own ? (hi ? c[1] : c[0]) : (hi ? c[3] : c[2]);
                if (keep) sts32(s + oL + j * (TR * 16), part);
                __syncwarp();
                if (lane == 0) mbar_arrive(lgb, lgc);
                kslot += NKW / 2;
                if (kslot >= NK) { kslot -= NK; kph ^= 1; }
            }
            j -= nt;
            batch0 += (nt + 3) >> 2;
            __syncwarp();
            if (lane == 0) mbar_arrive(sbar + B_SE);
        }
    } else if (w == W_SCH) {
        if (elect_one()) {
            asm volatile("mbarrier.expect_tx.shared::cta.b64 [%0], %1;" ::"r"(bar + B_HDR), "r"(2 * QBYTES) : "memory");
            uint32_t seg = 0, c = blockIdx.x;
            while (c < NCLAIM) {
                const Claim cl = decode_claim(c);
                const uint32_t s = sb + OFF_SEG + (seg % NSEG) * SEG_BYTES, b = bar + (seg % NSEG) * 8;
                mbar_wait(b + B_SE, ((seg / NSEG) & 1) ^ 1);
                sts128(s + S_DESC, cl.tile0 + cl.off, cl.ntiles | (c >= C_F ? F_FIN : c >= C_S ? F_SEMI : 0), cl.piece,
                       cl.sh | cl.off << 8);
                if (seg) mbar_arrive(bar + B_DS + ((seg - 1) % NSEG) * 8);
                const uint32_t scb = cl.ntiles * TR * 2 << cl.sh, r = cl.tile0 * TR;
                mbar_expect(b + B_HDR, 4 * scb + QBYTES);
                bulk_plain(s + S_Q, p.q + cl.head * D, QBYTES, b + B_HDR);
                bulk_plain(s + S_SC, p.ks + r, scb, b + B_HDR);
                bulk_plain(s + S_SC + SCB, p.kz + r, scb, b + B_HDR);
                bulk_plain(s + S_SC + 2 * SCB, p.vs + r, scb, b + B_HDR);
                bulk_plain(s + S_SC + 3 * SCB, p.vz + r, scb, b + B_HDR);
                if (seg == 0) {
                    bulk_plain(sb + OFF_QT, p.qcos, QBYTES, bar + B_HDR);
                    bulk_plain(sb + OFF_QT + QBYTES, p.qsin, QBYTES, bar + B_HDR);
                    mbar_wait(bar + B_GD, 0);
                }
                mbar_wait(bar + B_GO, seg & 1);
                seg++;
                const unsigned nx = atomicInc(&g_queue, NCLAIM - 1);
                if (nx == NCLAIM - 1) g_epoch = lds32(sb + OFF_TAG);
                c = gridDim.x + nx;
            }
#pragma unroll 1
            for (int i = 0; i < NGW; i++, seg++) {
                const uint32_t s = sb + OFF_SEG + (seg % NSEG) * SEG_BYTES, b = bar + (seg % NSEG) * 8;
                mbar_wait(b + B_SE, ((seg / NSEG) & 1) ^ 1);
                sts128(s + S_DESC, 0, F_END, 0, 0);
                mbar_arrive(bar + B_DS + ((seg - 1) % NSEG) * 8);
                mbar_arrive(b + B_HDR);
            }
        }
    } else {
        if (elect_one()) {
            uint64_t pol;
            asm volatile("createpolicy.fractional.L2::evict_first.b64 %0, 1.0;" : "=l"(pol));
            uint32_t kslot = 0, vslot = 0, kph = 1, vph = 1;
            int pend[LEAD];
#pragma unroll
            for (int i = 0; i < LEAD; i++) pend[i] = -1;
            auto issue_v = [&]() {
                if (pend[0] >= 0) {
                    const uint32_t b = bar + vslot * 8;
                    mbar_wait(b + B_EV, vph);
                    mbar_expect(b + B_FV, KBYTES);
                    bulk_stream(sb + OFF_V + vslot * KBYTES, p.qv + (size_t)pend[0] * (TR * D), KBYTES, b + B_FV, pol);
                    if (++vslot == NV) { vslot = 0; vph ^= 1; }
                }
#pragma unroll
                for (int i = 0; i + 1 < LEAD; i++) pend[i] = pend[i + 1];
                pend[LEAD - 1] = -1;
            };
            const Claim c0 = decode_claim(blockIdx.x % C_S);
            int4 desc = make_int4(c0.tile0 + c0.off, c0.ntiles, 0, GSH);
            for (uint32_t seg = 0; !(desc.y & F_END); seg++) {
                uint32_t tile = desc.x;
#pragma unroll 1
                for (int left = desc.y & F_NT; left > 0; left--, tile += 1u << (desc.w & 255)) {
                    if (left == 1) mbar_arrive(bar + B_GO);
                    const uint32_t t = sb + kslot * KSLOT, b = bar + kslot * 8;
                    const uint32_t ro = (tile % TPH) * (TR * D);
                    mbar_wait(b + B_EK, kph);
                    mbar_expect(b + B_FK, KSLOT);
                    bulk_stream(t, p.qk + (size_t)tile * (TR * D), KBYTES, b + B_FK, pol);
                    bulk_plain(t + T_C, p.kcos + ro, CBYTES, b + B_FK);
                    bulk_plain(t + T_S, p.ksin + ro, CBYTES, b + B_FK);
                    if (++kslot == NK) { kslot = 0; kph ^= 1; }
                    pend[LEAD - 1] = tile;
                    issue_v();
                }
                mbar_wait(bar + B_DS + (seg % NSEG) * 8, (seg / NSEG) & 1);
                desc = lds128(sb + OFF_SEG + ((seg + 1) % NSEG) * SEG_BYTES + S_DESC);
            }
#pragma unroll 1
            for (int i = 1; i < LEAD; i++) issue_v();
        }
    }
}

}

extern "C" void kernel_launch(void* const* d_in, const int* in_sizes, int n_in, void* d_out, int out_size) {
    (void)in_sizes; (void)n_in; (void)out_size;
    static int sms = 0;
    if (sms == 0) {
        int dev = 0;
        cudaGetDevice(&dev);
        cudaDeviceGetAttribute(&sms, cudaDevAttrMultiProcessorCount, dev);
        cudaFuncSetAttribute(kv_rope_decode_kernel, cudaFuncAttributeMaxDynamicSharedMemorySize, SMEM_BYTES);
    }
    Params p;
    p.q    = (const __nv_bfloat16*)d_in[0];
    p.qk   = (const int*)d_in[1];
    p.ks   = (const __nv_bfloat16*)d_in[2];
    p.kz   = (const __nv_bfloat16*)d_in[3];
    p.qv   = (const int*)d_in[4];
    p.vs   = (const __nv_bfloat16*)d_in[5];
    p.vz   = (const __nv_bfloat16*)d_in[6];
    p.qcos = (const __nv_bfloat16*)d_in[7];
    p.qsin = (const __nv_bfloat16*)d_in[8];
    p.kcos = (const __nv_bfloat16*)d_in[9];
    p.ksin = (const __nv_bfloat16*)d_in[10];
    p.out  = (__nv_bfloat16*)d_out;
    kv_rope_decode_kernel<<<sms, NTHREADS, SMEM_BYTES>>>(p);
}
```

```cpp
#include <cuda_runtime.h>
#include <cuda_bf16.h>
#include <stdint.h>

namespace {

constexpr int D      = 192;
constexpr int SKV    = 2048;
constexpr int NHEAD  = 256;
constexpr int TR     = 8;
constexpr int TPH    = SKV / TR;
constexpr int NKW    = 4;
constexpr int NVW    = 6;
constexpr int NB     = 6 / NVW;
constexpr int NGW    = 2;
constexpr int NK     = 8;
constexpr int NV     = 4;
constexpr int LEAD   = 5;
constexpr int NSEG   = 8;
constexpr int SEGT   = 16;
constexpr int NBAT   = 16;
constexpr int W_V = NKW, W_PROD = W_V + NVW, W_S = W_PROD + 1, W_G = W_S + 1, W_SCH = W_G + NGW, NWARPS = W_SCH + 1;
constexpr int NTHREADS = 32 + NWARPS * 32;

constexpr int MAINP  = 16;
constexpr int PF0    = 3;
constexpr int GSH    = 2;
__host__ __device__ constexpr int semi_size(uint32_t h) { return (0x88ccu >> (h / 64 * 4)) & 15; }
__host__ __device__ constexpr int fin_size(uint32_t h) { return (0x248cu >> (h / 64 * 4)) & 15; }
__host__ __device__ constexpr uint32_t cut_group(uint32_t h) { return (2 - h / 4) % 4; }
constexpr int NM     = TPH / MAINP;
static_assert(NM >> GSH == 4, "four interleave groups per head");
constexpr int C_S    = NHEAD * NM, C_F = C_S + NHEAD, NCLAIM = C_F + NHEAD;

constexpr int KBYTES = TR * D * 4;
constexpr int CBYTES = TR * D * 2;
constexpr int QBYTES = D * 2;
constexpr int T_C = KBYTES, T_S = T_C + CBYTES, KSLOT = T_S + CBYTES;
constexpr int SCB = SEGT * TR * 2 << GSH;
static_assert(MAINP <= SEGT && semi_size(0) <= SEGT && fin_size(0) <= SEGT && GSH >= 1, "a piece fills one segment slot");
constexpr int S_Q    = 0;
constexpr int S_SC   = S_Q + QBYTES;
constexpr int S_DESC = S_SC + 4 * SCB;
constexpr int S_BD   = S_DESC + 16;
constexpr int S_LG   = S_BD + SEGT * 8;
constexpr int S_PV   = S_LG + SEGT * TR * 16;
constexpr int S_G    = S_PV + SEGT * TR * 4;
constexpr int S_CF   = S_G + (D + 4) * 4;
constexpr int SEG_BYTES = (S_CF + 16 + 127) / 128 * 128;
constexpr int OFF_V = NK * KSLOT, OFF_SEG = OFF_V + NV * KBYTES, OFF_QT = OFF_SEG + NSEG * SEG_BYTES,
              OFF_TAG = OFF_QT + 2 * QBYTES, OFF_BAR = OFF_TAG + 16;
constexpr int B_FK = 0, B_DS = 64, B_PR = 128, B_HDR = 256, B_GD = 320, B_FC = 384, B_FV = 448, B_GO = 504,
              B_LG = 512, B_SE = 640, B_EV = 768, B_EK = 896;
constexpr int SMEM_BYTES = OFF_BAR + 1024;
static_assert(NK <= 8 && NV <= 7 && W_PROD >= 8 && NSEG == 8 && NBAT == 16, "barrier layout");
static_assert(SMEM_BYTES <= 232448 && SMEM_BYTES > 232448 / 2, "one CTA per SM");
static_assert(NSEG % NGW == 0 && NK % (NKW / 2) == 0 && NB * NVW == 6 && LEAD >= 1, "cfg");
static_assert(LEAD + NV >= 4 && LEAD + NV < NBAT && LEAD < NSEG, "no ring can be lapped or starved");

__device__ unsigned int g_queue;
constexpr int REC = 200, GB = 4;
__device__ unsigned int g_epoch;
__device__ __align__(32) uint32_t g_mail[NHEAD * NM * REC];

__device__ __forceinline__ uint32_t smem_u32(const void* p) { return (uint32_t)__cvta_generic_to_shared(p); }
__device__ __forceinline__ uint32_t pin(uint32_t x) {
    return __shfl_sync(0xffffffffu, x, threadIdx.x & 31);
}
template <class T> __device__ __forceinline__ T* pin(T* p) {
    return (T*)__shfl_sync(0xffffffffu, (unsigned long long)p, threadIdx.x & 31);
}
__device__ __forceinline__ bool elect_one() {
    uint32_t pred;
    asm volatile("{\n.reg .pred p;\nelect.sync _|p, 0xffffffff;\nselp.u32 %0, 1, 0, p;\n}" : "=r"(pred));
    return pred;
}
__device__ __forceinline__ void mbar_init(uint32_t bar, uint32_t cnt) {
    asm volatile("mbarrier.init.shared::cta.b64 [%0], %1;" ::"r"(bar), "r"(cnt) : "memory");
}
__device__ __forceinline__ void mbar_expect(uint32_t bar, uint32_t bytes) {
    asm volatile("mbarrier.arrive.expect_tx.shared::cta.b64 _, [%0], %1;" ::"r"(bar), "r"(bytes) : "memory");
}
__device__ __forceinline__ void mbar_arrive(uint32_t bar) {
    asm volatile("mbarrier.arrive.shared::cta.b64 _, [%0];" ::"r"(bar) : "memory");
}
__device__ __forceinline__ void mbar_arrive(uint32_t bar, uint32_t cnt) {
    asm volatile("mbarrier.arrive.shared::cta.b64 _, [%0], %1;" ::"r"(bar), "r"(cnt) : "memory");
}
__device__ __forceinline__ bool mbar_test(uint32_t bar, uint32_t parity) {
    uint32_t ok;
    asm volatile("{\n.reg .pred p;\nmbarrier.test_wait.parity.shared::cta.b64 p, [%1], %2;\nselp.u32 %0, 1, 0, p;\n}"
                 : "=r"(ok) : "r"(bar), "r"(parity) : "memory");
    return ok;
}
__device__ __forceinline__ void mbar_wait(uint32_t bar, uint32_t parity) {
    asm volatile("{\n.reg .pred p;\n.reg .u32 n;\n"
                 "mbarrier.try_wait.parity.shared::cta.b64 p, [%0], %1;\n"
                 "@p bra DONE;\n"
                 "mov.u32 n, 0;\n"
                 "LOOP:\n"
                 "mbarrier.try_wait.parity.shared::cta.b64 p, [%0], %1;\n"
                 "@p bra DONE;\n"
                 "add.u32 n, n, 1;\n"
                 "setp.lt.u32 p, n, 0x400000;\n"
                 "@p bra LOOP;\n"
                 "trap;\n"
                 "DONE:\n}" ::"r"(bar), "r"(parity) : "memory");
}
__device__ __forceinline__ void bulk_stream(uint32_t dst, const void* src, uint32_t bytes, uint32_t bar, uint64_t pol) {
    asm volatile("cp.async.bulk.shared::cluster.global.mbarrier::complete_tx::bytes.L2::cache_hint [%0], [%1], %2, [%3], %4;"
                 ::"r"(dst), "l"(src), "r"(bytes), "r"(bar), "l"(pol) : "memory");
}
__device__ __forceinline__ void bulk_plain(uint32_t dst, const void* src, uint32_t bytes, uint32_t bar) {
    asm volatile("cp.async.bulk.shared::cluster.global.mbarrier::complete_tx::bytes [%0], [%1], %2, [%3];"
                 ::"r"(dst), "l"(src), "r"(bytes), "r"(bar) : "memory");
}
__device__ __forceinline__ void l2_prefetch(const void* src, uint32_t bytes, uint64_t pol) {
    asm volatile("cp.async.bulk.prefetch.L2.global.L2::cache_hint [%0], %1, %2;" ::"l"(src), "r"(bytes), "l"(pol) : "memory");
}
__device__ __forceinline__ void l2_prefetch(const void* src, uint32_t bytes) {
    asm volatile("cp.async.bulk.prefetch.L2.global [%0], %1;" ::"l"(src), "r"(bytes) : "memory");
}
__device__ __forceinline__ int4 lds128(uint32_t a) {
    int4 v;
    asm volatile("ld.shared.v4.s32 {%0,%1,%2,%3}, [%4];" : "=r"(v.x), "=r"(v.y), "=r"(v.z), "=r"(v.w) : "r"(a));
    return v;
}
__device__ __forceinline__ uint2 lds64(uint32_t a) {
    uint2 v;
    asm volatile("ld.shared.v2.u32 {%0,%1}, [%2];" : "=r"(v.x), "=r"(v.y) : "r"(a));
    return v;
}
__device__ __forceinline__ uint32_t lds32(uint32_t a) {
    uint32_t v;
    asm volatile("ld.shared.u32 %0, [%1];" : "=r"(v) : "r"(a));
    return v;
}
__device__ __forceinline__ uint32_t lds16(uint32_t a) {
    uint16_t v;
    asm volatile("ld.shared.u16 %0, [%1];" : "=h"(v) : "r"(a));
    return v;
}
__device__ __forceinline__ void sts32(uint32_t a, float x) {
    asm volatile("st.shared.f32 [%0], %1;" ::"r"(a), "f"(x) : "memory");
}
__device__ __forceinline__ void sts128(uint32_t a, uint32_t x, uint32_t y, uint32_t z, uint32_t w) {
    asm volatile("st.shared.v4.u32 [%0], {%1,%2,%3,%4};" ::"r"(a), "r"(x), "r"(y), "r"(z), "r"(w) : "memory");
}
__device__ __forceinline__ void sts64(uint32_t a, float x, float y) {
    asm volatile("st.shared.v2.f32 [%0], {%1,%2};" ::"r"(a), "f"(x), "f"(y) : "memory");
}
__device__ __forceinline__ float bf_lo(uint32_t v) { return __uint_as_float(v << 16); }
__device__ __forceinline__ float rbf(float x) {
    uint32_t d; asm("cvt.rn.bf16x2.f32 %0, %1, %2;" : "=r"(d) : "f"(x), "f"(0.f)); return __uint_as_float(d);
}
__device__ __forceinline__ float rcp(float x) {
    float y;
    asm("rcp.approx.ftz.f32 %0, %1;" : "=f"(y) : "f"(x));
    return y;
}
__device__ __forceinline__ float lg2(float x) {
    float y;
    asm("lg2.approx.ftz.f32 %0, %1;" : "=f"(y) : "f"(x));
    return y;
}
__device__ __forceinline__ float ex2(float x) {
    float y;
    asm("ex2.approx.ftz.f32 %0, %1;" : "=f"(y) : "f"(x));
    return y;
}
__device__ __forceinline__ uint32_t bmul(uint32_t a, uint32_t b) {
    uint32_t d; asm("mul.rn.bf16x2 %0, %1, %2;" : "=r"(d) : "r"(a), "r"(b)); return d;
}
__device__ __forceinline__ uint32_t bsub(uint32_t a, uint32_t b) {
    uint32_t d; asm("sub.rn.bf16x2 %0, %1, %2;" : "=r"(d) : "r"(a), "r"(b)); return d;
}
__device__ __forceinline__ uint32_t bfma(uint32_t a, uint32_t b, uint32_t c) {
    uint32_t d; asm("fma.rn.bf16x2 %0, %1, %2, %3;" : "=r"(d) : "r"(a), "r"(b), "r"(c)); return d;
}
__device__ __forceinline__ uint32_t i2bf2(int lo, int hi) {
    uint32_t d; asm("cvt.rn.bf16x2.f32 %0, %1, %2;" : "=r"(d) : "f"((float)hi), "f"((float)lo)); return d;
}
__device__ __forceinline__ uint32_t rope2(uint32_t x, uint32_t c, uint32_t y, uint32_t s, uint32_t sg) {
    return bfma(bmul(y, s), sg, bmul(x, c));
}
__device__ __forceinline__ void mma_bf16(float (&c)[4], uint32_t a0, uint32_t a1, uint32_t a2, uint32_t a3,
                                         uint32_t b0, uint32_t b1) {
    asm("mma.sync.aligned.m16n8k16.row.col.f32.bf16.bf16.f32 {%0,%1,%2,%3}, {%4,%5,%6,%7}, {%8,%9}, {%0,%1,%2,%3};"
        : "+f"(c[0]), "+f"(c[1]), "+f"(c[2]), "+f"(c[3])
        : "r"(a0), "r"(a1), "r"(a2), "r"(a3), "r"(b0), "r"(b1));
}
__device__ __forceinline__ void mail_put(uint32_t* p, float x, uint32_t tag) {
    asm volatile("st.relaxed.gpu.global.u32 [%0], %1;" ::"l"(p), "r"((__float_as_uint(x) & ~3u) | tag) : "memory");
}

struct Claim { uint32_t head, tile0, piece, sh, off; int ntiles; };

__device__ __forceinline__ Claim decode_claim(uint32_t c) {
    Claim cl;
    cl.sh = cl.off = 0;
    if (c < C_S) {
        cl.head = c / NM; cl.piece = c % NM; cl.sh = GSH; cl.off = c % (1 << GSH); cl.tile0 = (c - cl.off) * MAINP;
        cl.ntiles = MAINP;
        if (cl.piece >> GSH == cut_group(cl.head))
            cl.ntiles -= (semi_size(cl.head) + fin_size(cl.head) + cl.off) >> GSH;
    } else {
        cl.head = (c - C_S) % NHEAD; cl.piece = 0;
        cl.ntiles = fin_size(cl.head); cl.tile0 = cl.head * TPH + (cut_group(cl.head) + 1) * (TPH / 4) - cl.ntiles;
        if (c < C_F) { cl.ntiles = semi_size(cl.head); cl.tile0 -= cl.ntiles; }
    }
    return cl;
}

struct Params {
    const int* qk; const __nv_bfloat16* kcos; const __nv_bfloat16* ksin; const int* qv;
    const __nv_bfloat16* ks; const __nv_bfloat16* kz; const __nv_bfloat16* vs; const __nv_bfloat16* vz;
    const __nv_bfloat16* q; const __nv_bfloat16* qcos; const __nv_bfloat16* qsin;
    __nv_bfloat16* out;
};

constexpr float NEG = -3.0e38f;
constexpr float LOG2E = 1.4426950408889634f;
constexpr int F_NT = 31, F_LAST = 64, F_SEMI = 128, F_FIN = 256, F_END = 512;
static_assert(NHEAD * NM * REC < (1 << 20), "batch descriptor");

__global__ void __launch_bounds__(NTHREADS, 1)
kv_rope_decode_kernel(const Params p) {
    extern __shared__ __align__(128) unsigned char smem[];
    if (threadIdx.x < 32 && elect_one()) {
        l2_prefetch(p.kcos + (blockIdx.x % (TPH / 2)) * (2 * TR * D), 2 * CBYTES);
        l2_prefetch(p.ksin + (blockIdx.x % (TPH / 2)) * (2 * TR * D), 2 * CBYTES);
        uint64_t pol;
        asm volatile("createpolicy.fractional.L2::evict_first.b64 %0, 1.0;" : "=l"(pol));
        const uint32_t off = blockIdx.x % (1 << GSH);
        l2_prefetch(p.qk + (size_t)((blockIdx.x - off) * MAINP + off * PF0) * (TR * D), PF0 * KBYTES, pol);
    }
    const int w = __shfl_sync(0xffffffffu, (threadIdx.x >> 5) - 1, 0), lane = threadIdx.x & 31;
    if (w < 0) return;
    const uint32_t sb = __shfl_sync(0xffffffffu, smem_u32(smem), 0);
    const uint32_t bar = sb + OFF_BAR;

    if (w < 8 && elect_one()) {
        const uint32_t cnt = w == 4 ? 8 : w == 5 ? NKW + NVW : w == 6 ? NVW : w == 7 ? 2 : 1;
#pragma unroll
        for (int i = 0; i < 16; i++) mbar_init(bar + w * 128 + i * 8, cnt);
        asm volatile("fence.mbarrier_init.release.cluster;" ::: "memory");
    }
    asm volatile("bar.sync 0, %0;" ::"n"(NWARPS * 32) : "memory");

    if ((unsigned)(w - W_V) < NVW) {
        const int v = w - W_V, g = lane >> 3, l = lane & 7;
        const bool up = lane & 16, up2 = lane & 8;
        const uint32_t oV = pin(sb + OFF_V + g * (2 * D * 4) + v * (NB * 128) + l * 16), oP = pin(S_PV + g * 8);
        const uint32_t col = pin(v * (NB * 32) + l * 4 + (up ? 2 : 0) + (up2 ? 1 : 0));
        __nv_bfloat16* const outp = pin(p.out + col);
        uint32_t* const mailp = pin(g_mail + col);
        float acc[4 * NB];
#pragma unroll
        for (int i = 0; i < 4 * NB; i++) acc[i] = 0.f;
        uint32_t vslot = 0, seg = 0, vph = 0;
        uint32_t s = sb + OFF_SEG, t0 = 0;
        mbar_wait(bar + B_PR, 0);
        uint2 bd = lds64(s + S_BD);
        uint2 pv = lds64(s + oP);
        bool ready = false;
        int4 x0[NB], x1[NB];
        auto load_tile = [&]() {
            const uint32_t t = oV + vslot * KBYTES;
            if (!ready) mbar_wait(bar + B_FV + vslot * 8, vph);
#pragma unroll
            for (int j = 0; j < NB; j++) {
                x0[j] = lds128(t + j * 128);
                x1[j] = lds128(t + 768 + j * 128);
            }
            __syncwarp();
            if (lane == 0) mbar_arrive(bar + B_EV + vslot * 8);
            if (++vslot == NV) { vslot = 0; vph ^= 1; }
            ready = mbar_test(bar + B_FV + vslot * 8, vph);
        };
        auto fma_tile = [&]() {
            const float pv0 = __uint_as_float(pv.x), pv1 = __uint_as_float(pv.y);
#pragma unroll
            for (int j = 0; j < NB; j++) {
                acc[j * 4 + 0] = fmaf(pv1, (float)x1[j].x, fmaf(pv0, (float)x0[j].x, acc[j * 4 + 0]));
                acc[j * 4 + 1] = fmaf(pv1, (float)x1[j].y, fmaf(pv0, (float)x0[j].y, acc[j * 4 + 1]));
                acc[j * 4 + 2] = fmaf(pv1, (float)x1[j].z, fmaf(pv0, (float)x0[j].z, acc[j * 4 + 2]));
                acc[j * 4 + 3] = fmaf(pv1, (float)x1[j].w, fmaf(pv0, (float)x0[j].w, acc[j * 4 + 3]));
            }
        };
        for (uint32_t batch = 1; !(bd.y & F_END); batch++) {
            const uint32_t n = bd.y & F_NT, sbar = bar + (seg % NSEG) * 8;
            const bool last = bd.y & F_LAST;
            const uint32_t seg2 = seg + last, t2 = last ? 0 : t0 + n;
            const uint32_t s2 = sb + OFF_SEG + (seg2 % NSEG) * SEG_BYTES;
#pragma unroll
            for (int i = 0; i < 4 * NB; i++) acc[i] *= __uint_as_float(bd.x);
#pragma unroll 1
            for (uint32_t i = 1; i < n; i++) {
                load_tile();
                const uint2 pn = lds64(s + oP + (t0 + i) * (TR * 4));
                fma_tile();
                pv = pn;
            }
            load_tile();
            const bool early = mbar_test(sbar + B_FC, (seg / NSEG) & 1);
            const bool next = mbar_test(bar + B_PR + (batch % NBAT) * 8, (batch / NBAT) & 1);
            fma_tile();
            int4 cf;
            uint32_t gv[NB];
            uint2 bn, pn;
            if (early) {
                cf = lds128(s + S_CF);
#pragma unroll
                for (int j = 0; j < NB; j++) gv[j] = lds32(s + S_G + (col + j * 32) * 4);
            }
            if (last) {
                float o[NB];
#pragma unroll
                for (int j = 0; j < NB; j++) {
                    const float u0 = (up ? acc[j * 4 + 2] : acc[j * 4 + 0]) + __shfl_xor_sync(0xffffffffu, up ? acc[j * 4 + 0] : acc[j * 4 + 2], 16);
                    const float u1 = (up ? acc[j * 4 + 3] : acc[j * 4 + 1]) + __shfl_xor_sync(0xffffffffu, up ? acc[j * 4 + 1] : acc[j * 4 + 3], 16);
                    o[j] = (up2 ? u1 : u0) + __shfl_xor_sync(0xffffffffu, up2 ? u0 : u1, 8);
                }
                if (!early) {
                    mbar_wait(sbar + B_FC, (seg / NSEG) & 1);
                    cf = lds128(s + S_CF);
#pragma unroll
                    for (int j = 0; j < NB; j++) gv[j] = lds32(s + S_G + (col + j * 32) * 4);
                }
#pragma unroll
                for (int j = 0; j < NB; j++) {
                    const float gj = (bd.y & (F_SEMI | F_FIN)) ? __uint_as_float(gv[j]) : 0.f;
                    o[j] = fmaf(o[j], __int_as_float(cf.x), fmaf(gj, __int_as_float(cf.y), __int_as_float(cf.z)));
                }
                if (bd.y & F_FIN) {
#pragma unroll
                    for (int j = 0; j < NB; j++) {
                        const __nv_bfloat16 r = __float2bfloat16_rn(o[j]);
                        asm volatile("st.global.b16 [%0], %1;" ::"l"(outp + (bd.y >> 12) + j * 32), "h"(*(const uint16_t*)&r) : "memory");
                    }
                } else {
#pragma unroll
                    for (int j = 0; j < NB; j++) mail_put(mailp + (bd.y >> 12) + j * 32, o[j], cf.w & 3);
                    if (col < REC - D) mail_put(mailp + (bd.y >> 12) + D, __int_as_float(cf.w), cf.w & 3);
                }
#pragma unroll
                for (int i = 0; i < 4 * NB; i++) acc[i] = 0.f;
            }
            if (next) {
                bn = lds64(s2 + S_BD + t2 * 8);
                pn = lds64(s2 + oP + t2 * (TR * 4));
            }
            if (last) {
                __syncwarp();
                if (lane == 0) mbar_arrive(sbar + B_SE);
            }
            if (!next) {
                mbar_wait(bar + B_PR + (batch % NBAT) * 8, (batch / NBAT) & 1);
                bn = lds64(s2 + S_BD + t2 * 8);
                pn = lds64(s2 + oP + t2 * (TR * 4));
            }
            bd = bn; pv = pn; s = s2; t0 = t2; seg = seg2;
        }
    } else if (w == W_S) {
        uint32_t batch = 0;
        for (uint32_t seg = 0;; seg++) {
            const uint32_t s = sb + OFF_SEG + (seg % NSEG) * SEG_BYTES, sbar = bar + (seg % NSEG) * 8;
            const uint32_t sph = (seg / NSEG) & 1;
            mbar_wait(sbar + B_HDR, sph);
            const int4 desc = lds128(s + S_DESC);
            if (desc.y & F_END) {
                if (lane == 0) {
                    sts64(s + S_BD, 0.f, __uint_as_float(F_END));
                    mbar_arrive(bar + B_PR + (batch % NBAT) * 8);
                }
                break;
            }
            float m = NEG, L = 0.f, C = 0.f;
            const uint32_t head = (uint32_t)desc.x / TPH, index = (desc.y & F_FIN) ? head * D : (head * NM + desc.z) * REC;
            const int nt = desc.y & F_NT;
#pragma unroll 1
            for (int t0 = 0; t0 < nt; t0 += 4, batch++) {
                const int n = min(4, nt - t0);
                const bool valid = lane < n * TR;
                const uint32_t tl = t0 + (valid ? lane >> 3 : 0), row = tl * TR + (lane & 7);
                const uint32_t sc = s + S_SC + (((tl << (desc.w & 255)) + (desc.w >> 8)) * TR + (lane & 7)) * 2;
                const float vs = bf_lo(lds16(sc + 2 * SCB)), vz = bf_lo(lds16(sc + 3 * SCB));
                mbar_wait(bar + B_LG + (batch % NBAT) * 8, (batch / NBAT) & 1);
                const int4 part = lds128(s + S_LG + row * 16);
                const float dot = (__int_as_float(part.x) + __int_as_float(part.y)) + (__int_as_float(part.z) + __int_as_float(part.w));
                const float sv = rbf(rbf(dot) * 0.07216878364870322f) * LOG2E;
                int key = __float_as_int(fmaxf(m, sv));
                key ^= (key >> 31) & 0x7fffffff;
                key = __reduce_max_sync(0xffffffffu, key);
                const float mn = __int_as_float(key ^ ((key >> 31) & 0x7fffffff));
                const float alpha = ex2(m - mn), pr = ex2(sv - mn), pv = pr * vs;
                m = mn;
                sts32(s + S_PV + row * 4, pv);
                if (lane == 0)
                    sts64(s + S_BD + t0 * 8, alpha,
                          __uint_as_float(n | (t0 + n < nt ? 0 : index << 12 | F_LAST | (desc.y & (F_SEMI | F_FIN)))));
                __syncwarp();
                if (lane == 0) mbar_arrive(bar + B_PR + (batch % NBAT) * 8);
                L = fmaf(L, alpha, valid ? pr : 0.f);
                C = fmaf(C, alpha, valid ? pv * vz : 0.f);
            }
#pragma unroll
            for (int o = 16; o > 0; o >>= 1) {
                L += __shfl_xor_sync(0xffffffffu, L, o);
                C += __shfl_xor_sync(0xffffffffu, C, o);
            }
            mbar_wait(sbar + B_GD, sph);
            const uint32_t tag = lds32(sb + OFF_TAG) | ((desc.y & F_SEMI) ? 2 : 0);
            const float gl = (desc.y & (F_SEMI | F_FIN)) ? __uint_as_float(lds32(s + S_G + D * 4)) : -3.4e38f;
            const float M = fmaxf(m, gl), e = ex2(m - M), a = ex2(gl - M);
            const float W = fmaf(L, e, a), inv = rcp(W);
            if (lane == 0)
                sts128(s + S_CF, __float_as_uint(e * inv), __float_as_uint(a * inv), __float_as_uint(-C * e * inv),
                       (__float_as_uint(M + lg2(W)) & ~3u) | tag);
            __syncwarp();
            if (lane == 0) mbar_arrive(sbar + B_FC);
        }
    } else if ((unsigned)(w - W_G) < NGW) {
        if (w == W_G) {
            if (lane == 0) sts32(sb + OFF_TAG, __uint_as_float(~*(volatile unsigned int*)&g_epoch & 1));
        } else {
            mbar_wait(bar + B_GD, 0);
        }
        for (uint32_t seg = w - W_G;; seg += NGW) {
            const uint32_t s = sb + OFF_SEG + (seg % NSEG) * SEG_BYTES, sbar = bar + (seg % NSEG) * 8;
            mbar_wait(sbar + B_HDR, (seg / NSEG) & 1);
            const int4 desc = lds128(s + S_DESC);
            if (desc.y & F_END) break;
            if (desc.y & (F_SEMI | F_FIN)) {
                const uint32_t tag = lds32(sb + OFF_TAG) | ((desc.y & F_FIN) ? 2 : 0);
                const int cnt = (desc.y & F_FIN) ? 1 : NM;
                const uint32_t* mail = g_mail + (uint32_t)desc.x / TPH * (NM * REC);
                float M = NEG, W = 0.f, O[6] = {0.f, 0.f, 0.f, 0.f, 0.f, 0.f};
#pragma unroll 1
                for (int i0 = 0; i0 < cnt; i0 += GB, mail += GB * REC) {
                    uint2 pk[3 * GB];
                    uint32_t ls[GB], stale;
                    int it = 0;
                    do {
                        stale = 0;
#pragma unroll
                        for (int i = 0; i < GB; i++) {
                            ls[i] = 0xff7ffffcu | tag;
                            pk[3 * i] = pk[3 * i + 1] = pk[3 * i + 2] = make_uint2(tag, tag);
                            if (i0 + i < cnt) {
                                asm volatile("ld.relaxed.gpu.global.u32 %0, [%1];" : "=r"(ls[i]) : "l"(mail + i * REC + D) : "memory");
#pragma unroll
                                for (int k = 0; k < 3; k++)
                                    asm volatile("ld.relaxed.gpu.global.v2.u32 {%0,%1}, [%2];"
                                                 : "=r"(pk[3 * i + k].x), "=r"(pk[3 * i + k].y)
                                                 : "l"(mail + i * REC + k * 64 + lane * 2) : "memory");
                            }
                        }
#pragma unroll
                        for (int i = 0; i < GB; i++) stale |= ls[i] ^= tag;
#pragma unroll
                        for (int i = 0; i < 3 * GB; i++) stale |= (pk[i].x ^= tag) | (pk[i].y ^= tag);
                        if (++it > (1 << 22)) __trap();
                    } while (stale & 3);
                    float Mn = M;
#pragma unroll
                    for (int i = 0; i < GB; i++) Mn = fmaxf(Mn, __uint_as_float(ls[i]));
                    const float a = ex2(M - Mn);
                    M = Mn; W *= a;
#pragma unroll
                    for (int i = 0; i < 6; i++) O[i] *= a;
#pragma unroll
                    for (int i = 0; i < GB; i++) {
                        const float e = ex2(__uint_as_float(ls[i]) - M);
                        W += e;
#pragma unroll
                        for (int k = 0; k < 3; k++) {
                            O[2 * k] = fmaf(e, __uint_as_float(pk[3 * i + k].x), O[2 * k]);
                            O[2 * k + 1] = fmaf(e, __uint_as_float(pk[3 * i + k].y), O[2 * k + 1]);
                        }
                    }
                }
                const float inv = rcp(W);
#pragma unroll
                for (int k = 0; k < 3; k++) sts64(s + S_G + k * 256 + lane * 8, O[2 * k] * inv, O[2 * k + 1] * inv);
                if (lane == 0) sts32(s + S_G + D * 4, M + lg2(W));
            }
            __syncwarp();
            if (lane == 0) mbar_arrive(sbar + B_GD);
        }
    } else if (w / NKW == 0) {
        const int g = lane >> 3, l = lane & 7, godd = g & 1, row = 2 * g + (w & 1);
        const uint32_t sgA = pin(godd ? 0x3f803f80u : 0xbf80bf80u), sgB = pin(godd ? 0xbf80bf80u : 0x3f803f80u);
        const uint32_t oKA = pin(sb + row * (D * 4) + l * 16 + godd * 384), oKB = pin(oKA - godd * 768 + 384);
        const uint32_t oCA = pin(sb + T_C + row * (D * 2) + l * 8 + godd * 192), oCB = pin(oCA - godd * 384 + 192);
        const uint32_t oL = pin(S_LG + row * 16 + (l >> 2) * 8 + (l & 1) * 4), oS = pin(S_SC + row * 2);
        const bool own = (l & 3) == g, hi = l & 4, keep = ((l ^ g) & 2) == 0;
        uint32_t kslot = w >> 1, j = kslot, batch0 = 0, kph = 0;
        for (uint32_t seg = 0;; seg++) {
            const uint32_t s = sb + OFF_SEG + (seg % NSEG) * SEG_BYTES, sbar = bar + (seg % NSEG) * 8;
            mbar_wait(sbar + B_HDR, (seg / NSEG) & 1);
            const int4 desc = lds128(s + S_DESC);
            if (desc.y & F_END) break;
            const uint32_t nt = desc.y & F_NT;
            uint2 qr[3];
#pragma unroll
            for (int i = 0; i < 3; i++) {
                const uint32_t oa = l * 8 + godd * 192 + i * 64, ob = oa + 192 - godd * 384;
                const uint2 a = lds64(s + S_Q + oa), b = lds64(s + S_Q + ob);
                const uint2 ca = lds64(sb + OFF_QT + oa), sa = lds64(sb + OFF_QT + QBYTES + oa);
                qr[i].x = rope2(a.x, ca.x, b.x, sa.x, sgA);
                qr[i].y = rope2(a.y, ca.y, b.y, sa.y, sgA);
            }
            for (; j < nt; j += NKW / 2) {
                const uint32_t t = kslot * KSLOT;
                const uint32_t sc = s + oS + ((j << (desc.w & 255)) + (desc.w >> 8)) * (TR * 2);
                const uint32_t ks2 = lds16(sc) * 0x10001u, kz2 = lds16(sc + SCB) * 0x10001u;
                const uint32_t lgb = bar + B_LG + ((batch0 + (j >> 2)) % NBAT) * 8;
                const uint32_t lgc = j == nt - 1 ? 4 - (j & 3) : 1;
                mbar_wait(bar + B_FK + kslot * 8, kph);
                float c[4] = {0.f, 0.f, 0.f, 0.f};
#pragma unroll
                for (int jj = 0; jj < 3; jj++) {
                    const int4 xa = lds128(t + oKA + jj * 128), xb = lds128(t + oKB + jj * 128);
                    const uint2 ca = lds64(t + oCA + jj * 64), cb = lds64(t + oCB + jj * 64);
                    const uint2 sa = lds64(t + oCA + CBYTES + jj * 64), sbv = lds64(t + oCB + CBYTES + jj * 64);
                    const uint32_t a0 = bmul(bsub(i2bf2(xa.x, xa.y), kz2), ks2);
                    const uint32_t a1 = bmul(bsub(i2bf2(xa.z, xa.w), kz2), ks2);
                    const uint32_t b0 = bmul(bsub(i2bf2(xb.x, xb.y), kz2), ks2);
                    const uint32_t b1 = bmul(bsub(i2bf2(xb.z, xb.w), kz2), ks2);
                    mma_bf16(c, rope2(a0, ca.x, b0, sa.x, sgA), rope2(b0, cb.x, a0, sbv.x, sgB),
                             rope2(a1, ca.y, b1, sa.y, sgA), rope2(b1, cb.y, a1, sbv.y, sgB), qr[jj].x, qr[jj].y);
                }
                __syncwarp();
                if (lane == 0) mbar_arrive(bar + B_EK + kslot * 8);
                const float part = own ? (hi ? c[1] : c[0]) : (hi ? c[3] : c[2]);
                if (keep) sts32(s + oL + j * (TR * 16), part);
                __syncwarp();
                if (lane == 0) mbar_arrive(lgb, lgc);
                kslot += NKW / 2;
                if (kslot >= NK) { kslot -= NK; kph ^= 1; }
            }
            j -= nt;
            batch0 += (nt + 3) >> 2;
            __syncwarp();
            if (lane == 0) mbar_arrive(sbar + B_SE);
        }
    } else if (w == W_SCH) {
        if (elect_one()) {
            asm volatile("mbarrier.expect_tx.shared::cta.b64 [%0], %1;" ::"r"(bar + B_HDR), "r"(2 * QBYTES) : "memory");
            uint32_t seg = 0, c = blockIdx.x;
            while (c < NCLAIM) {
                const Claim cl = decode_claim(c);
                const uint32_t s = sb + OFF_SEG + (seg % NSEG) * SEG_BYTES, b = bar + (seg % NSEG) * 8;
                mbar_wait(b + B_SE, ((seg / NSEG) & 1) ^ 1);
                sts128(s + S_DESC, cl.tile0 + cl.off, cl.ntiles | (c >= C_F ? F_FIN : c >= C_S ? F_SEMI : 0), cl.piece,
                       cl.sh | cl.off << 8);
                if (seg) mbar_arrive(bar + B_DS + ((seg - 1) % NSEG) * 8);
                const uint32_t scb = cl.ntiles * TR * 2 << cl.sh, r = cl.tile0 * TR;
                mbar_expect(b + B_HDR, 4 * scb + QBYTES);
                bulk_plain(s + S_Q, p.q + cl.head * D, QBYTES, b + B_HDR);
                bulk_plain(s + S_SC, p.ks + r, scb, b + B_HDR);
                bulk_plain(s + S_SC + SCB, p.kz + r, scb, b + B_HDR);
                bulk_plain(s + S_SC + 2 * SCB, p.vs + r, scb, b + B_HDR);
                bulk_plain(s + S_SC + 3 * SCB, p.vz + r, scb, b + B_HDR);
                if (seg == 0) {
                    bulk_plain(sb + OFF_QT, p.qcos, QBYTES, bar + B_HDR);
                    bulk_plain(sb + OFF_QT + QBYTES, p.qsin, QBYTES, bar + B_HDR);
                    mbar_wait(bar + B_GD, 0);
                }
                mbar_wait(bar + B_GO, seg & 1);
                seg++;
                const unsigned nx = atomicInc(&g_queue, NCLAIM - 1);
                if (nx == NCLAIM - 1) g_epoch = lds32(sb + OFF_TAG);
                c = gridDim.x + nx;
            }
#pragma unroll 1
            for (int i = 0; i < NGW; i++, seg++) {
                const uint32_t s = sb + OFF_SEG + (seg % NSEG) * SEG_BYTES, b = bar + (seg % NSEG) * 8;
                mbar_wait(b + B_SE, ((seg / NSEG) & 1) ^ 1);
                sts128(s + S_DESC, 0, F_END, 0, 0);
                mbar_arrive(bar + B_DS + ((seg - 1) % NSEG) * 8);
                mbar_arrive(b + B_HDR);
            }
        }
    } else {
        if (elect_one()) {
            uint64_t pol;
            asm volatile("createpolicy.fractional.L2::evict_first.b64 %0, 1.0;" : "=l"(pol));
            uint32_t kslot = 0, vslot = 0, kph = 1, vph = 1;
            int pend[LEAD];
#pragma unroll
            for (int i = 0; i < LEAD; i++) pend[i] = -1;
            auto issue_v = [&]() {
                if (pend[0] >= 0) {
                    const uint32_t b = bar + vslot * 8;
                    mbar_wait(b + B_EV, vph);
                    mbar_expect(b + B_FV, KBYTES);
                    bulk_stream(sb + OFF_V + vslot * KBYTES, p.qv + (size_t)pend[0] * (TR * D), KBYTES, b + B_FV, pol);
                    if (++vslot == NV) { vslot = 0; vph ^= 1; }
                }
#pragma unroll
                for (int i = 0; i + 1 < LEAD; i++) pend[i] = pend[i + 1];
                pend[LEAD - 1] = -1;
            };
            const Claim c0 = decode_claim(blockIdx.x % C_S);
            int4 desc = make_int4(c0.tile0 + c0.off, c0.ntiles, 0, GSH);
            for (uint32_t seg = 0; !(desc.y & F_END); seg++) {
                uint32_t tile = desc.x;
#pragma unroll 1
                for (int left = desc.y & F_NT; left > 0; left--, tile += 1u << (desc.w & 255)) {
                    if (left == 1) mbar_arrive(bar + B_GO);
                    const uint32_t t = sb + kslot * KSLOT, b = bar + kslot * 8;
                    const uint32_t ro = (tile % TPH) * (TR * D);
                    mbar_wait(b + B_EK, kph);
                    mbar_expect(b + B_FK, KSLOT);
                    bulk_stream(t, p.qk + (size_t)tile * (TR * D), KBYTES, b + B_FK, pol);
                    bulk_plain(t + T_C, p.kcos + ro, CBYTES, b + B_FK);
                    bulk_plain(t + T_S, p.ksin + ro, CBYTES, b + B_FK);
                    if (++kslot == NK) { kslot = 0; kph ^= 1; }
                    pend[LEAD - 1] = tile;
                    issue_v();
                }
                mbar_wait(bar + B_DS + (seg % NSEG) * 8, (seg / NSEG) & 1);
                desc = lds128(sb + OFF_SEG + ((seg + 1) % NSEG) * SEG_BYTES + S_DESC);
            }
#pragma unroll 1
            for (int i = 1; i < LEAD; i++) issue_v();
        }
    }
}

}

extern "C" void kernel_launch(void* const* d_in, const int* in_sizes, int n_in, void* d_out, int out_size) {
    (void)in_sizes; (void)n_in; (void)out_size;
    static int sms = 0;
    if (sms == 0) {
        int dev = 0;
        cudaGetDevice(&dev);
        cudaDeviceGetAttribute(&sms, cudaDevAttrMultiProcessorCount, dev);
        cudaFuncSetAttribute(kv_rope_decode_kernel, cudaFuncAttributeMaxDynamicSharedMemorySize, SMEM_BYTES);
    }
    Params p;
    p.q    = (const __nv_bfloat16*)d_in[0];
    p.qk   = (const int*)d_in[1];
    p.ks   = (const __nv_bfloat16*)d_in[2];
    p.kz   = (const __nv_bfloat16*)d_in[3];
    p.qv   = (const int*)d_in[4];
    p.vs   = (const __nv_bfloat16*)d_in[5];
    p.vz   = (const __nv_bfloat16*)d_in[6];
    p.qcos = (const __nv_bfloat16*)d_in[7];
    p.qsin = (const __nv_bfloat16*)d_in[8];
    p.kcos = (const __nv_bfloat16*)d_in[9];
    p.ksin = (const __nv_bfloat16*)d_in[10];
    p.out  = (__nv_bfloat16*)d_out;
    kv_rope_decode_kernel<<<sms, NTHREADS, SMEM_BYTES>>>(p);
}
```

```cpp
#include <cuda_runtime.h>
#include <cuda_bf16.h>
#include <stdint.h>

namespace {

constexpr int D      = 192;
constexpr int SKV    = 2048;
constexpr int NHEAD  = 256;
constexpr int TR     = 8;
constexpr int TPH    = SKV / TR;
constexpr int NKW    = 4;
constexpr int NVW    = 6;
constexpr int NB     = 6 / NVW;
constexpr int NGW    = 2;
constexpr int NK     = 8;
constexpr int NV     = 6;
constexpr int WIN    = 4;
constexpr int LEAD   = 5;
constexpr int NSEG   = 8;
constexpr int SEGT   = 16;
constexpr int NBAT   = 16;
constexpr int W_V = NKW, W_PROD = W_V + NVW, W_S = W_PROD + 1, W_G = W_S + 1, W_SCH = W_G + NGW, NWARPS = W_SCH + 1;
constexpr int NTHREADS = 32 + NWARPS * 32;

constexpr int MAINP  = 16;
constexpr int PF0    = 3;
constexpr int GSH    = 2;
__host__ __device__ constexpr int semi_size(uint32_t h) { return (0x88ccu >> (h / 64 * 4)) & 15; }
__host__ __device__ constexpr int fin_size(uint32_t h) { return (0x248cu >> (h / 64 * 4)) & 15; }
__host__ __device__ constexpr uint32_t cut_group(uint32_t h) { return (2 - h / 4) % 4; }
constexpr int NM     = TPH / MAINP;
static_assert(NM >> GSH == 4, "four interleave groups per head");
constexpr int C_S    = NHEAD * NM, C_F = C_S + NHEAD, NCLAIM = C_F + NHEAD;

constexpr int KBYTES = TR * D * 4;
constexpr int CBYTES = TR * D * 2;
constexpr int QBYTES = D * 2;
constexpr int T_C = KBYTES, T_S = T_C + CBYTES, KSLOT = T_S + CBYTES;
constexpr int SCB = SEGT * TR * 2 << GSH;
static_assert(MAINP <= SEGT && semi_size(0) <= SEGT && fin_size(0) <= SEGT && GSH >= 1, "a piece fills one segment slot");
constexpr int S_Q    = 0;
constexpr int S_SC   = S_Q + QBYTES;
constexpr int S_DESC = S_SC + 4 * SCB;
constexpr int S_BD   = S_DESC + 16;
constexpr int S_LG   = S_BD + SEGT * 8;
constexpr int S_PV   = S_LG + SEGT * TR * 16;
constexpr int S_G    = S_PV + SEGT * TR * 4;
constexpr int S_CF   = S_G + (D + 4) * 4;
constexpr int SEG_BYTES = (S_CF + 16 + 127) / 128 * 128;
constexpr int OFF_V = NK * KSLOT, OFF_SEG = OFF_V + NV * KBYTES, OFF_QT = OFF_SEG + NSEG * SEG_BYTES,
              OFF_TAG = OFF_QT + 2 * QBYTES, OFF_BAR = OFF_TAG + 16;
constexpr int B_FK = 0, B_DS = 64, B_PR = 128, B_HDR = 256, B_GD = 320, B_FC = 384, B_FV = 448, B_GO = 504,
              B_LG = 512, B_SE = 640, B_EV = 768, B_EK = 896;
constexpr int SMEM_BYTES = OFF_BAR + 1024;
static_assert(NK <= 8 && NV <= 7 && W_PROD >= 8 && NSEG == 8 && NBAT == 16, "barrier layout");
static_assert(SMEM_BYTES <= 232448 && SMEM_BYTES > 232448 / 2, "one CTA per SM");
static_assert(NSEG % NGW == 0 && NK % (NKW / 2) == 0 && NB * NVW == 6 && LEAD >= 1, "cfg");
static_assert(WIN < NV && LEAD + NV >= 4 && LEAD + NV < NBAT && LEAD < NSEG, "no ring can be lapped or starved");

__device__ unsigned int g_queue;
constexpr int REC = 200, GB = 4;
__device__ unsigned int g_epoch;
__device__ __align__(32) uint32_t g_mail[NHEAD * NM * REC];

__device__ __forceinline__ uint32_t smem_u32(const void* p) { return (uint32_t)__cvta_generic_to_shared(p); }
__device__ __forceinline__ uint32_t pin(uint32_t x) {
    return __shfl_sync(0xffffffffu, x, threadIdx.x & 31);
}
template <class T> __device__ __forceinline__ T* pin(T* p) {
    return (T*)__shfl_sync(0xffffffffu, (unsigned long long)p, threadIdx.x & 31);
}
__device__ __forceinline__ bool elect_one() {
    uint32_t pred;
    asm volatile("{\n.reg .pred p;\nelect.sync _|p, 0xffffffff;\nselp.u32 %0, 1, 0, p;\n}" : "=r"(pred));
    return pred;
}
__device__ __forceinline__ void mbar_init(uint32_t bar, uint32_t cnt) {
    asm volatile("mbarrier.init.shared::cta.b64 [%0], %1;" ::"r"(bar), "r"(cnt) : "memory");
}
__device__ __forceinline__ void mbar_expect(uint32_t bar, uint32_t bytes) {
    asm volatile("mbarrier.arrive.expect_tx.shared::cta.b64 _, [%0], %1;" ::"r"(bar), "r"(bytes) : "memory");
}
__device__ __forceinline__ void mbar_arrive(uint32_t bar) {
    asm volatile("mbarrier.arrive.shared::cta.b64 _, [%0];" ::"r"(bar) : "memory");
}
__device__ __forceinline__ void mbar_arrive(uint32_t bar, uint32_t cnt) {
    asm volatile("mbarrier.arrive.shared::cta.b64 _, [%0], %1;" ::"r"(bar), "r"(cnt) : "memory");
}
__device__ __forceinline__ bool mbar_test(uint32_t bar, uint32_t parity) {
    uint32_t ok;
    asm volatile("{\n.reg .pred p;\nmbarrier.test_wait.parity.shared::cta.b64 p, [%1], %2;\nselp.u32 %0, 1, 0, p;\n}"
                 : "=r"(ok) : "r"(bar), "r"(parity) : "memory");
    return ok;
}
__device__ __forceinline__ void mbar_wait(uint32_t bar, uint32_t parity) {
    asm volatile("{\n.reg .pred p;\n.reg .u32 n;\n"
                 "mbarrier.try_wait.parity.shared::cta.b64 p, [%0], %1;\n"
                 "@p bra DONE;\n"
                 "mov.u32 n, 0;\n"
                 "LOOP:\n"
                 "mbarrier.try_wait.parity.shared::cta.b64 p, [%0], %1;\n"
                 "@p bra DONE;\n"
                 "add.u32 n, n, 1;\n"
                 "setp.lt.u32 p, n, 0x400000;\n"
                 "@p bra LOOP;\n"
                 "trap;\n"
                 "DONE:\n}" ::"r"(bar), "r"(parity) : "memory");
}
__device__ __forceinline__ void bulk_stream(uint32_t dst, const void* src, uint32_t bytes, uint32_t bar, uint64_t pol) {
    asm volatile("cp.async.bulk.shared::cluster.global.mbarrier::complete_tx::bytes.L2::cache_hint [%0], [%1], %2, [%3], %4;"
                 ::"r"(dst), "l"(src), "r"(bytes), "r"(bar), "l"(pol) : "memory");
}
__device__ __forceinline__ void bulk_plain(uint32_t dst, const void* src, uint32_t bytes, uint32_t bar) {
    asm volatile("cp.async.bulk.shared::cluster.global.mbarrier::complete_tx::bytes [%0], [%1], %2, [%3];"
                 ::"r"(dst), "l"(src), "r"(bytes), "r"(bar) : "memory");
}
__device__ __forceinline__ void l2_prefetch(const void* src, uint32_t bytes, uint64_t pol) {
    asm volatile("cp.async.bulk.prefetch.L2.global.L2::cache_hint [%0], %1, %2;" ::"l"(src), "r"(bytes), "l"(pol) : "memory");
}
__device__ __forceinline__ void l2_prefetch(const void* src, uint32_t bytes) {
    asm volatile("cp.async.bulk.prefetch.L2.global [%0], %1;" ::"l"(src), "r"(bytes) : "memory");
}
__device__ __forceinline__ int4 lds128(uint32_t a) {
    int4 v;
    asm volatile("ld.shared.v4.s32 {%0,%1,%2,%3}, [%4];" : "=r"(v.x), "=r"(v.y), "=r"(v.z), "=r"(v.w) : "r"(a));
    return v;
}
__device__ __forceinline__ uint2 lds64(uint32_t a) {
    uint2 v;
    asm volatile("ld.shared.v2.u32 {%0,%1}, [%2];" : "=r"(v.x), "=r"(v.y) : "r"(a));
    return v;
}
__device__ __forceinline__ uint32_t lds32(uint32_t a) {
    uint32_t v;
    asm volatile("ld.shared.u32 %0, [%1];" : "=r"(v) : "r"(a));
    return v;
}
__device__ __forceinline__ uint32_t lds16(uint32_t a) {
    uint16_t v;
    asm volatile("ld.shared.u16 %0, [%1];" : "=h"(v) : "r"(a));
    return v;
}
__device__ __forceinline__ void sts32(uint32_t a, float x) {
    asm volatile("st.shared.f32 [%0], %1;" ::"r"(a), "f"(x) : "memory");
}
__device__ __forceinline__ void sts128(uint32_t a, uint32_t x, uint32_t y, uint32_t z, uint32_t w) {
    asm volatile("st.shared.v4.u32 [%0], {%1,%2,%3,%4};" ::"r"(a), "r"(x), "r"(y), "r"(z), "r"(w) : "memory");
}
__device__ __forceinline__ void sts64(uint32_t a, float x, float y) {
    asm volatile("st.shared.v2.f32 [%0], {%1,%2};" ::"r"(a), "f"(x), "f"(y) : "memory");
}
__device__ __forceinline__ float bf_lo(uint32_t v) { return __uint_as_float(v << 16); }
__device__ __forceinline__ float rbf(float x) {
    uint32_t d; asm("cvt.rn.bf16x2.f32 %0, %1, %2;" : "=r"(d) : "f"(x), "f"(0.f)); return __uint_as_float(d);
}
__device__ __forceinline__ float rcp(float x) {
    float y;
    asm("rcp.approx.ftz.f32 %0, %1;" : "=f"(y) : "f"(x));
    return y;
}
__device__ __forceinline__ float lg2(float x) {
    float y;
    asm("lg2.approx.ftz.f32 %0, %1;" : "=f"(y) : "f"(x));
    return y;
}
__device__ __forceinline__ float ex2(float x) {
    float y;
    asm("ex2.approx.ftz.f32 %0, %1;" : "=f"(y) : "f"(x));
    return y;
}
__device__ __forceinline__ uint32_t bmul(uint32_t a, uint32_t b) {
    uint32_t d; asm("mul.rn.bf16x2 %0, %1, %2;" : "=r"(d) : "r"(a), "r"(b)); return d;
}
__device__ __forceinline__ uint32_t bsub(uint32_t a, uint32_t b) {
    uint32_t d; asm("sub.rn.bf16x2 %0, %1, %2;" : "=r"(d) : "r"(a), "r"(b)); return d;
}
__device__ __forceinline__ uint32_t bfma(uint32_t a, uint32_t b, uint32_t c) {
    uint32_t d; asm("fma.rn.bf16x2 %0, %1, %2, %3;" : "=r"(d) : "r"(a), "r"(b), "r"(c)); return d;
}
__device__ __forceinline__ uint32_t i2bf2(int lo, int hi) {
    uint32_t d; asm("cvt.rn.bf16x2.f32 %0, %1, %2;" : "=r"(d) : "f"((float)hi), "f"((float)lo)); return d;
}
__device__ __forceinline__ uint32_t rope2(uint32_t x, uint32_t c, uint32_t y, uint32_t s, uint32_t sg) {
    return bfma(bmul(y, s), sg, bmul(x, c));
}
__device__ __forceinline__ void mma_bf16(float (&c)[4], uint32_t a0, uint32_t a1, uint32_t a2, uint32_t a3,
                                         uint32_t b0, uint32_t b1) {
    asm("mma.sync.aligned.m16n8k16.row.col.f32.bf16.bf16.f32 {%0,%1,%2,%3}, {%4,%5,%6,%7}, {%8,%9}, {%0,%1,%2,%3};"
        : "+f"(c[0]), "+f"(c[1]), "+f"(c[2]), "+f"(c[3])
        : "r"(a0), "r"(a1), "r"(a2), "r"(a3), "r"(b0), "r"(b1));
}
__device__ __forceinline__ void mail_put(uint32_t* p, float x, uint32_t tag) {
    asm volatile("st.relaxed.gpu.global.u32 [%0], %1;" ::"l"(p), "r"((__float_as_uint(x) & ~3u) | tag) : "memory");
}

struct Claim { uint32_t head, tile0, piece, sh, off; int ntiles; };

__device__ __forceinline__ Claim decode_claim(uint32_t c) {
    Claim cl;
    cl.sh = cl.off = 0;
    if (c < C_S) {
        cl.head = c / NM; cl.piece = c % NM; cl.sh = GSH; cl.off = c % (1 << GSH); cl.tile0 = (c - cl.off) * MAINP;
        cl.ntiles = MAINP;
        if (cl.piece >> GSH == cut_group(cl.head))
            cl.ntiles -= (semi_size(cl.head) + fin_size(cl.head) + cl.off) >> GSH;
    } else {
        cl.head = (c - C_S) % NHEAD; cl.piece = 0;
        cl.ntiles = fin_size(cl.head); cl.tile0 = cl.head * TPH + (cut_group(cl.head) + 1) * (TPH / 4) - cl.ntiles;
        if (c < C_F) { cl.ntiles = semi_size(cl.head); cl.tile0 -= cl.ntiles; }
    }
    return cl;
}

struct Params {
    const int* qk; const __nv_bfloat16* kcos; const __nv_bfloat16* ksin; const int* qv;
    const __nv_bfloat16* ks; const __nv_bfloat16* kz; const __nv_bfloat16* vs; const __nv_bfloat16* vz;
    const __nv_bfloat16* q; const __nv_bfloat16* qcos; const __nv_bfloat16* qsin;
    __nv_bfloat16* out;
};

constexpr float NEG = -3.0e38f;
constexpr float LOG2E = 1.4426950408889634f;
constexpr int F_NT = 31, F_LAST = 64, F_SEMI = 128, F_FIN = 256, F_END = 512;
static_assert(NHEAD * NM * REC < (1 << 20), "batch descriptor");

__global__ void __launch_bounds__(NTHREADS, 1)
kv_rope_decode_kernel(const Params p) {
    extern __shared__ __align__(128) unsigned char smem[];
    if (threadIdx.x < 32 && elect_one()) {
        l2_prefetch(p.kcos + (blockIdx.x % (TPH / 2)) * (2 * TR * D), 2 * CBYTES);
        l2_prefetch(p.ksin + (blockIdx.x % (TPH / 2)) * (2 * TR * D), 2 * CBYTES);
        uint64_t pol;
        asm volatile("createpolicy.fractional.L2::evict_first.b64 %0, 1.0;" : "=l"(pol));
        const uint32_t off = blockIdx.x % (1 << GSH);
        l2_prefetch(p.qk + (size_t)((blockIdx.x - off) * MAINP + off * PF0) * (TR * D), PF0 * KBYTES, pol);
    }
    const int w = __shfl_sync(0xffffffffu, (threadIdx.x >> 5) - 1, 0), lane = threadIdx.x & 31;
    if (w < 0) return;
    const uint32_t sb = __shfl_sync(0xffffffffu, smem_u32(smem), 0);
    const uint32_t bar = sb + OFF_BAR;

    if (w < 8 && elect_one()) {
        const uint32_t cnt = w == 4 ? 8 : w == 5 ? NKW + NVW : w == 6 ? NVW : w == 7 ? 2 : 1;
#pragma unroll
        for (int i = 0; i < 16; i++) mbar_init(bar + w * 128 + i * 8, cnt);
        asm volatile("fence.mbarrier_init.release.cluster;" ::: "memory");
    }
    asm volatile("bar.sync 0, %0;" ::"n"(NWARPS * 32) : "memory");

    if ((unsigned)(w - W_V) < NVW) {
        const int v = w - W_V, g = lane >> 3, l = lane & 7;
        const bool up = lane & 16, up2 = lane & 8;
        const uint32_t oV = pin(sb + OFF_V + g * (2 * D * 4) + v * (NB * 128) + l * 16), oP = pin(S_PV + g * 8);
        const uint32_t col = pin(v * (NB * 32) + l * 4 + (up ? 2 : 0) + (up2 ? 1 : 0));
        __nv_bfloat16* const outp = pin(p.out + col);
        uint32_t* const mailp = pin(g_mail + col);
        float acc[4 * NB];
#pragma unroll
        for (int i = 0; i < 4 * NB; i++) acc[i] = 0.f;
        uint32_t vslot = 0, seg = 0, vph = 0;
        uint32_t s = sb + OFF_SEG, t0 = 0;
        mbar_wait(bar + B_PR, 0);
        uint2 bd = lds64(s + S_BD);
        uint2 pv = lds64(s + oP);
        bool ready = false;
        int4 x0[NB], x1[NB];
        auto load_tile = [&]() {
            const uint32_t t = oV + vslot * KBYTES;
            if (!ready) mbar_wait(bar + B_FV + vslot * 8, vph);
#pragma unroll
            for (int j = 0; j < NB; j++) {
                x0[j] = lds128(t + j * 128);
                x1[j] = lds128(t + 768 + j * 128);
            }
            __syncwarp();
            if (lane == 0) mbar_arrive(bar + B_EV + vslot * 8);
            if (++vslot == NV) { vslot = 0; vph ^= 1; }
            ready = mbar_test(bar + B_FV + vslot * 8, vph);
        };
        auto fma_tile = [&]() {
            const float pv0 = __uint_as_float(pv.x), pv1 = __uint_as_float(pv.y);
#pragma unroll
            for (int j = 0; j < NB; j++) {
                acc[j * 4 + 0] = fmaf(pv1, (float)x1[j].x, fmaf(pv0, (float)x0[j].x, acc[j * 4 + 0]));
                acc[j * 4 + 1] = fmaf(pv1, (float)x1[j].y, fmaf(pv0, (float)x0[j].y, acc[j * 4 + 1]));
                acc[j * 4 + 2] = fmaf(pv1, (float)x1[j].z, fmaf(pv0, (float)x0[j].z, acc[j * 4 + 2]));
                acc[j * 4 + 3] = fmaf(pv1, (float)x1[j].w, fmaf(pv0, (float)x0[j].w, acc[j * 4 + 3]));
            }
        };
        for (uint32_t batch = 1; !(bd.y & F_END); batch++) {
            const uint32_t n = bd.y & F_NT, sbar = bar + (seg % NSEG) * 8;
            const bool last = bd.y & F_LAST;
            const uint32_t seg2 = seg + last, t2 = last ? 0 : t0 + n;
            const uint32_t s2 = sb + OFF_SEG + (seg2 % NSEG) * SEG_BYTES;
#pragma unroll
            for (int i = 0; i < 4 * NB; i++) acc[i] *= __uint_as_float(bd.x);
#pragma unroll 1
            for (uint32_t i = 1; i < n; i++) {
                load_tile();
                const uint2 pn = lds64(s + oP + (t0 + i) * (TR * 4));
                fma_tile();
                pv = pn;
            }
            load_tile();
            const bool early = mbar_test(sbar + B_FC, (seg / NSEG) & 1);
            const bool next = mbar_test(bar + B_PR + (batch % NBAT) * 8, (batch / NBAT) & 1);
            fma_tile();
            int4 cf;
            uint32_t gv[NB];
            uint2 bn, pn;
            if (early) {
                cf = lds128(s + S_CF);
#pragma unroll
                for (int j = 0; j < NB; j++) gv[j] = lds32(s + S_G + (col + j * 32) * 4);
            }
            if (last) {
                float o[NB];
#pragma unroll
                for (int j = 0; j < NB; j++) {
                    const float u0 = (up ? acc[j * 4 + 2] : acc[j * 4 + 0]) + __shfl_xor_sync(0xffffffffu, up ? acc[j * 4 + 0] : acc[j * 4 + 2], 16);
                    const float u1 = (up ? acc[j * 4 + 3] : acc[j * 4 + 1]) + __shfl_xor_sync(0xffffffffu, up ? acc[j * 4 + 1] : acc[j * 4 + 3], 16);
                    o[j] = (up2 ? u1 : u0) + __shfl_xor_sync(0xffffffffu, up2 ? u0 : u1, 8);
                }
                if (!early) {
                    mbar_wait(sbar + B_FC, (seg / NSEG) & 1);
                    cf = lds128(s + S_CF);
#pragma unroll
                    for (int j = 0; j < NB; j++) gv[j] = lds32(s + S_G + (col + j * 32) * 4);
                }
#pragma unroll
                for (int j = 0; j < NB; j++) {
                    const float gj = (bd.y & (F_SEMI | F_FIN)) ? __uint_as_float(gv[j]) : 0.f;
                    o[j] = fmaf(o[j], __int_as_float(cf.x), fmaf(gj, __int_as_float(cf.y), __int_as_float(cf.z)));
                }
                if (bd.y & F_FIN) {
#pragma unroll
                    for (int j = 0; j < NB; j++) {
                        const __nv_bfloat16 r = __float2bfloat16_rn(o[j]);
                        asm volatile("st.global.b16 [%0], %1;" ::"l"(outp + (bd.y >> 12) + j * 32), "h"(*(const uint16_t*)&r) : "memory");
                    }
                } else {
#pragma unroll
                    for (int j = 0; j < NB; j++) mail_put(mailp + (bd.y >> 12) + j * 32, o[j], cf.w & 3);
                    if (col < REC - D) mail_put(mailp + (bd.y >> 12) + D, __int_as_float(cf.w), cf.w & 3);
                }
#pragma unroll
                for (int i = 0; i < 4 * NB; i++) acc[i] = 0.f;
            }
            if (next) {
                bn = lds64(s2 + S_BD + t2 * 8);
                pn = lds64(s2 + oP + t2 * (TR * 4));
            }
            if (last) {
                __syncwarp();
                if (lane == 0) mbar_arrive(sbar + B_SE);
            }
            if (!next) {
                mbar_wait(bar + B_PR + (batch % NBAT) * 8, (batch / NBAT) & 1);
                bn = lds64(s2 + S_BD + t2 * 8);
                pn = lds64(s2 + oP + t2 * (TR * 4));
            }
            bd = bn; pv = pn; s = s2; t0 = t2; seg = seg2;
        }
    } else if (w == W_S) {
        uint32_t batch = 0;
        for (uint32_t seg = 0;; seg++) {
            const uint32_t s = sb + OFF_SEG + (seg % NSEG) * SEG_BYTES, sbar = bar + (seg % NSEG) * 8;
            const uint32_t sph = (seg / NSEG) & 1;
            mbar_wait(sbar + B_HDR, sph);
            const int4 desc = lds128(s + S_DESC);
            if (desc.y & F_END) {
                if (lane == 0) {
                    sts64(s + S_BD, 0.f, __uint_as_float(F_END));
                    mbar_arrive(bar + B_PR + (batch % NBAT) * 8);
                }
                break;
            }
            float m = NEG, L = 0.f, C = 0.f;
            const uint32_t head = (uint32_t)desc.x / TPH, index = (desc.y & F_FIN) ? head * D : (head * NM + desc.z) * REC;
            const int nt = desc.y & F_NT;
#pragma unroll 1
            for (int t0 = 0; t0 < nt; t0 += 4, batch++) {
                const int n = min(4, nt - t0);
                const bool valid = lane < n * TR;
                const uint32_t tl = t0 + (valid ? lane >> 3 : 0), row = tl * TR + (lane & 7);
                const uint32_t sc = s + S_SC + (((tl << (desc.w & 255)) + (desc.w >> 8)) * TR + (lane & 7)) * 2;
                const float vs = bf_lo(lds16(sc + 2 * SCB)), vz = bf_lo(lds16(sc + 3 * SCB));
                mbar_wait(bar + B_LG + (batch % NBAT) * 8, (batch / NBAT) & 1);
                const int4 part = lds128(s + S_LG + row * 16);
                const float dot = (__int_as_float(part.x) + __int_as_float(part.y)) + (__int_as_float(part.z) + __int_as_float(part.w));
                const float sv = rbf(rbf(dot) * 0.07216878364870322f) * LOG2E;
                int key = __float_as_int(fmaxf(m, sv));
                key ^= (key >> 31) & 0x7fffffff;
                key = __reduce_max_sync(0xffffffffu, key);
                const float mn = __int_as_float(key ^ ((key >> 31) & 0x7fffffff));
                const float alpha = ex2(m - mn), pr = ex2(sv - mn), pv = pr * vs;
                m = mn;
                sts32(s + S_PV + row * 4, pv);
                if (lane == 0)
                    sts64(s + S_BD + t0 * 8, alpha,
                          __uint_as_float(n | (t0 + n < nt ? 0 : index << 12 | F_LAST | (desc.y & (F_SEMI | F_FIN)))));
                __syncwarp();
                if (lane == 0) mbar_arrive(bar + B_PR + (batch % NBAT) * 8);
                L = fmaf(L, alpha, valid ? pr : 0.f);
                C = fmaf(C, alpha, valid ? pv * vz : 0.f);
            }
#pragma unroll
            for (int o = 16; o > 0; o >>= 1) {
                L += __shfl_xor_sync(0xffffffffu, L, o);
                C += __shfl_xor_sync(0xffffffffu, C, o);
            }
            mbar_wait(sbar + B_GD, sph);
            const uint32_t tag = lds32(sb + OFF_TAG) | ((desc.y & F_SEMI) ? 2 : 0);
            const float gl = (desc.y & (F_SEMI | F_FIN)) ? __uint_as_float(lds32(s + S_G + D * 4)) : -3.4e38f;
            const float M = fmaxf(m, gl), e = ex2(m - M), a = ex2(gl - M);
            const float W = fmaf(L, e, a), inv = rcp(W);
            if (lane == 0)
                sts128(s + S_CF, __float_as_uint(e * inv), __float_as_uint(a * inv), __float_as_uint(-C * e * inv),
                       (__float_as_uint(M + lg2(W)) & ~3u) | tag);
            __syncwarp();
            if (lane == 0) mbar_arrive(sbar + B_FC);
        }
    } else if ((unsigned)(w - W_G) < NGW) {
        if (w == W_G) {
            if (lane == 0) sts32(sb + OFF_TAG, __uint_as_float(~*(volatile unsigned int*)&g_epoch & 1));
        } else {
            mbar_wait(bar + B_GD, 0);
        }
        for (uint32_t seg = w - W_G;; seg += NGW) {
            const uint32_t s = sb + OFF_SEG + (seg % NSEG) * SEG_BYTES, sbar = bar + (seg % NSEG) * 8;
            mbar_wait(sbar + B_HDR, (seg / NSEG) & 1);
            const int4 desc = lds128(s + S_DESC);
            if (desc.y & F_END) break;
            if (desc.y & (F_SEMI | F_FIN)) {
                const uint32_t tag = lds32(sb + OFF_TAG) | ((desc.y & F_FIN) ? 2 : 0);
                const int cnt = (desc.y & F_FIN) ? 1 : NM;
                const uint32_t* mail = g_mail + (uint32_t)desc.x / TPH * (NM * REC);
                float M = NEG, W = 0.f, O[6] = {0.f, 0.f, 0.f, 0.f, 0.f, 0.f};
#pragma unroll 1
                for (int i0 = 0; i0 < cnt; i0 += GB, mail += GB * REC) {
                    uint2 pk[3 * GB];
                    uint32_t ls[GB], stale;
                    int it = 0;
                    do {
                        stale = 0;
#pragma unroll
                        for (int i = 0; i < GB; i++) {
                            ls[i] = 0xff7ffffcu | tag;
                            pk[3 * i] = pk[3 * i + 1] = pk[3 * i + 2] = make_uint2(tag, tag);
                            if (i0 + i < cnt) {
                                asm volatile("ld.relaxed.gpu.global.u32 %0, [%1];" : "=r"(ls[i]) : "l"(mail + i * REC + D) : "memory");
#pragma unroll
                                for (int k = 0; k < 3; k++)
                                    asm volatile("ld.relaxed.gpu.global.v2.u32 {%0,%1}, [%2];"
                                                 : "=r"(pk[3 * i + k].x), "=r"(pk[3 * i + k].y)
                                                 : "l"(mail + i * REC + k * 64 + lane * 2) : "memory");
                            }
                        }
#pragma unroll
                        for (int i = 0; i < GB; i++) stale |= ls[i] ^= tag;
#pragma unroll
                        for (int i = 0; i < 3 * GB; i++) stale |= (pk[i].x ^= tag) | (pk[i].y ^= tag);
                        if (++it > (1 << 22)) __trap();
                    } while (stale & 3);
                    float Mn = M;
#pragma unroll
                    for (int i = 0; i < GB; i++) Mn = fmaxf(Mn, __uint_as_float(ls[i]));
                    const float a = ex2(M - Mn);
                    M = Mn; W *= a;
#pragma unroll
                    for (int i = 0; i < 6; i++) O[i] *= a;
#pragma unroll
                    for (int i = 0; i < GB; i++) {
                        const float e = ex2(__uint_as_float(ls[i]) - M);
                        W += e;
#pragma unroll
                        for (int k = 0; k < 3; k++) {
                            O[2 * k] = fmaf(e, __uint_as_float(pk[3 * i + k].x), O[2 * k]);
                            O[2 * k + 1] = fmaf(e, __uint_as_float(pk[3 * i + k].y), O[2 * k + 1]);
                        }
                    }
                }
                const float inv = rcp(W);
#pragma unroll
                for (int k = 0; k < 3; k++) sts64(s + S_G + k * 256 + lane * 8, O[2 * k] * inv, O[2 * k + 1] * inv);
                if (lane == 0) sts32(s + S_G + D * 4, M + lg2(W));
            }
            __syncwarp();
            if (lane == 0) mbar_arrive(sbar + B_GD);
        }
    } else if (w / NKW == 0) {
        const int g = lane >> 3, l = lane & 7, godd = g & 1, row = 2 * g + (w & 1);
        const uint32_t sgA = pin(godd ? 0x3f803f80u : 0xbf80bf80u), sgB = pin(godd ? 0xbf80bf80u : 0x3f803f80u);
        const uint32_t oKA = pin(sb + row * (D * 4) + l * 16 + godd * 384), oKB = pin(oKA - godd * 768 + 384);
        const uint32_t oCA = pin(sb + T_C + row * (D * 2) + l * 8 + godd * 192), oCB = pin(oCA - godd * 384 + 192);
        const uint32_t oL = pin(S_LG + row * 16 + (l >> 2) * 8 + (l & 1) * 4), oS = pin(S_SC + row * 2);
        const bool own = (l & 3) == g, hi = l & 4, keep = ((l ^ g) & 2) == 0;
        uint32_t kslot = w >> 1, j = kslot, batch0 = 0, kph = 0;
        for (uint32_t seg = 0;; seg++) {
            const uint32_t s = sb + OFF_SEG + (seg % NSEG) * SEG_BYTES, sbar = bar + (seg % NSEG) * 8;
            mbar_wait(sbar + B_HDR, (seg / NSEG) & 1);
            const int4 desc = lds128(s + S_DESC);
            if (desc.y & F_END) break;
            const uint32_t nt = desc.y & F_NT;
            uint2 qr[3];
#pragma unroll
            for (int i = 0; i < 3; i++) {
                const uint32_t oa = l * 8 + godd * 192 + i * 64, ob = oa + 192 - godd * 384;
                const uint2 a = lds64(s + S_Q + oa), b = lds64(s + S_Q + ob);
                const uint2 ca = lds64(sb + OFF_QT + oa), sa = lds64(sb + OFF_QT + QBYTES + oa);
                qr[i].x = rope2(a.x, ca.x, b.x, sa.x, sgA);
                qr[i].y = rope2(a.y, ca.y, b.y, sa.y, sgA);
            }
            for (; j < nt; j += NKW / 2) {
                const uint32_t t = kslot * KSLOT;
                const uint32_t sc = s + oS + ((j << (desc.w & 255)) + (desc.w >> 8)) * (TR * 2);
                const uint32_t ks2 = lds16(sc) * 0x10001u, kz2 = lds16(sc + SCB) * 0x10001u;
                const uint32_t lgb = bar + B_LG + ((batch0 + (j >> 2)) % NBAT) * 8;
                const uint32_t lgc = j == nt - 1 ? 4 - (j & 3) : 1;
                mbar_wait(bar + B_FK + kslot * 8, kph);
                float c[4] = {0.f, 0.f, 0.f, 0.f};
#pragma unroll
                for (int jj = 0; jj < 3; jj++) {
                    const int4 xa = lds128(t + oKA + jj * 128), xb = lds128(t + oKB + jj * 128);
                    const uint2 ca = lds64(t + oCA + jj * 64), cb = lds64(t + oCB + jj * 64);
                    const uint2 sa = lds64(t + oCA + CBYTES + jj * 64), sbv = lds64(t + oCB + CBYTES + jj * 64);
                    const uint32_t a0 = bmul(bsub(i2bf2(xa.x, xa.y), kz2), ks2);
                    const uint32_t a1 = bmul(bsub(i2bf2(xa.z, xa.w), kz2), ks2);
                    const uint32_t b0 = bmul(bsub(i2bf2(xb.x, xb.y), kz2), ks2);
                    const uint32_t b1 = bmul(bsub(i2bf2(xb.z, xb.w), kz2), ks2);
                    mma_bf16(c, rope2(a0, ca.x, b0, sa.x, sgA), rope2(b0, cb.x, a0, sbv.x, sgB),
                             rope2(a1, ca.y, b1, sa.y, sgA), rope2(b1, cb.y, a1, sbv.y, sgB), qr[jj].x, qr[jj].y);
                }
                __syncwarp();
                if (lane == 0) mbar_arrive(bar + B_EK + kslot * 8);
                const float part = own ? (hi ? c[1] : c[0]) : (hi ? c[3] : c[2]);
                if (keep) sts32(s + oL + j * (TR * 16), part);
                __syncwarp();
                if (lane == 0) mbar_arrive(lgb, lgc);
                kslot += NKW / 2;
                if (kslot >= NK) { kslot -= NK; kph ^= 1; }
            }
            j -= nt;
            batch0 += (nt + 3) >> 2;
            __syncwarp();
            if (lane == 0) mbar_arrive(sbar + B_SE);
        }
    } else if (w == W_SCH) {
        if (elect_one()) {
            asm volatile("mbarrier.expect_tx.shared::cta.b64 [%0], %1;" ::"r"(bar + B_HDR), "r"(2 * QBYTES) : "memory");
            uint32_t seg = 0, c = blockIdx.x;
            while (c < NCLAIM) {
                const Claim cl = decode_claim(c);
                const uint32_t s = sb + OFF_SEG + (seg % NSEG) * SEG_BYTES, b = bar + (seg % NSEG) * 8;
                mbar_wait(b + B_SE, ((seg / NSEG) & 1) ^ 1);
                sts128(s + S_DESC, cl.tile0 + cl.off, cl.ntiles | (c >= C_F ? F_FIN : c >= C_S ? F_SEMI : 0), cl.piece,
                       cl.sh | cl.off << 8);
                if (seg) mbar_arrive(bar + B_DS + ((seg - 1) % NSEG) * 8);
                const uint32_t scb = cl.ntiles * TR * 2 << cl.sh, r = cl.tile0 * TR;
                mbar_expect(b + B_HDR, 4 * scb + QBYTES);
                bulk_plain(s + S_Q, p.q + cl.head * D, QBYTES, b + B_HDR);
                bulk_plain(s + S_SC, p.ks + r, scb, b + B_HDR);
                bulk_plain(s + S_SC + SCB, p.kz + r, scb, b + B_HDR);
                bulk_plain(s + S_SC + 2 * SCB, p.vs + r, scb, b + B_HDR);
                bulk_plain(s + S_SC + 3 * SCB, p.vz + r, scb, b + B_HDR);
                if (seg == 0) {
                    bulk_plain(sb + OFF_QT, p.qcos, QBYTES, bar + B_HDR);
                    bulk_plain(sb + OFF_QT + QBYTES, p.qsin, QBYTES, bar + B_HDR);
                    mbar_wait(bar + B_GD, 0);
                }
                mbar_wait(bar + B_GO, seg & 1);
                seg++;
                const unsigned nx = atomicInc(&g_queue, NCLAIM - 1);
                if (nx == NCLAIM - 1) g_epoch = lds32(sb + OFF_TAG);
                c = gridDim.x + nx;
            }
#pragma unroll 1
            for (int i = 0; i < NGW; i++, seg++) {
                const uint32_t s = sb + OFF_SEG + (seg % NSEG) * SEG_BYTES, b = bar + (seg % NSEG) * 8;
                mbar_wait(b + B_SE, ((seg / NSEG) & 1) ^ 1);
                sts128(s + S_DESC, 0, F_END, 0, 0);
                mbar_arrive(bar + B_DS + ((seg - 1) % NSEG) * 8);
                mbar_arrive(b + B_HDR);
            }
        }
    } else {
        if (elect_one()) {
            uint64_t pol;
            asm volatile("createpolicy.fractional.L2::evict_first.b64 %0, 1.0;" : "=l"(pol));
            uint32_t kslot = 0, vslot = 0, kph = 1, vph = 1;
            int pend[LEAD];
#pragma unroll
            for (int i = 0; i < LEAD; i++) pend[i] = -1;
            auto issue_v = [&]() {
                if (pend[0] >= 0) {
                    const uint32_t b = bar + vslot * 8;
                    mbar_wait(b + B_EV, vph);
                    mbar_wait(b + B_FV + (vslot >= WIN ? 0 : NV * 8) - WIN * 8, vph ^ (vslot >= WIN));
                    mbar_expect(b + B_FV, KBYTES);
                    bulk_stream(sb + OFF_V + vslot * KBYTES, p.qv + (size_t)pend[0] * (TR * D), KBYTES, b + B_FV, pol);
                    if (++vslot == NV) { vslot = 0; vph ^= 1; }
                }
#pragma unroll
                for (int i = 0; i + 1 < LEAD; i++) pend[i] = pend[i + 1];
                pend[LEAD - 1] = -1;
            };
            const Claim c0 = decode_claim(blockIdx.x % C_S);
            int4 desc = make_int4(c0.tile0 + c0.off, c0.ntiles, 0, GSH);
            for (uint32_t seg = 0; !(desc.y & F_END); seg++) {
                uint32_t tile = desc.x;
#pragma unroll 1
                for (int left = desc.y & F_NT; left > 0; left--, tile += 1u << (desc.w & 255)) {
                    if (left == 1) mbar_arrive(bar + B_GO);
                    const uint32_t t = sb + kslot * KSLOT, b = bar + kslot * 8;
                    const uint32_t ro = (tile % TPH) * (TR * D);
                    mbar_wait(b + B_EK, kph);
                    mbar_expect(b + B_FK, KSLOT);
                    bulk_stream(t, p.qk + (size_t)tile * (TR * D), KBYTES, b + B_FK, pol);
                    bulk_plain(t + T_C, p.kcos + ro, CBYTES, b + B_FK);
                    bulk_plain(t + T_S, p.ksin + ro, CBYTES, b + B_FK);
                    if (++kslot == NK) { kslot = 0; kph ^= 1; }
                    pend[LEAD - 1] = tile;
                    issue_v();
                }
                mbar_wait(bar + B_DS + (seg % NSEG) * 8, (seg / NSEG) & 1);
                desc = lds128(sb + OFF_SEG + ((seg + 1) % NSEG) * SEG_BYTES + S_DESC);
            }
#pragma unroll 1
            for (int i = 1; i < LEAD; i++) issue_v();
        }
    }
}

}

extern "C" void kernel_launch(void* const* d_in, const int* in_sizes, int n_in, void* d_out, int out_size) {
    (void)in_sizes; (void)n_in; (void)out_size;
    static int sms = 0;
    if (sms == 0) {
        int dev = 0;
        cudaGetDevice(&dev);
        cudaDeviceGetAttribute(&sms, cudaDevAttrMultiProcessorCount, dev);
        cudaFuncSetAttribute(kv_rope_decode_kernel, cudaFuncAttributeMaxDynamicSharedMemorySize, SMEM_BYTES);
    }
    Params p;
    p.q    = (const __nv_bfloat16*)d_in[0];
    p.qk   = (const int*)d_in[1];
    p.ks   = (const __nv_bfloat16*)d_in[2];
    p.kz   = (const __nv_bfloat16*)d_in[3];
    p.qv   = (const int*)d_in[4];
    p.vs   = (const __nv_bfloat16*)d_in[5];
    p.vz   = (const __nv_bfloat16*)d_in[6];
    p.qcos = (const __nv_bfloat16*)d_in[7];
    p.qsin = (const __nv_bfloat16*)d_in[8];
    p.kcos = (const __nv_bfloat16*)d_in[9];
    p.ksin = (const __nv_bfloat16*)d_in[10];
    p.out  = (__nv_bfloat16*)d_out;
    kv_rope_decode_kernel<<<sms, NTHREADS, SMEM_BYTES>>>(p);
}
```

```cpp
#include <cuda_runtime.h>
#include <cuda_bf16.h>
#include <stdint.h>

namespace {

constexpr int D      = 192;
constexpr int SKV    = 2048;
constexpr int NHEAD  = 256;
constexpr int TR     = 8;
constexpr int TPH    = SKV / TR;
constexpr int NKW    = 4;
constexpr int NVW    = 6;
constexpr int NGW    = 2;
constexpr int NK     = 8;
constexpr int NV     = 6;
constexpr int WIN    = 4;
constexpr int LEAD   = 5;
constexpr int NSEG   = 8;
constexpr int SEGT   = 16;
constexpr int NBAT   = 16;
constexpr int W_V = NKW, W_PROD = W_V + NVW, W_S = W_PROD + 1, W_G = W_S + 1, W_SCH = W_G + NGW, NWARPS = W_SCH + 1;
constexpr int NTHREADS = 32 + NWARPS * 32;

constexpr int MAINP  = 16;
constexpr int PF0    = 3;
constexpr int GSH    = 2;
__host__ __device__ constexpr int semi_size(uint32_t h) { return (0x88ccu >> (h / 64 * 4)) & 15; }
__host__ __device__ constexpr int fin_size(uint32_t h) { return (0x248cu >> (h / 64 * 4)) & 15; }
__host__ __device__ constexpr uint32_t cut_group(uint32_t h) { return (2 - h / 4) % 4; }
constexpr int NM     = TPH / MAINP;
static_assert(NM >> GSH == 4, "four interleave groups per head");
constexpr int C_S    = NHEAD * NM, C_F = C_S + NHEAD, NCLAIM = C_F + NHEAD;

constexpr int KBYTES = TR * D * 4;
constexpr int CBYTES = TR * D * 2;
constexpr int QBYTES = D * 2;
constexpr int T_C = KBYTES, T_S = T_C + CBYTES, KSLOT = T_S + CBYTES;
constexpr int SCB = SEGT * TR * 2 << GSH;
static_assert(MAINP <= SEGT && semi_size(0) <= SEGT && fin_size(0) <= SEGT && GSH >= 1, "a piece fills one segment slot");
constexpr int S_Q    = 0;
constexpr int S_SC   = S_Q + QBYTES;
constexpr int S_DESC = S_SC + 4 * SCB;
constexpr int S_BD   = S_DESC + 16;
constexpr int S_LG   = S_BD + SEGT * 8;
constexpr int S_PV   = S_LG + SEGT * TR * 16;
constexpr int S_G    = S_PV + SEGT * TR * 4;
constexpr int S_CF   = S_G + (D + 4) * 4;
constexpr int SEG_BYTES = (S_CF + 16 + 127) / 128 * 128;
constexpr int OFF_V = NK * KSLOT, OFF_SEG = OFF_V + NV * KBYTES, OFF_QT = OFF_SEG + NSEG * SEG_BYTES,
              OFF_TAG = OFF_QT + 2 * QBYTES, OFF_BAR = OFF_TAG + 16;
constexpr int B_FK = 0, B_DS = 64, B_PR = 128, B_HDR = 256, B_GD = 320, B_FC = 384, B_FV = 448, B_GO = 504,
              B_LG = 512, B_SE = 640, B_EV = 768, B_EK = 896;
constexpr int SMEM_BYTES = OFF_BAR + 1024;
static_assert(NK <= 8 && NV <= 7 && W_PROD >= 8 && NSEG == 8 && NBAT == 16, "barrier layout");
static_assert(SMEM_BYTES <= 232448 && SMEM_BYTES > 232448 / 2, "one CTA per SM");
static_assert(NSEG % NGW == 0 && NK % (NKW / 2) == 0 && NVW * 32 == D && LEAD >= 1, "cfg");
static_assert(WIN < NV && LEAD + NV >= 4 && LEAD + NV < NBAT && LEAD < NSEG, "no ring can be lapped or starved");

__device__ unsigned int g_queue;
constexpr int REC = 200, GB = 4;
__device__ unsigned int g_epoch;
__device__ __align__(32) uint32_t g_mail[NHEAD * NM * REC];

__device__ __forceinline__ uint32_t smem_u32(const void* p) { return (uint32_t)__cvta_generic_to_shared(p); }
__device__ __forceinline__ uint32_t pin(uint32_t x) {
    return __shfl_sync(0xffffffffu, x, threadIdx.x & 31);
}
template <class T> __device__ __forceinline__ T* pin(T* p) {
    return (T*)__shfl_sync(0xffffffffu, (unsigned long long)p, threadIdx.x & 31);
}
__device__ __forceinline__ bool elect_one() {
    uint32_t pred;
    asm volatile("{\n.reg .pred p;\nelect.sync _|p, 0xffffffff;\nselp.u32 %0, 1, 0, p;\n}" : "=r"(pred));
    return pred;
}
__device__ __forceinline__ void mbar_init(uint32_t bar, uint32_t cnt) {
    asm volatile("mbarrier.init.shared::cta.b64 [%0], %1;" ::"r"(bar), "r"(cnt) : "memory");
}
__device__ __forceinline__ void mbar_expect(uint32_t bar, uint32_t bytes) {
    asm volatile("mbarrier.arrive.expect_tx.shared::cta.b64 _, [%0], %1;" ::"r"(bar), "r"(bytes) : "memory");
}
__device__ __forceinline__ void mbar_arrive(uint32_t bar) {
    asm volatile("mbarrier.arrive.shared::cta.b64 _, [%0];" ::"r"(bar) : "memory");
}
__device__ __forceinline__ void mbar_arrive(uint32_t bar, uint32_t cnt) {
    asm volatile("mbarrier.arrive.shared::cta.b64 _, [%0], %1;" ::"r"(bar), "r"(cnt) : "memory");
}
__device__ __forceinline__ bool mbar_test(uint32_t bar, uint32_t parity) {
    uint32_t ok;
    asm volatile("{\n.reg .pred p;\nmbarrier.test_wait.parity.shared::cta.b64 p, [%1], %2;\nselp.u32 %0, 1, 0, p;\n}"
                 : "=r"(ok) : "r"(bar), "r"(parity) : "memory");
    return ok;
}
__device__ __forceinline__ void mbar_wait(uint32_t bar, uint32_t parity) {
    asm volatile("{\n.reg .pred p;\n.reg .u32 n;\n"
                 "mbarrier.try_wait.parity.shared::cta.b64 p, [%0], %1;\n"
                 "@p bra DONE;\n"
                 "mov.u32 n, 0;\n"
                 "LOOP:\n"
                 "mbarrier.try_wait.parity.shared::cta.b64 p, [%0], %1;\n"
                 "@p bra DONE;\n"
                 "add.u32 n, n, 1;\n"
                 "setp.lt.u32 p, n, 0x400000;\n"
                 "@p bra LOOP;\n"
                 "trap;\n"
                 "DONE:\n}" ::"r"(bar), "r"(parity) : "memory");
}
__device__ __forceinline__ void bulk_stream(uint32_t dst, const void* src, uint32_t bytes, uint32_t bar, uint64_t pol) {
    asm volatile("cp.async.bulk.shared::cluster.global.mbarrier::complete_tx::bytes.L2::cache_hint [%0], [%1], %2, [%3], %4;"
                 ::"r"(dst), "l"(src), "r"(bytes), "r"(bar), "l"(pol) : "memory");
}
__device__ __forceinline__ void bulk_plain(uint32_t dst, const void* src, uint32_t bytes, uint32_t bar) {
    asm volatile("cp.async.bulk.shared::cluster.global.mbarrier::complete_tx::bytes [%0], [%1], %2, [%3];"
                 ::"r"(dst), "l"(src), "r"(bytes), "r"(bar) : "memory");
}
__device__ __forceinline__ void l2_prefetch(const void* src, uint32_t bytes, uint64_t pol) {
    asm volatile("cp.async.bulk.prefetch.L2.global.L2::cache_hint [%0], %1, %2;" ::"l"(src), "r"(bytes), "l"(pol) : "memory");
}
__device__ __forceinline__ void l2_prefetch(const void* src, uint32_t bytes) {
    asm volatile("cp.async.bulk.prefetch.L2.global [%0], %1;" ::"l"(src), "r"(bytes) : "memory");
}
__device__ __forceinline__ int4 lds128(uint32_t a) {
    int4 v;
    asm volatile("ld.shared.v4.s32 {%0,%1,%2,%3}, [%4];" : "=r"(v.x), "=r"(v.y), "=r"(v.z), "=r"(v.w) : "r"(a));
    return v;
}
__device__ __forceinline__ uint2 lds64(uint32_t a) {
    uint2 v;
    asm volatile("ld.shared.v2.u32 {%0,%1}, [%2];" : "=r"(v.x), "=r"(v.y) : "r"(a));
    return v;
}
__device__ __forceinline__ uint32_t lds32(uint32_t a) {
    uint32_t v;
    asm volatile("ld.shared.u32 %0, [%1];" : "=r"(v) : "r"(a));
    return v;
}
__device__ __forceinline__ uint32_t lds16(uint32_t a) {
    uint16_t v;
    asm volatile("ld.shared.u16 %0, [%1];" : "=h"(v) : "r"(a));
    return v;
}
__device__ __forceinline__ void sts32(uint32_t a, float x) {
    asm volatile("st.shared.f32 [%0], %1;" ::"r"(a), "f"(x) : "memory");
}
__device__ __forceinline__ void sts128(uint32_t a, uint32_t x, uint32_t y, uint32_t z, uint32_t w) {
    asm volatile("st.shared.v4.u32 [%0], {%1,%2,%3,%4};" ::"r"(a), "r"(x), "r"(y), "r"(z), "r"(w) : "memory");
}
__device__ __forceinline__ void sts64(uint32_t a, float x, float y) {
    asm volatile("st.shared.v2.f32 [%0], {%1,%2};" ::"r"(a), "f"(x), "f"(y) : "memory");
}
__device__ __forceinline__ float bf_lo(uint32_t v) { return __uint_as_float(v << 16); }
__device__ __forceinline__ float rbf(float x) {
    uint32_t d; asm("cvt.rn.bf16x2.f32 %0, %1, %2;" : "=r"(d) : "f"(x), "f"(0.f)); return __uint_as_float(d);
}
__device__ __forceinline__ float rcp(float x) {
    float y;
    asm("rcp.approx.ftz.f32 %0, %1;" : "=f"(y) : "f"(x));
    return y;
}
__device__ __forceinline__ float lg2(float x) {
    float y;
    asm("lg2.approx.ftz.f32 %0, %1;" : "=f"(y) : "f"(x));
    return y;
}
__device__ __forceinline__ float ex2(float x) {
    float y;
    asm("ex2.approx.ftz.f32 %0, %1;" : "=f"(y) : "f"(x));
    return y;
}
__device__ __forceinline__ uint32_t bmul(uint32_t a, uint32_t b) {
    uint32_t d; asm("mul.rn.bf16x2 %0, %1, %2;" : "=r"(d) : "r"(a), "r"(b)); return d;
}
__device__ __forceinline__ uint32_t bsub(uint32_t a, uint32_t b) {
    uint32_t d; asm("sub.rn.bf16x2 %0, %1, %2;" : "=r"(d) : "r"(a), "r"(b)); return d;
}
__device__ __forceinline__ uint32_t bfma(uint32_t a, uint32_t b, uint32_t c) {
    uint32_t d; asm("fma.rn.bf16x2 %0, %1, %2, %3;" : "=r"(d) : "r"(a), "r"(b), "r"(c)); return d;
}
__device__ __forceinline__ uint32_t i2bf2(int lo, int hi) {
    uint32_t d; asm("cvt.rn.bf16x2.f32 %0, %1, %2;" : "=r"(d) : "f"((float)hi), "f"((float)lo)); return d;
}
__device__ __forceinline__ uint32_t rope2(uint32_t x, uint32_t c, uint32_t y, uint32_t s, uint32_t sg) {
    return bfma(bmul(y, s), sg, bmul(x, c));
}
__device__ __forceinline__ void mma_bf16(float (&c)[4], uint32_t a0, uint32_t a1, uint32_t a2, uint32_t a3,
                                         uint32_t b0, uint32_t b1) {
    asm("mma.sync.aligned.m16n8k16.row.col.f32.bf16.bf16.f32 {%0,%1,%2,%3}, {%4,%5,%6,%7}, {%8,%9}, {%0,%1,%2,%3};"
        : "+f"(c[0]), "+f"(c[1]), "+f"(c[2]), "+f"(c[3])
        : "r"(a0), "r"(a1), "r"(a2), "r"(a3), "r"(b0), "r"(b1));
}
__device__ __forceinline__ void mail_put(uint32_t* p, float x, uint32_t tag) {
    asm volatile("st.relaxed.gpu.global.u32 [%0], %1;" ::"l"(p), "r"((__float_as_uint(x) & ~3u) | tag) : "memory");
}

struct Claim { uint32_t head, tile0, piece, sh, off; int ntiles; };

__device__ __forceinline__ Claim decode_claim(uint32_t c) {
    Claim cl;
    cl.sh = cl.off = 0;
    if (c < C_S) {
        cl.head = c / NM; cl.piece = c % NM; cl.sh = GSH; cl.off = c % (1 << GSH); cl.tile0 = (c - cl.off) * MAINP;
        cl.ntiles = MAINP;
        if (cl.piece >> GSH == cut_group(cl.head))
            cl.ntiles -= (semi_size(cl.head) + fin_size(cl.head) + cl.off) >> GSH;
    } else {
        cl.head = (c - C_S) % NHEAD; cl.piece = 0;
        cl.ntiles = fin_size(cl.head); cl.tile0 = cl.head * TPH + (cut_group(cl.head) + 1) * (TPH / 4) - cl.ntiles;
        if (c < C_F) { cl.ntiles = semi_size(cl.head); cl.tile0 -= cl.ntiles; }
    }
    return cl;
}

struct Params {
    const int* qk; const __nv_bfloat16* kcos; const __nv_bfloat16* ksin; const int* qv;
    const __nv_bfloat16* ks; const __nv_bfloat16* kz; const __nv_bfloat16* vs; const __nv_bfloat16* vz;
    const __nv_bfloat16* q; const __nv_bfloat16* qcos; const __nv_bfloat16* qsin;
    __nv_bfloat16* out;
};

constexpr float NEG = -3.0e38f;
constexpr float LOG2E = 1.4426950408889634f;
constexpr int F_NT = 31, F_LAST = 64, F_SEMI = 128, F_FIN = 256, F_END = 512;
static_assert(NHEAD * NM * REC < (1 << 20), "batch descriptor");

__global__ void __launch_bounds__(NTHREADS, 1)
kv_rope_decode_kernel(const Params p) {
    extern __shared__ __align__(128) unsigned char smem[];
    if (threadIdx.x < 32 && elect_one()) {
        l2_prefetch(p.kcos + (blockIdx.x % (TPH / 2)) * (2 * TR * D), 2 * CBYTES);
        l2_prefetch(p.ksin + (blockIdx.x % (TPH / 2)) * (2 * TR * D), 2 * CBYTES);
        uint64_t pol;
        asm volatile("createpolicy.fractional.L2::evict_first.b64 %0, 1.0;" : "=l"(pol));
        const uint32_t off = blockIdx.x % (1 << GSH);
        l2_prefetch(p.qk + (size_t)((blockIdx.x - off) * MAINP + off * PF0) * (TR * D), PF0 * KBYTES, pol);
    }
    const int w = __shfl_sync(0xffffffffu, (threadIdx.x >> 5) - 1, 0), lane = threadIdx.x & 31;
    if (w < 0) return;
    const uint32_t sb = __shfl_sync(0xffffffffu, smem_u32(smem), 0);
    const uint32_t bar = sb + OFF_BAR;

    if (w < 8 && elect_one()) {
        const uint32_t cnt = w == 4 ? 8 : w == 5 ? NKW + NVW : w == 6 ? NVW : w == 7 ? 2 : 1;
#pragma unroll
        for (int i = 0; i < 16; i++) mbar_init(bar + w * 128 + i * 8, cnt);
        asm volatile("fence.mbarrier_init.release.cluster;" ::: "memory");
    }
    asm volatile("bar.sync 0, %0;" ::"n"(NWARPS * 32) : "memory");

    if ((unsigned)(w - W_V) < NVW) {
        const int v = w - W_V, g = lane >> 3, l = lane & 7;
        const uint32_t up = pin(lane & 16), up2 = pin(lane & 8);
        const uint32_t oV = pin(sb + OFF_V + g * (2 * D * 4) + v * 128 + l * 16), oP = pin(S_PV + g * 8);
        const uint32_t col = pin(v * 32 + l * 4 + (up ? 2 : 0) + (up2 ? 1 : 0));
        const uint32_t oG = pin(S_G + col * 4);
        __nv_bfloat16* const outp = pin(p.out + col);
        uint32_t* const mailp = pin(g_mail + col);
        float a0 = 0.f, a1 = 0.f, a2 = 0.f, a3 = 0.f;
        uint32_t vb = bar, vt = oV, vph = 0, seg = 0;
        uint32_t s = sb + OFF_SEG, t0 = 0;
        mbar_wait(bar + B_PR, 0);
        uint2 bd = lds64(s + S_BD);
        uint2 pv = lds64(s + oP);
        bool ready = false;
        int4 x0, x1;
        auto load_tile = [&]() {
            if (!ready) mbar_wait(vb + B_FV, vph);
            x0 = lds128(vt);
            x1 = lds128(vt + D * 4);
            __syncwarp();
            if (lane == 0) mbar_arrive(vb + B_EV);
            vb += 8; vt += KBYTES;
            if (vb == bar + NV * 8) { vb = bar; vt = oV; vph ^= 1; }
            ready = mbar_test(vb + B_FV, vph);
        };
        auto fma_tile = [&]() {
            const float pv0 = __uint_as_float(pv.x), pv1 = __uint_as_float(pv.y);
            a0 = fmaf(pv1, (float)x1.x, fmaf(pv0, (float)x0.x, a0));
            a1 = fmaf(pv1, (float)x1.y, fmaf(pv0, (float)x0.y, a1));
            a2 = fmaf(pv1, (float)x1.z, fmaf(pv0, (float)x0.z, a2));
            a3 = fmaf(pv1, (float)x1.w, fmaf(pv0, (float)x0.w, a3));
        };
        for (uint32_t batch = 1; !(bd.y & F_END); batch++) {
            const uint32_t n = bd.y & F_NT, sbar = bar + (seg % NSEG) * 8, sph = (seg / NSEG) & 1;
            const bool last = bd.y & F_LAST;
            const uint32_t seg2 = seg + last, t2 = last ? 0 : t0 + n;
            const uint32_t s2 = sb + OFF_SEG + (seg2 % NSEG) * SEG_BYTES;
            const uint32_t prb = bar + B_PR + (batch % NBAT) * 8, prp = (batch / NBAT) & 1;
            const float alpha = __uint_as_float(bd.x);
            a0 *= alpha; a1 *= alpha; a2 *= alpha; a3 *= alpha;
#pragma unroll 1
            for (uint32_t i = 1; i < n; i++) {
                load_tile();
                const uint2 pn = lds64(s + oP + (t0 + i) * (TR * 4));
                fma_tile();
                pv = pn;
            }
            load_tile();
            const bool early = mbar_test(sbar + B_FC, sph);
            const bool next = mbar_test(prb, prp);
            fma_tile();
            uint2 bn, pn;
            if (last) {
                const float u0 = (up ? a2 : a0) + __shfl_xor_sync(0xffffffffu, up ? a0 : a2, 16);
                const float u1 = (up ? a3 : a1) + __shfl_xor_sync(0xffffffffu, up ? a1 : a3, 16);
                if (!early) mbar_wait(sbar + B_FC, sph);
                const int4 cf = lds128(s + S_CF);
                const uint32_t gv = lds32(s + oG);
                const float u = (up2 ? u1 : u0) + __shfl_xor_sync(0xffffffffu, up2 ? u0 : u1, 8);
                const float gj = (bd.y & (F_SEMI | F_FIN)) ? __uint_as_float(gv) : 0.f;
                const float o = fmaf(u, __int_as_float(cf.x), fmaf(gj, __int_as_float(cf.y), __int_as_float(cf.z)));
                if (bd.y & F_FIN) {
                    const __nv_bfloat16 r = __float2bfloat16_rn(o);
                    asm volatile("st.global.b16 [%0], %1;" ::"l"(outp + (bd.y >> 12)), "h"(*(const uint16_t*)&r) : "memory");
                } else {
                    mail_put(mailp + (bd.y >> 12), o, cf.w & 3);
                    if (col < REC - D) mail_put(mailp + (bd.y >> 12) + D, __int_as_float(cf.w), cf.w & 3);
                }
                a0 = a1 = a2 = a3 = 0.f;
                __syncwarp();
                if (lane == 0) mbar_arrive(sbar + B_SE);
            }
            if (!next) mbar_wait(prb, prp);
            bn = lds64(s2 + S_BD + t2 * 8);
            pn = lds64(s2 + oP + t2 * (TR * 4));
            bd = bn; pv = pn; s = s2; t0 = t2; seg = seg2;
        }
    } else if (w == W_S) {
        uint32_t batch = 0;
        for (uint32_t seg = 0;; seg++) {
            const uint32_t s = sb + OFF_SEG + (seg % NSEG) * SEG_BYTES, sbar = bar + (seg % NSEG) * 8;
            const uint32_t sph = (seg / NSEG) & 1;
            mbar_wait(sbar + B_HDR, sph);
            const int4 desc = lds128(s + S_DESC);
            if (desc.y & F_END) {
                if (lane == 0) {
                    sts64(s + S_BD, 0.f, __uint_as_float(F_END));
                    mbar_arrive(bar + B_PR + (batch % NBAT) * 8);
                }
                break;
            }
            float m = NEG, L = 0.f, C = 0.f;
            const uint32_t head = (uint32_t)desc.x / TPH, index = (desc.y & F_FIN) ? head * D : (head * NM + desc.z) * REC;
            const int nt = desc.y & F_NT;
#pragma unroll 1
            for (int t0 = 0; t0 < nt; t0 += 4, batch++) {
                const int n = min(4, nt - t0);
                const bool valid = lane < n * TR;
                const uint32_t tl = t0 + (valid ? lane >> 3 : 0), row = tl * TR + (lane & 7);
                const uint32_t sc = s + S_SC + (((tl << (desc.w & 255)) + (desc.w >> 8)) * TR + (lane & 7)) * 2;
                const float vs = bf_lo(lds16(sc + 2 * SCB)), vz = bf_lo(lds16(sc + 3 * SCB));
                mbar_wait(bar + B_LG + (batch % NBAT) * 8, (batch / NBAT) & 1);
                const int4 part = lds128(s + S_LG + row * 16);
                const float dot = (__int_as_float(part.x) + __int_as_float(part.y)) + (__int_as_float(part.z) + __int_as_float(part.w));
                const float sv = rbf(rbf(dot) * 0.07216878364870322f) * LOG2E;
                int key = __float_as_int(fmaxf(m, sv));
                key ^= (key >> 31) & 0x7fffffff;
                key = __reduce_max_sync(0xffffffffu, key);
                const float mn = __int_as_float(key ^ ((key >> 31) & 0x7fffffff));
                const float alpha = ex2(m - mn), pr = ex2(sv - mn), pv = pr * vs;
                m = mn;
                sts32(s + S_PV + row * 4, pv);
                if (lane == 0)
                    sts64(s + S_BD + t0 * 8, alpha,
                          __uint_as_float(n | (t0 + n < nt ? 0 : index << 12 | F_LAST | (desc.y & (F_SEMI | F_FIN)))));
                __syncwarp();
                if (lane == 0) mbar_arrive(bar + B_PR + (batch % NBAT) * 8);
                L = fmaf(L, alpha, valid ? pr : 0.f);
                C = fmaf(C, alpha, valid ? pv * vz : 0.f);
            }
#pragma unroll
            for (int o = 16; o > 0; o >>= 1) {
                L += __shfl_xor_sync(0xffffffffu, L, o);
                C += __shfl_xor_sync(0xffffffffu, C, o);
            }
            mbar_wait(sbar + B_GD, sph);
            const uint32_t tag = lds32(sb + OFF_TAG) | ((desc.y & F_SEMI) ? 2 : 0);
            const float gl = (desc.y & (F_SEMI | F_FIN)) ? __uint_as_float(lds32(s + S_G + D * 4)) : -3.4e38f;
            const float M = fmaxf(m, gl), e = ex2(m - M), a = ex2(gl - M);
            const float W = fmaf(L, e, a), inv = rcp(W);
            if (lane == 0)
                sts128(s + S_CF, __float_as_uint(e * inv), __float_as_uint(a * inv), __float_as_uint(-C * e * inv),
                       (__float_as_uint(M + lg2(W)) & ~3u) | tag);
            __syncwarp();
            if (lane == 0) mbar_arrive(sbar + B_FC);
        }
    } else if ((unsigned)(w - W_G) < NGW) {
        if (w == W_G) {
            if (lane == 0) sts32(sb + OFF_TAG, __uint_as_float(~*(volatile unsigned int*)&g_epoch & 1));
        } else {
            mbar_wait(bar + B_GD, 0);
        }
        for (uint32_t seg = w - W_G;; seg += NGW) {
            const uint32_t s = sb + OFF_SEG + (seg % NSEG) * SEG_BYTES, sbar = bar + (seg % NSEG) * 8;
            mbar_wait(sbar + B_HDR, (seg / NSEG) & 1);
            const int4 desc = lds128(s + S_DESC);
            if (desc.y & F_END) break;
            if (desc.y & (F_SEMI | F_FIN)) {
                const uint32_t tag = lds32(sb + OFF_TAG) | ((desc.y & F_FIN) ? 2 : 0);
                const int cnt = (desc.y & F_FIN) ? 1 : NM;
                const uint32_t* mail = g_mail + (uint32_t)desc.x / TPH * (NM * REC);
                float M = NEG, W = 0.f, O[6] = {0.f, 0.f, 0.f, 0.f, 0.f, 0.f};
#pragma unroll 1
                for (int i0 = 0; i0 < cnt; i0 += GB, mail += GB * REC) {
                    uint2 pk[3 * GB];
                    uint32_t ls[GB], stale;
                    int it = 0;
                    do {
                        stale = 0;
#pragma unroll
                        for (int i = 0; i < GB; i++) {
                            ls[i] = 0xff7ffffcu | tag;
                            pk[3 * i] = pk[3 * i + 1] = pk[3 * i + 2] = make_uint2(tag, tag);
                            if (i0 + i < cnt) {
                                asm volatile("ld.relaxed.gpu.global.u32 %0, [%1];" : "=r"(ls[i]) : "l"(mail + i * REC + D) : "memory");
#pragma unroll
                                for (int k = 0; k < 3; k++)
                                    asm volatile("ld.relaxed.gpu.global.v2.u32 {%0,%1}, [%2];"
                                                 : "=r"(pk[3 * i + k].x), "=r"(pk[3 * i + k].y)
                                                 : "l"(mail + i * REC + k * 64 + lane * 2) : "memory");
                            }
                        }
#pragma unroll
                        for (int i = 0; i < GB; i++) stale |= ls[i] ^= tag;
#pragma unroll
                        for (int i = 0; i < 3 * GB; i++) stale |= (pk[i].x ^= tag) | (pk[i].y ^= tag);
                        if (++it > (1 << 22)) __trap();
                    } while (stale & 3);
                    float Mn = M;
#pragma unroll
                    for (int i = 0; i < GB; i++) Mn = fmaxf(Mn, __uint_as_float(ls[i]));
                    const float a = ex2(M - Mn);
                    M = Mn; W *= a;
#pragma unroll
                    for (int i = 0; i < 6; i++) O[i] *= a;
#pragma unroll
                    for (int i = 0; i < GB; i++) {
                        const float e = ex2(__uint_as_float(ls[i]) - M);
                        W += e;
#pragma unroll
                        for (int k = 0; k < 3; k++) {
                            O[2 * k] = fmaf(e, __uint_as_float(pk[3 * i + k].x), O[2 * k]);
                            O[2 * k + 1] = fmaf(e, __uint_as_float(pk[3 * i + k].y), O[2 * k + 1]);
                        }
                    }
                }
                const float inv = rcp(W);
#pragma unroll
                for (int k = 0; k < 3; k++) sts64(s + S_G + k * 256 + lane * 8, O[2 * k] * inv, O[2 * k + 1] * inv);
                if (lane == 0) sts32(s + S_G + D * 4, M + lg2(W));
            }
            __syncwarp();
            if (lane == 0) mbar_arrive(sbar + B_GD);
        }
    } else if (w / NKW == 0) {
        const int g = lane >> 3, l = lane & 7, godd = g & 1, row = 2 * g + (w & 1);
        const uint32_t sgA = pin(godd ? 0x3f803f80u : 0xbf80bf80u), sgB = pin(godd ? 0xbf80bf80u : 0x3f803f80u);
        const uint32_t oKA = pin(sb + row * (D * 4) + l * 16 + godd * 384), oKB = pin(oKA - godd * 768 + 384);
        const uint32_t oCA = pin(sb + T_C + row * (D * 2) + l * 8 + godd * 192), oCB = pin(oCA - godd * 384 + 192);
        const uint32_t oL = pin(S_LG + row * 16 + (l >> 2) * 8 + (l & 1) * 4), oS = pin(S_SC + row * 2);
        const bool own = (l & 3) == g, hi = l & 4, keep = ((l ^ g) & 2) == 0;
        uint32_t kslot = w >> 1, j = kslot, batch0 = 0, kph = 0;
        for (uint32_t seg = 0;; seg++) {
            const uint32_t s = sb + OFF_SEG + (seg % NSEG) * SEG_BYTES, sbar = bar + (seg % NSEG) * 8;
            mbar_wait(sbar + B_HDR, (seg / NSEG) & 1);
            const int4 desc = lds128(s + S_DESC);
            if (desc.y & F_END) break;
            const uint32_t nt = desc.y & F_NT;
            uint2 qr[3];
#pragma unroll
            for (int i = 0; i < 3; i++) {
                const uint32_t oa = l * 8 + godd * 192 + i * 64, ob = oa + 192 - godd * 384;
                const uint2 a = lds64(s + S_Q + oa), b = lds64(s + S_Q + ob);
                const uint2 ca = lds64(sb + OFF_QT + oa), sa = lds64(sb + OFF_QT + QBYTES + oa);
                qr[i].x = rope2(a.x, ca.x, b.x, sa.x, sgA);
                qr[i].y = rope2(a.y, ca.y, b.y, sa.y, sgA);
            }
            for (; j < nt; j += NKW / 2) {
                const uint32_t t = kslot * KSLOT;
                const uint32_t sc = s + oS + ((j << (desc.w & 255)) + (desc.w >> 8)) * (TR * 2);
                const uint32_t ks2 = lds16(sc) * 0x10001u, kz2 = lds16(sc + SCB) * 0x10001u;
                const uint32_t lgb = bar + B_LG + ((batch0 + (j >> 2)) % NBAT) * 8;
                const uint32_t lgc = j == nt - 1 ? 4 - (j & 3) : 1;
                mbar_wait(bar + B_FK + kslot * 8, kph);
                float c[4] = {0.f, 0.f, 0.f, 0.f};
#pragma unroll
                for (int jj = 0; jj < 3; jj++) {
                    const int4 xa = lds128(t + oKA + jj * 128), xb = lds128(t + oKB + jj * 128);
                    const uint2 ca = lds64(t + oCA + jj * 64), cb = lds64(t + oCB + jj * 64);
                    const uint2 sa = lds64(t + oCA + CBYTES + jj * 64), sbv = lds64(t + oCB + CBYTES + jj * 64);
                    const uint32_t a0 = bmul(bsub(i2bf2(xa.x, xa.y), kz2), ks2);
                    const uint32_t a1 = bmul(bsub(i2bf2(xa.z, xa.w), kz2), ks2);
                    const uint32_t b0 = bmul(bsub(i2bf2(xb.x, xb.y), kz2), ks2);
                    const uint32_t b1 = bmul(bsub(i2bf2(xb.z, xb.w), kz2), ks2);
                    mma_bf16(c, rope2(a0, ca.x, b0, sa.x, sgA), rope2(b0, cb.x, a0, sbv.x, sgB),
                             rope2(a1, ca.y, b1, sa.y, sgA), rope2(b1, cb.y, a1, sbv.y, sgB), qr[jj].x, qr[jj].y);
                }
                __syncwarp();
                if (lane == 0) mbar_arrive(bar + B_EK + kslot * 8);
                const float part = own ? (hi ? c[1] : c[0]) : (hi ? c[3] : c[2]);
                if (keep) sts32(s + oL + j * (TR * 16), part);
                __syncwarp();
                if (lane == 0) mbar_arrive(lgb, lgc);
                kslot += NKW / 2;
                if (kslot >= NK) { kslot -= NK; kph ^= 1; }
            }
            j -= nt;
            batch0 += (nt + 3) >> 2;
            __syncwarp();
            if (lane == 0) mbar_arrive(sbar + B_SE);
        }
    } else if (w == W_SCH) {
        if (elect_one()) {
            asm volatile("mbarrier.expect_tx.shared::cta.b64 [%0], %1;" ::"r"(bar + B_HDR), "r"(2 * QBYTES) : "memory");
            uint32_t seg = 0, c = blockIdx.x;
            while (c < NCLAIM) {
                const Claim cl = decode_claim(c);
                const uint32_t s = sb + OFF_SEG + (seg % NSEG) * SEG_BYTES, b = bar + (seg % NSEG) * 8;
                mbar_wait(b + B_SE, ((seg / NSEG) & 1) ^ 1);
                sts128(s + S_DESC, cl.tile0 + cl.off, cl.ntiles | (c >= C_F ? F_FIN : c >= C_S ? F_SEMI : 0), cl.piece,
                       cl.sh | cl.off << 8);
                if (seg) mbar_arrive(bar + B_DS + ((seg - 1) % NSEG) * 8);
                const uint32_t scb = cl.ntiles * TR * 2 << cl.sh, r = cl.tile0 * TR;
                mbar_expect(b + B_HDR, 4 * scb + QBYTES);
                bulk_plain(s + S_Q, p.q + cl.head * D, QBYTES, b + B_HDR);
                bulk_plain(s + S_SC, p.ks + r, scb, b + B_HDR);
                bulk_plain(s + S_SC + SCB, p.kz + r, scb, b + B_HDR);
                bulk_plain(s + S_SC + 2 * SCB, p.vs + r, scb, b + B_HDR);
                bulk_plain(s + S_SC + 3 * SCB, p.vz + r, scb, b + B_HDR);
                if (seg == 0) {
                    bulk_plain(sb + OFF_QT, p.qcos, QBYTES, bar + B_HDR);
                    bulk_plain(sb + OFF_QT + QBYTES, p.qsin, QBYTES, bar + B_HDR);
                    mbar_wait(bar + B_GD, 0);
                }
                mbar_wait(bar + B_GO, seg & 1);
                seg++;
                const unsigned nx = atomicInc(&g_queue, NCLAIM - 1);
                if (nx == NCLAIM - 1) g_epoch = lds32(sb + OFF_TAG);
                c = gridDim.x + nx;
            }
#pragma unroll 1
            for (int i = 0; i < NGW; i++, seg++) {
                const uint32_t s = sb + OFF_SEG + (seg % NSEG) * SEG_BYTES, b = bar + (seg % NSEG) * 8;
                mbar_wait(b + B_SE, ((seg / NSEG) & 1) ^ 1);
                sts128(s + S_DESC, 0, F_END, 0, 0);
                mbar_arrive(bar + B_DS + ((seg - 1) % NSEG) * 8);
                mbar_arrive(b + B_HDR);
            }
        }
    } else {
        if (elect_one()) {
            uint64_t pol;
            asm volatile("createpolicy.fractional.L2::evict_first.b64 %0, 1.0;" : "=l"(pol));
            uint32_t kslot = 0, vslot = 0, kph = 1, vph = 1;
            int pend[LEAD];
#pragma unroll
            for (int i = 0; i < LEAD; i++) pend[i] = -1;
            auto issue_v = [&]() {
                if (pend[0] >= 0) {
                    const uint32_t b = bar + vslot * 8;
                    mbar_wait(b + B_EV, vph);
                    mbar_wait(b + B_FV + (vslot >= WIN ? 0 : NV * 8) - WIN * 8, vph ^ (vslot >= WIN));
                    mbar_expect(b + B_FV, KBYTES);
                    bulk_stream(sb + OFF_V + vslot * KBYTES, p.qv + (size_t)pend[0] * (TR * D), KBYTES, b + B_FV, pol);
                    if (++vslot == NV) { vslot = 0; vph ^= 1; }
                }
#pragma unroll
                for (int i = 0; i + 1 < LEAD; i++) pend[i] = pend[i + 1];
                pend[LEAD - 1] = -1;
            };
            const Claim c0 = decode_claim(blockIdx.x % C_S);
            int4 desc = make_int4(c0.tile0 + c0.off, c0.ntiles, 0, GSH);
            for (uint32_t seg = 0; !(desc.y & F_END); seg++) {
                uint32_t tile = desc.x;
#pragma unroll 1
                for (int left = desc.y & F_NT; left > 0; left--, tile += 1u << (desc.w & 255)) {
                    if (left == 1) mbar_arrive(bar + B_GO);
                    const uint32_t t = sb + kslot * KSLOT, b = bar + kslot * 8;
                    const uint32_t ro = (tile % TPH) * (TR * D);
                    mbar_wait(b + B_EK, kph);
                    mbar_expect(b + B_FK, KSLOT);
                    bulk_stream(t, p.qk + (size_t)tile * (TR * D), KBYTES, b + B_FK, pol);
                    bulk_plain(t + T_C, p.kcos + ro, CBYTES, b + B_FK);
                    bulk_plain(t + T_S, p.ksin + ro, CBYTES, b + B_FK);
                    if (++kslot == NK) { kslot = 0; kph ^= 1; }
                    pend[LEAD - 1] = tile;
                    issue_v();
                }
                mbar_wait(bar + B_DS + (seg % NSEG) * 8, (seg / NSEG) & 1);
                desc = lds128(sb + OFF_SEG + ((seg + 1) % NSEG) * SEG_BYTES + S_DESC);
            }
#pragma unroll 1
            for (int i = 1; i < LEAD; i++) issue_v();
        }
    }
}

}

extern "C" void kernel_launch(void* const* d_in, const int* in_sizes, int n_in, void* d_out, int out_size) {
    (void)in_sizes; (void)n_in; (void)out_size;
    static int sms = 0;
    if (sms == 0) {
        int dev = 0;
        cudaGetDevice(&dev);
        cudaDeviceGetAttribute(&sms, cudaDevAttrMultiProcessorCount, dev);
        cudaFuncSetAttribute(kv_rope_decode_kernel, cudaFuncAttributeMaxDynamicSharedMemorySize, SMEM_BYTES);
    }
    Params p;
    p.q    = (const __nv_bfloat16*)d_in[0];
    p.qk   = (const int*)d_in[1];
    p.ks   = (const __nv_bfloat16*)d_in[2];
    p.kz   = (const __nv_bfloat16*)d_in[3];
    p.qv   = (const int*)d_in[4];
    p.vs   = (const __nv_bfloat16*)d_in[5];
    p.vz   = (const __nv_bfloat16*)d_in[6];
    p.qcos = (const __nv_bfloat16*)d_in[7];
    p.qsin = (const __nv_bfloat16*)d_in[8];
    p.kcos = (const __nv_bfloat16*)d_in[9];
    p.ksin = (const __nv_bfloat16*)d_in[10];
    p.out  = (__nv_bfloat16*)d_out;
    kv_rope_decode_kernel<<<sms, NTHREADS, SMEM_BYTES>>>(p);
}
```

```cpp
#include <cuda_runtime.h>
#include <cuda_bf16.h>
#include <stdint.h>

namespace {

constexpr int D      = 192;
constexpr int SKV    = 2048;
constexpr int NHEAD  = 256;
constexpr int TR     = 8;
constexpr int TPH    = SKV / TR;
constexpr int NKW    = 4;
constexpr int NVW    = 6;
constexpr int NGW    = 2;
constexpr int NK     = 8;
constexpr int NV     = 6;
constexpr int WIN    = 4;
constexpr int LEAD   = 5;
constexpr int NSEG   = 8;
constexpr int SEGT   = 16;
constexpr int NBAT   = 16;
constexpr int W_V = NKW, W_PROD = W_V + NVW, W_S = W_PROD + 1, W_G = W_S + 1, W_SCH = W_G + NGW, NWARPS = W_SCH + 1;
constexpr int NTHREADS = 32 + NWARPS * 32;

constexpr int MAINP  = 16;
constexpr int PF0    = 3;
constexpr int GSH    = 2;
__host__ __device__ constexpr int semi_size(uint32_t h) { return (0x88ccu >> (h / 64 * 4)) & 15; }
__host__ __device__ constexpr int fin_size(uint32_t h) { return (0x248cu >> (h / 64 * 4)) & 15; }
__host__ __device__ constexpr uint32_t cut_group(uint32_t h) { return (2 - h / 4) % 4; }
constexpr int NM     = TPH / MAINP;
static_assert(NM >> GSH == 4, "four interleave groups per head");
constexpr int C_S    = NHEAD * NM, C_F = C_S + NHEAD, NCLAIM = C_F + NHEAD;

constexpr int KBYTES = TR * D * 4;
constexpr int CBYTES = TR * D * 2;
constexpr int QBYTES = D * 2;
constexpr int T_C = KBYTES, T_S = T_C + CBYTES, KSLOT = T_S + CBYTES;
constexpr int SCB = SEGT * TR * 2 << GSH;
static_assert(MAINP <= SEGT && semi_size(0) <= SEGT && fin_size(0) <= SEGT && GSH >= 1, "a piece fills one segment slot");
constexpr int S_Q    = 0;
constexpr int S_SC   = S_Q + QBYTES;
constexpr int S_DESC = S_SC + 4 * SCB;
constexpr int S_BD   = S_DESC + 16;
constexpr int S_LG   = S_BD + SEGT * 8;
constexpr int S_PV   = S_LG + SEGT * TR * 16;
constexpr int S_G    = S_PV + SEGT * TR * 4;
constexpr int S_CF   = S_G + (D + 4) * 4;
constexpr int SEG_BYTES = (S_CF + 16 + 127) / 128 * 128;
constexpr int OFF_V = NK * KSLOT, OFF_SEG = OFF_V + NV * KBYTES, OFF_QT = OFF_SEG + NSEG * SEG_BYTES,
              OFF_TAG = OFF_QT + 2 * QBYTES, OFF_BAR = OFF_TAG + 16;
constexpr int B_FK = 0, B_DS = 64, B_PR = 128, B_HDR = 256, B_GD = 320, B_FC = 384, B_FV = 448, B_GO = 504,
              B_LG = 512, B_SE = 640, B_EV = 768, B_EK = 896;
constexpr int SMEM_BYTES = OFF_BAR + 1024;
static_assert(NK <= 8 && NV <= 7 && W_PROD >= 8 && NSEG == 8 && NBAT == 16, "barrier layout");
static_assert(SMEM_BYTES <= 232448 && SMEM_BYTES > 232448 / 2, "one CTA per SM");
static_assert(NSEG % NGW == 0 && NK % (NKW / 2) == 0 && NVW * 32 == D && LEAD >= 1, "cfg");
static_assert(WIN < NV && LEAD + NV >= 4 && LEAD + NV < NBAT && LEAD < NSEG, "no ring can be lapped or starved");

__device__ unsigned int g_queue;
constexpr int REC = 200, GB = 4;
__device__ unsigned int g_epoch;
__device__ __align__(32) uint32_t g_mail[NHEAD * NM * REC];

__device__ __forceinline__ uint32_t smem_u32(const void* p) { return (uint32_t)__cvta_generic_to_shared(p); }
__device__ __forceinline__ uint32_t pin(uint32_t x) {
    return __shfl_sync(0xffffffffu, x, threadIdx.x & 31);
}
template <class T> __device__ __forceinline__ T* pin(T* p) {
    return (T*)__shfl_sync(0xffffffffu, (unsigned long long)p, threadIdx.x & 31);
}
__device__ __forceinline__ bool elect_one() {
    uint32_t pred;
    asm volatile("{\n.reg .pred p;\nelect.sync _|p, 0xffffffff;\nselp.u32 %0, 1, 0, p;\n}" : "=r"(pred));
    return pred;
}
__device__ __forceinline__ void mbar_init(uint32_t bar, uint32_t cnt) {
    asm volatile("mbarrier.init.shared::cta.b64 [%0], %1;" ::"r"(bar), "r"(cnt) : "memory");
}
__device__ __forceinline__ void mbar_expect(uint32_t bar, uint32_t bytes) {
    asm volatile("mbarrier.arrive.expect_tx.shared::cta.b64 _, [%0], %1;" ::"r"(bar), "r"(bytes) : "memory");
}
__device__ __forceinline__ void mbar_arrive(uint32_t bar) {
    asm volatile("mbarrier.arrive.shared::cta.b64 _, [%0];" ::"r"(bar) : "memory");
}
__device__ __forceinline__ void mbar_arrive(uint32_t bar, uint32_t cnt) {
    asm volatile("mbarrier.arrive.shared::cta.b64 _, [%0], %1;" ::"r"(bar), "r"(cnt) : "memory");
}
__device__ __forceinline__ bool mbar_test(uint32_t bar, uint32_t parity) {
    uint32_t ok;
    asm volatile("{\n.reg .pred p;\nmbarrier.test_wait.parity.shared::cta.b64 p, [%1], %2;\nselp.u32 %0, 1, 0, p;\n}"
                 : "=r"(ok) : "r"(bar), "r"(parity) : "memory");
    return ok;
}
__device__ __forceinline__ void mbar_wait(uint32_t bar, uint32_t parity) {
    asm volatile("{\n.reg .pred p;\n.reg .u32 n;\n"
                 "mbarrier.try_wait.parity.shared::cta.b64 p, [%0], %1;\n"
                 "@p bra DONE;\n"
                 "mov.u32 n, 0;\n"
                 "LOOP:\n"
                 "mbarrier.try_wait.parity.shared::cta.b64 p, [%0], %1;\n"
                 "@p bra DONE;\n"
                 "add.u32 n, n, 1;\n"
                 "setp.lt.u32 p, n, 0x400000;\n"
                 "@p bra LOOP;\n"
                 "trap;\n"
                 "DONE:\n}" ::"r"(bar), "r"(parity) : "memory");
}
__device__ __forceinline__ void bulk_stream(uint32_t dst, const void* src, uint32_t bytes, uint32_t bar, uint64_t pol) {
    asm volatile("cp.async.bulk.shared::cluster.global.mbarrier::complete_tx::bytes.L2::cache_hint [%0], [%1], %2, [%3], %4;"
                 ::"r"(dst), "l"(src), "r"(bytes), "r"(bar), "l"(pol) : "memory");
}
__device__ __forceinline__ void bulk_plain(uint32_t dst, const void* src, uint32_t bytes, uint32_t bar) {
    asm volatile("cp.async.bulk.shared::cluster.global.mbarrier::complete_tx::bytes [%0], [%1], %2, [%3];"
                 ::"r"(dst), "l"(src), "r"(bytes), "r"(bar) : "memory");
}
__device__ __forceinline__ void l2_prefetch(const void* src, uint32_t bytes, uint64_t pol) {
    asm volatile("cp.async.bulk.prefetch.L2.global.L2::cache_hint [%0], %1, %2;" ::"l"(src), "r"(bytes), "l"(pol) : "memory");
}
__device__ __forceinline__ void l2_prefetch(const void* src, uint32_t bytes) {
    asm volatile("cp.async.bulk.prefetch.L2.global [%0], %1;" ::"l"(src), "r"(bytes) : "memory");
}
__device__ __forceinline__ int4 lds128(uint32_t a) {
    int4 v;
    asm volatile("ld.shared.v4.s32 {%0,%1,%2,%3}, [%4];" : "=r"(v.x), "=r"(v.y), "=r"(v.z), "=r"(v.w) : "r"(a));
    return v;
}
__device__ __forceinline__ uint2 lds64(uint32_t a) {
    uint2 v;
    asm volatile("ld.shared.v2.u32 {%0,%1}, [%2];" : "=r"(v.x), "=r"(v.y) : "r"(a));
    return v;
}
__device__ __forceinline__ uint32_t lds32(uint32_t a) {
    uint32_t v;
    asm volatile("ld.shared.u32 %0, [%1];" : "=r"(v) : "r"(a));
    return v;
}
__device__ __forceinline__ uint32_t lds16(uint32_t a) {
    uint16_t v;
    asm volatile("ld.shared.u16 %0, [%1];" : "=h"(v) : "r"(a));
    return v;
}
__device__ __forceinline__ void sts32(uint32_t a, float x) {
    asm volatile("st.shared.f32 [%0], %1;" ::"r"(a), "f"(x) : "memory");
}
__device__ __forceinline__ void sts128(uint32_t a, uint32_t x, uint32_t y, uint32_t z, uint32_t w) {
    asm volatile("st.shared.v4.u32 [%0], {%1,%2,%3,%4};" ::"r"(a), "r"(x), "r"(y), "r"(z), "r"(w) : "memory");
}
__device__ __forceinline__ void sts64(uint32_t a, float x, float y) {
    asm volatile("st.shared.v2.f32 [%0], {%1,%2};" ::"r"(a), "f"(x), "f"(y) : "memory");
}
__device__ __forceinline__ float bf_lo(uint32_t v) { return __uint_as_float(v << 16); }
__device__ __forceinline__ float rbf(float x) {
    uint32_t d; asm("cvt.rn.bf16x2.f32 %0, %1, %2;" : "=r"(d) : "f"(x), "f"(0.f)); return __uint_as_float(d);
}
__device__ __forceinline__ float rcp(float x) {
    float y;
    asm("rcp.approx.ftz.f32 %0, %1;" : "=f"(y) : "f"(x));
    return y;
}
__device__ __forceinline__ float lg2(float x) {
    float y;
    asm("lg2.approx.ftz.f32 %0, %1;" : "=f"(y) : "f"(x));
    return y;
}
__device__ __forceinline__ float ex2(float x) {
    float y;
    asm("ex2.approx.ftz.f32 %0, %1;" : "=f"(y) : "f"(x));
    return y;
}
__device__ __forceinline__ uint32_t bmul(uint32_t a, uint32_t b) {
    uint32_t d; asm("mul.rn.bf16x2 %0, %1, %2;" : "=r"(d) : "r"(a), "r"(b)); return d;
}
__device__ __forceinline__ uint32_t bsub(uint32_t a, uint32_t b) {
    uint32_t d; asm("sub.rn.bf16x2 %0, %1, %2;" : "=r"(d) : "r"(a), "r"(b)); return d;
}
__device__ __forceinline__ uint32_t bfma(uint32_t a, uint32_t b, uint32_t c) {
    uint32_t d; asm("fma.rn.bf16x2 %0, %1, %2, %3;" : "=r"(d) : "r"(a), "r"(b), "r"(c)); return d;
}
__device__ __forceinline__ uint32_t i2bf2(int lo, int hi) {
    uint32_t d; asm("cvt.rn.bf16x2.f32 %0, %1, %2;" : "=r"(d) : "f"((float)hi), "f"((float)lo)); return d;
}
__device__ __forceinline__ uint32_t rope2(uint32_t x, uint32_t c, uint32_t y, uint32_t s, uint32_t sg) {
    return bfma(bmul(y, s), sg, bmul(x, c));
}
__device__ __forceinline__ void mma_bf16(float (&c)[4], uint32_t a0, uint32_t a1, uint32_t a2, uint32_t a3,
                                         uint32_t b0, uint32_t b1) {
    asm("mma.sync.aligned.m16n8k16.row.col.f32.bf16.bf16.f32 {%0,%1,%2,%3}, {%4,%5,%6,%7}, {%8,%9}, {%0,%1,%2,%3};"
        : "+f"(c[0]), "+f"(c[1]), "+f"(c[2]), "+f"(c[3])
        : "r"(a0), "r"(a1), "r"(a2), "r"(a3), "r"(b0), "r"(b1));
}
__device__ __forceinline__ void mail_put(uint32_t* p, float x, uint32_t tag) {
    asm volatile("st.relaxed.gpu.global.u32 [%0], %1;" ::"l"(p), "r"((__float_as_uint(x) & ~3u) | tag) : "memory");
}

struct Claim { uint32_t head, tile0, piece, sh, off; int ntiles; };

__device__ __forceinline__ Claim decode_claim(uint32_t c) {
    Claim cl;
    cl.sh = cl.off = 0;
    if (c < C_S) {
        cl.head = c / NM; cl.piece = c % NM; cl.sh = GSH; cl.off = c % (1 << GSH); cl.tile0 = (c - cl.off) * MAINP;
        cl.ntiles = MAINP;
        if (cl.piece >> GSH == cut_group(cl.head))
            cl.ntiles -= (semi_size(cl.head) + fin_size(cl.head) + cl.off) >> GSH;
    } else {
        cl.head = (c - C_S) % NHEAD; cl.piece = 0;
        cl.ntiles = fin_size(cl.head); cl.tile0 = cl.head * TPH + (cut_group(cl.head) + 1) * (TPH / 4) - cl.ntiles;
        if (c < C_F) { cl.ntiles = semi_size(cl.head); cl.tile0 -= cl.ntiles; }
    }
    return cl;
}

struct Params {
    const int* qk; const __nv_bfloat16* kcos; const __nv_bfloat16* ksin; const int* qv;
    const __nv_bfloat16* ks; const __nv_bfloat16* kz; const __nv_bfloat16* vs; const __nv_bfloat16* vz;
    const __nv_bfloat16* q; const __nv_bfloat16* qcos; const __nv_bfloat16* qsin;
    __nv_bfloat16* out;
};

constexpr float NEG = -3.0e38f;
constexpr float LOG2E = 1.4426950408889634f;
constexpr int F_NT = 31, F_LAST = 64, F_SEMI = 128, F_FIN = 256, F_END = 512;
static_assert(NHEAD * NM * REC < (1 << 20), "batch descriptor");

__global__ void __launch_bounds__(NTHREADS, 1)
kv_rope_decode_kernel(const Params p) {
    extern __shared__ __align__(128) unsigned char smem[];
    if (threadIdx.x < 32 && elect_one()) {
        l2_prefetch(p.kcos + (blockIdx.x % (TPH / 2)) * (2 * TR * D), 2 * CBYTES);
        l2_prefetch(p.ksin + (blockIdx.x % (TPH / 2)) * (2 * TR * D), 2 * CBYTES);
        uint64_t pol;
        asm volatile("createpolicy.fractional.L2::evict_first.b64 %0, 1.0;" : "=l"(pol));
        const uint32_t off = blockIdx.x % (1 << GSH);
        l2_prefetch(p.qk + (size_t)((blockIdx.x - off) * MAINP + off * PF0) * (TR * D), PF0 * KBYTES, pol);
    }
    const int w = __shfl_sync(0xffffffffu, (threadIdx.x >> 5) - 1, 0), lane = threadIdx.x & 31;
    if (w < 0) return;
    const uint32_t sb = __shfl_sync(0xffffffffu, smem_u32(smem), 0);
    const uint32_t bar = sb + OFF_BAR;

    if (w < 8 && elect_one()) {
        const uint32_t cnt = w == 4 ? 8 : w == 5 ? NKW + NVW : w == 6 ? NVW : w == 7 ? 2 : 1;
#pragma unroll
        for (int i = 0; i < 16; i++) mbar_init(bar + w * 128 + i * 8, cnt);
        asm volatile("fence.mbarrier_init.release.cluster;" ::: "memory");
    }
    asm volatile("bar.sync 0, %0;" ::"n"(NWARPS * 32) : "memory");

    if ((unsigned)(w - W_V) < NVW) {
        const int v = w - W_V, g = lane >> 3, l = lane & 7;
        const uint32_t up = pin(lane & 16), up2 = pin(lane & 8);
        const uint32_t oV = pin(sb + OFF_V + g * (2 * D * 4) + v * 128 + l * 16), oP = pin(S_PV + g * 8);
        const uint32_t col = pin(v * 32 + l * 4 + (up ? 2 : 0) + (up2 ? 1 : 0));
        const uint32_t oG = pin(S_G + col * 4);
        __nv_bfloat16* const outp = pin(p.out + col);
        uint32_t* const mailp = pin(g_mail + col);
        float a0 = 0.f, a1 = 0.f, a2 = 0.f, a3 = 0.f;
        uint32_t vb = bar, vt = oV, vph = 0, seg = 0;
        uint32_t s = sb + OFF_SEG, t0 = 0;
        mbar_wait(bar + B_PR, 0);
        uint2 bd = lds64(s + S_BD);
        uint2 pv = lds64(s + oP);
        bool ready = false;
        int4 x0, x1;
        auto load_tile = [&]() {
            if (!ready) mbar_wait(vb + B_FV, vph);
            x0 = lds128(vt);
            x1 = lds128(vt + D * 4);
            __syncwarp();
            if (lane == 0) mbar_arrive(vb + B_EV);
            vb += 8; vt += KBYTES;
            if (vb == bar + NV * 8) { vb = bar; vt = oV; vph ^= 1; }
            ready = mbar_test(vb + B_FV, vph);
        };
        auto fma_tile = [&]() {
            const float pv0 = __uint_as_float(pv.x), pv1 = __uint_as_float(pv.y);
            a0 = fmaf(pv1, (float)x1.x, fmaf(pv0, (float)x0.x, a0));
            a1 = fmaf(pv1, (float)x1.y, fmaf(pv0, (float)x0.y, a1));
            a2 = fmaf(pv1, (float)x1.z, fmaf(pv0, (float)x0.z, a2));
            a3 = fmaf(pv1, (float)x1.w, fmaf(pv0, (float)x0.w, a3));
        };
        for (uint32_t batch = 1; !(bd.y & F_END); batch++) {
            const uint32_t n = bd.y & F_NT, sbar = bar + (seg % NSEG) * 8, sph = (seg / NSEG) & 1;
            const bool last = bd.y & F_LAST;
            const uint32_t seg2 = seg + last, t2 = last ? 0 : t0 + n;
            const uint32_t s2 = sb + OFF_SEG + (seg2 % NSEG) * SEG_BYTES;
            const uint32_t prb = bar + B_PR + (batch % NBAT) * 8, prp = (batch / NBAT) & 1;
            const float alpha = __uint_as_float(bd.x);
            a0 *= alpha; a1 *= alpha; a2 *= alpha; a3 *= alpha;
#pragma unroll 1
            for (uint32_t i = 1; i < n; i++) {
                load_tile();
                const uint2 pn = lds64(s + oP + (t0 + i) * (TR * 4));
                fma_tile();
                pv = pn;
            }
            load_tile();
            const bool early = mbar_test(sbar + B_FC, sph);
            const bool next = mbar_test(prb, prp);
            fma_tile();
            uint2 bn, pn;
            if (last) {
                const float u0 = (up ? a2 : a0) + __shfl_xor_sync(0xffffffffu, up ? a0 : a2, 16);
                const float u1 = (up ? a3 : a1) + __shfl_xor_sync(0xffffffffu, up ? a1 : a3, 16);
                if (!early) mbar_wait(sbar + B_FC, sph);
                const int4 cf = lds128(s + S_CF);
                const uint32_t gv = lds32(s + oG);
                const float u = (up2 ? u1 : u0) + __shfl_xor_sync(0xffffffffu, up2 ? u0 : u1, 8);
                const float gj = (bd.y & (F_SEMI | F_FIN)) ? __uint_as_float(gv) : 0.f;
                const float o = fmaf(u, __int_as_float(cf.x), fmaf(gj, __int_as_float(cf.y), __int_as_float(cf.z)));
                if (bd.y & F_FIN) {
                    const __nv_bfloat16 r = __float2bfloat16_rn(o);
                    asm volatile("st.global.b16 [%0], %1;" ::"l"(outp + (bd.y >> 12)), "h"(*(const uint16_t*)&r) : "memory");
                    if (cf.w & 2) return;
                } else {
                    mail_put(mailp + (bd.y >> 12), o, cf.w & 3);
                    if (col < REC - D) mail_put(mailp + (bd.y >> 12) + D, __int_as_float(cf.w), cf.w & 3);
                }
                a0 = a1 = a2 = a3 = 0.f;
                __syncwarp();
                if (lane == 0) mbar_arrive(sbar + B_SE);
            }
            if (!next) mbar_wait(prb, prp);
            bn = lds64(s2 + S_BD + t2 * 8);
            pn = lds64(s2 + oP + t2 * (TR * 4));
            bd = bn; pv = pn; s = s2; t0 = t2; seg = seg2;
        }
    } else if (w == W_S) {
        uint32_t batch = 0;
        for (uint32_t seg = 0;; seg++) {
            const uint32_t s = sb + OFF_SEG + (seg % NSEG) * SEG_BYTES, sbar = bar + (seg % NSEG) * 8;
            const uint32_t sph = (seg / NSEG) & 1;
            mbar_wait(sbar + B_HDR, sph);
            const int4 desc = lds128(s + S_DESC);
            if (desc.y & F_END) {
                if (lane == 0) {
                    sts64(s + S_BD, 0.f, __uint_as_float(F_END));
                    mbar_arrive(bar + B_PR + (batch % NBAT) * 8);
                }
                break;
            }
            float m = NEG, L = 0.f, C = 0.f;
            const uint32_t head = (uint32_t)desc.x / TPH, index = (desc.y & F_FIN) ? head * D : (head * NM + desc.z) * REC;
            const int nt = desc.y & F_NT;
#pragma unroll 1
            for (int t0 = 0; t0 < nt; t0 += 4, batch++) {
                const int n = min(4, nt - t0);
                const bool valid = lane < n * TR;
                const uint32_t tl = t0 + (valid ? lane >> 3 : 0), row = tl * TR + (lane & 7);
                const uint32_t sc = s + S_SC + (((tl << (desc.w & 255)) + (desc.w >> 8)) * TR + (lane & 7)) * 2;
                const float vs = bf_lo(lds16(sc + 2 * SCB)), vz = bf_lo(lds16(sc + 3 * SCB));
                mbar_wait(bar + B_LG + (batch % NBAT) * 8, (batch / NBAT) & 1);
                const int4 part = lds128(s + S_LG + row * 16);
                const float dot = (__int_as_float(part.x) + __int_as_float(part.y)) + (__int_as_float(part.z) + __int_as_float(part.w));
                const float sv = rbf(rbf(dot) * 0.07216878364870322f) * LOG2E;
                int key = __float_as_int(fmaxf(m, sv));
                key ^= (key >> 31) & 0x7fffffff;
                key = __reduce_max_sync(0xffffffffu, key);
                const float mn = __int_as_float(key ^ ((key >> 31) & 0x7fffffff));
                const float alpha = ex2(m - mn), pr = ex2(sv - mn), pv = pr * vs;
                m = mn;
                sts32(s + S_PV + row * 4, pv);
                if (lane == 0)
                    sts64(s + S_BD + t0 * 8, alpha,
                          __uint_as_float(n | (t0 + n < nt ? 0 : index << 12 | F_LAST | (desc.y & (F_SEMI | F_FIN)))));
                __syncwarp();
                if (lane == 0) mbar_arrive(bar + B_PR + (batch % NBAT) * 8);
                L = fmaf(L, alpha, valid ? pr : 0.f);
                C = fmaf(C, alpha, valid ? pv * vz : 0.f);
            }
#pragma unroll
            for (int o = 16; o > 0; o >>= 1) {
                L += __shfl_xor_sync(0xffffffffu, L, o);
                C += __shfl_xor_sync(0xffffffffu, C, o);
            }
            mbar_wait(sbar + B_GD, sph);
            uint32_t tag = lds32(sb + OFF_TAG) | ((desc.y & F_SEMI) ? 2 : 0);
            if ((desc.y & F_FIN) && mbar_test(bar + B_HDR + ((seg + 1) % NSEG) * 8, ((seg + 1) / NSEG) & 1))
                tag |= lds32(sb + OFF_SEG + ((seg + 1) % NSEG) * SEG_BYTES + S_DESC + 4) / (F_END / 2);
            const float gl = (desc.y & (F_SEMI | F_FIN)) ? __uint_as_float(lds32(s + S_G + D * 4)) : -3.4e38f;
            const float M = fmaxf(m, gl), e = ex2(m - M), a = ex2(gl - M);
            const float W = fmaf(L, e, a), inv = rcp(W);
            if (lane == 0)
                sts128(s + S_CF, __float_as_uint(e * inv), __float_as_uint(a * inv), __float_as_uint(-C * e * inv),
                       (__float_as_uint(M + lg2(W)) & ~3u) | tag);
            __syncwarp();
            if (lane == 0) mbar_arrive(sbar + B_FC);
        }
    } else if ((unsigned)(w - W_G) < NGW) {
        if (w == W_G) {
            if (lane == 0) sts32(sb + OFF_TAG, __uint_as_float(~*(volatile unsigned int*)&g_epoch & 1));
        } else {
            mbar_wait(bar + B_GD, 0);
        }
        for (uint32_t seg = w - W_G;; seg += NGW) {
            const uint32_t s = sb + OFF_SEG + (seg % NSEG) * SEG_BYTES, sbar = bar + (seg % NSEG) * 8;
            mbar_wait(sbar + B_HDR, (seg / NSEG) & 1);
            const int4 desc = lds128(s + S_DESC);
            if (desc.y & F_END) break;
            if (desc.y & (F_SEMI | F_FIN)) {
                const uint32_t tag = lds32(sb + OFF_TAG) | ((desc.y & F_FIN) ? 2 : 0);
                const int cnt = (desc.y & F_FIN) ? 1 : NM;
                const uint32_t* mail = g_mail + (uint32_t)desc.x / TPH * (NM * REC);
                float M = NEG, W = 0.f, O[6] = {0.f, 0.f, 0.f, 0.f, 0.f, 0.f};
#pragma unroll 1
                for (int i0 = 0; i0 < cnt; i0 += GB, mail += GB * REC) {
                    uint2 pk[3 * GB];
                    uint32_t ls[GB], stale;
                    int it = 0;
                    do {
                        stale = 0;
#pragma unroll
                        for (int i = 0; i < GB; i++) {
                            ls[i] = 0xff7ffffcu | tag;
                            pk[3 * i] = pk[3 * i + 1] = pk[3 * i + 2] = make_uint2(tag, tag);
                            if (i0 + i < cnt) {
                                asm volatile("ld.relaxed.gpu.global.u32 %0, [%1];" : "=r"(ls[i]) : "l"(mail + i * REC + D) : "memory");
#pragma unroll
                                for (int k = 0; k < 3; k++)
                                    asm volatile("ld.relaxed.gpu.global.v2.u32 {%0,%1}, [%2];"
                                                 : "=r"(pk[3 * i + k].x), "=r"(pk[3 * i + k].y)
                                                 : "l"(mail + i * REC + k * 64 + lane * 2) : "memory");
                            }
                        }
#pragma unroll
                        for (int i = 0; i < GB; i++) stale |= ls[i] ^= tag;
#pragma unroll
                        for (int i = 0; i < 3 * GB; i++) stale |= (pk[i].x ^= tag) | (pk[i].y ^= tag);
                        if (++it > (1 << 22)) __trap();
                    } while (stale & 3);
                    float Mn = M;
#pragma unroll
                    for (int i = 0; i < GB; i++) Mn = fmaxf(Mn, __uint_as_float(ls[i]));
                    const float a = ex2(M - Mn);
                    M = Mn; W *= a;
#pragma unroll
                    for (int i = 0; i < 6; i++) O[i] *= a;
#pragma unroll
                    for (int i = 0; i < GB; i++) {
                        const float e = ex2(__uint_as_float(ls[i]) - M);
                        W += e;
#pragma unroll
                        for (int k = 0; k < 3; k++) {
                            O[2 * k] = fmaf(e, __uint_as_float(pk[3 * i + k].x), O[2 * k]);
                            O[2 * k + 1] = fmaf(e, __uint_as_float(pk[3 * i + k].y), O[2 * k + 1]);
                        }
                    }
                }
                const float inv = rcp(W);
#pragma unroll
                for (int k = 0; k < 3; k++) sts64(s + S_G + k * 256 + lane * 8, O[2 * k] * inv, O[2 * k + 1] * inv);
                if (lane == 0) sts32(s + S_G + D * 4, M + lg2(W));
            }
            __syncwarp();
            if (lane == 0) mbar_arrive(sbar + B_GD);
        }
    } else if (w / NKW == 0) {
        const int g = lane >> 3, l = lane & 7, godd = g & 1, row = 2 * g + (w & 1);
        const uint32_t sgA = pin(godd ? 0x3f803f80u : 0xbf80bf80u), sgB = pin(godd ? 0xbf80bf80u : 0x3f803f80u);
        const uint32_t oKA = pin(sb + row * (D * 4) + l * 16 + godd * 384), oKB = pin(oKA - godd * 768 + 384);
        const uint32_t oCA = pin(sb + T_C + row * (D * 2) + l * 8 + godd * 192), oCB = pin(oCA - godd * 384 + 192);
        const uint32_t oL = pin(S_LG + row * 16 + (l >> 2) * 8 + (l & 1) * 4), oS = pin(S_SC + row * 2);
        const bool own = (l & 3) == g, hi = l & 4, keep = ((l ^ g) & 2) == 0;
        uint32_t kslot = w >> 1, j = kslot, batch0 = 0, kph = 0;
        for (uint32_t seg = 0;; seg++) {
            const uint32_t s = sb + OFF_SEG + (seg % NSEG) * SEG_BYTES, sbar = bar + (seg % NSEG) * 8;
            mbar_wait(sbar + B_HDR, (seg / NSEG) & 1);
            const int4 desc = lds128(s + S_DESC);
            if (desc.y & F_END) break;
            const uint32_t nt = desc.y & F_NT;
            uint2 qr[3];
#pragma unroll
            for (int i = 0; i < 3; i++) {
                const uint32_t oa = l * 8 + godd * 192 + i * 64, ob = oa + 192 - godd * 384;
                const uint2 a = lds64(s + S_Q + oa), b = lds64(s + S_Q + ob);
                const uint2 ca = lds64(sb + OFF_QT + oa), sa = lds64(sb + OFF_QT + QBYTES + oa);
                qr[i].x = rope2(a.x, ca.x, b.x, sa.x, sgA);
                qr[i].y = rope2(a.y, ca.y, b.y, sa.y, sgA);
            }
            for (; j < nt; j += NKW / 2) {
                const uint32_t t = kslot * KSLOT;
                const uint32_t sc = s + oS + ((j << (desc.w & 255)) + (desc.w >> 8)) * (TR * 2);
                const uint32_t ks2 = lds16(sc) * 0x10001u, kz2 = lds16(sc + SCB) * 0x10001u;
                const uint32_t lgb = bar + B_LG + ((batch0 + (j >> 2)) % NBAT) * 8;
                const uint32_t lgc = j == nt - 1 ? 4 - (j & 3) : 1;
                mbar_wait(bar + B_FK + kslot * 8, kph);
                float c[4] = {0.f, 0.f, 0.f, 0.f};
#pragma unroll
                for (int jj = 0; jj < 3; jj++) {
                    const int4 xa = lds128(t + oKA + jj * 128), xb = lds128(t + oKB + jj * 128);
                    const uint2 ca = lds64(t + oCA + jj * 64), cb = lds64(t + oCB + jj * 64);
                    const uint2 sa = lds64(t + oCA + CBYTES + jj * 64), sbv = lds64(t + oCB + CBYTES + jj * 64);
                    const uint32_t a0 = bmul(bsub(i2bf2(xa.x, xa.y), kz2), ks2);
                    const uint32_t a1 = bmul(bsub(i2bf2(xa.z, xa.w), kz2), ks2);
                    const uint32_t b0 = bmul(bsub(i2bf2(xb.x, xb.y), kz2), ks2);
                    const uint32_t b1 = bmul(bsub(i2bf2(xb.z, xb.w), kz2), ks2);
                    mma_bf16(c, rope2(a0, ca.x, b0, sa.x, sgA), rope2(b0, cb.x, a0, sbv.x, sgB),
                             rope2(a1, ca.y, b1, sa.y, sgA), rope2(b1, cb.y, a1, sbv.y, sgB), qr[jj].x, qr[jj].y);
                }
                __syncwarp();
                if (lane == 0) mbar_arrive(bar + B_EK + kslot * 8);
                const float part = own ? (hi ? c[1] : c[0]) : (hi ? c[3] : c[2]);
                if (keep) sts32(s + oL + j * (TR * 16), part);
                __syncwarp();
                if (lane == 0) mbar_arrive(lgb, lgc);
                kslot += NKW / 2;
                if (kslot >= NK) { kslot -= NK; kph ^= 1; }
            }
            j -= nt;
            batch0 += (nt + 3) >> 2;
            __syncwarp();
            if (lane == 0) mbar_arrive(sbar + B_SE);
        }
    } else if (w == W_SCH) {
        if (elect_one()) {
            asm volatile("mbarrier.expect_tx.shared::cta.b64 [%0], %1;" ::"r"(bar + B_HDR), "r"(2 * QBYTES) : "memory");
            uint32_t seg = 0, c = blockIdx.x;
            while (c < NCLAIM) {
                const Claim cl = decode_claim(c);
                const uint32_t s = sb + OFF_SEG + (seg % NSEG) * SEG_BYTES, b = bar + (seg % NSEG) * 8;
                mbar_wait(b + B_SE, ((seg / NSEG) & 1) ^ 1);
                sts128(s + S_DESC, cl.tile0 + cl.off, cl.ntiles | (c >= C_F ? F_FIN : c >= C_S ? F_SEMI : 0), cl.piece,
                       cl.sh | cl.off << 8);
                if (seg) mbar_arrive(bar + B_DS + ((seg - 1) % NSEG) * 8);
                const uint32_t scb = cl.ntiles * TR * 2 << cl.sh, r = cl.tile0 * TR;
                mbar_expect(b + B_HDR, 4 * scb + QBYTES);
                bulk_plain(s + S_Q, p.q + cl.head * D, QBYTES, b + B_HDR);
                bulk_plain(s + S_SC, p.ks + r, scb, b + B_HDR);
                bulk_plain(s + S_SC + SCB, p.kz + r, scb, b + B_HDR);
                bulk_plain(s + S_SC + 2 * SCB, p.vs + r, scb, b + B_HDR);
                bulk_plain(s + S_SC + 3 * SCB, p.vz + r, scb, b + B_HDR);
                if (seg == 0) {
                    bulk_plain(sb + OFF_QT, p.qcos, QBYTES, bar + B_HDR);
                    bulk_plain(sb + OFF_QT + QBYTES, p.qsin, QBYTES, bar + B_HDR);
                    mbar_wait(bar + B_GD, 0);
                }
                mbar_wait(bar + B_GO, seg & 1);
                seg++;
                const unsigned nx = atomicInc(&g_queue, NCLAIM - 1);
                if (nx == NCLAIM - 1) g_epoch = lds32(sb + OFF_TAG);
                c = gridDim.x + nx;
            }
#pragma unroll 1
            for (int i = 0; i < NGW; i++, seg++) {
                const uint32_t s = sb + OFF_SEG + (seg % NSEG) * SEG_BYTES, b = bar + (seg % NSEG) * 8;
                mbar_wait(b + B_SE, ((seg / NSEG) & 1) ^ 1);
                sts128(s + S_DESC, 0, F_END, 0, 0);
                mbar_arrive(bar + B_DS + ((seg - 1) % NSEG) * 8);
                mbar_arrive(b + B_HDR);
            }
        }
    } else {
        if (elect_one()) {
            uint64_t pol;
            asm volatile("createpolicy.fractional.L2::evict_first.b64 %0, 1.0;" : "=l"(pol));
            uint32_t kslot = 0, vslot = 0, kph = 1, vph = 1;
            int pend[LEAD];
#pragma unroll
            for (int i = 0; i < LEAD; i++) pend[i] = -1;
            auto issue_v = [&]() {
                if (pend[0] >= 0) {
                    const uint32_t b = bar + vslot * 8;
                    mbar_wait(b + B_EV, vph);
                    mbar_wait(b + B_FV + (vslot >= WIN ? 0 : NV * 8) - WIN * 8, vph ^ (vslot >= WIN));
                    mbar_expect(b + B_FV, KBYTES);
                    bulk_stream(sb + OFF_V + vslot * KBYTES, p.qv + (size_t)pend[0] * (TR * D), KBYTES, b + B_FV, pol);
                    if (++vslot == NV) { vslot = 0; vph ^= 1; }
                }
#pragma unroll
                for (int i = 0; i + 1 < LEAD; i++) pend[i] = pend[i + 1];
                pend[LEAD - 1] = -1;
            };
            const Claim c0 = decode_claim(blockIdx.x % C_S);
            int4 desc = make_int4(c0.tile0 + c0.off, c0.ntiles, 0, GSH);
            for (uint32_t seg = 0; !(desc.y & F_END); seg++) {
                uint32_t tile = desc.x;
#pragma unroll 1
                for (int left = desc.y & F_NT; left > 0; left--, tile += 1u << (desc.w & 255)) {
                    if (left == 1) mbar_arrive(bar + B_GO);
                    const uint32_t t = sb + kslot * KSLOT, b = bar + kslot * 8;
                    const uint32_t ro = (tile % TPH) * (TR * D);
                    mbar_wait(b + B_EK, kph);
                    mbar_expect(b + B_FK, KSLOT);
                    bulk_stream(t, p.qk + (size_t)tile * (TR * D), KBYTES, b + B_FK, pol);
                    bulk_plain(t + T_C, p.kcos + ro, CBYTES, b + B_FK);
                    bulk_plain(t + T_S, p.ksin + ro, CBYTES, b + B_FK);
                    if (++kslot == NK) { kslot = 0; kph ^= 1; }
                    pend[LEAD - 1] = tile;
                    issue_v();
                }
                mbar_wait(bar + B_DS + (seg % NSEG) * 8, (seg / NSEG) & 1);
                desc = lds128(sb + OFF_SEG + ((seg + 1) % NSEG) * SEG_BYTES + S_DESC);
            }
#pragma unroll 1
            for (int i = 1; i < LEAD; i++) issue_v();
        }
    }
}

}

extern "C" void kernel_launch(void* const* d_in, const int* in_sizes, int n_in, void* d_out, int out_size) {
    (void)in_sizes; (void)n_in; (void)out_size;
    static int sms = 0;
    if (sms == 0) {
        int dev = 0;
        cudaGetDevice(&dev);
        cudaDeviceGetAttribute(&sms, cudaDevAttrMultiProcessorCount, dev);
        cudaFuncSetAttribute(kv_rope_decode_kernel, cudaFuncAttributeMaxDynamicSharedMemorySize, SMEM_BYTES);
    }
    Params p;
    p.q    = (const __nv_bfloat16*)d_in[0];
    p.qk   = (const int*)d_in[1];
    p.ks   = (const __nv_bfloat16*)d_in[2];
    p.kz   = (const __nv_bfloat16*)d_in[3];
    p.qv   = (const int*)d_in[4];
    p.vs   = (const __nv_bfloat16*)d_in[5];
    p.vz   = (const __nv_bfloat16*)d_in[6];
    p.qcos = (const __nv_bfloat16*)d_in[7];
    p.qsin = (const __nv_bfloat16*)d_in[8];
    p.kcos = (const __nv_bfloat16*)d_in[9];
    p.ksin = (const __nv_bfloat16*)d_in[10];
    p.out  = (__nv_bfloat16*)d_out;
    kv_rope_decode_kernel<<<sms, NTHREADS, SMEM_BYTES>>>(p);
}
```

```cpp
#include <cuda_runtime.h>
#include <cuda_bf16.h>
#include <stdint.h>

namespace {

constexpr int D      = 192;
constexpr int SKV    = 2048;
constexpr int NHEAD  = 256;
constexpr int TR     = 8;
constexpr int TPH    = SKV / TR;
constexpr int NKW    = 4;
constexpr int NVW    = 6;
constexpr int NGW    = 2;
constexpr int NK     = 8;
constexpr int NV     = 6;
constexpr int WIN    = 4;
constexpr int LEAD   = 5;
constexpr int NSEG   = 8;
constexpr int SEGT   = 16;
constexpr int NBAT   = 16;
constexpr int W_V = NKW, W_PROD = W_V + NVW, W_S = W_PROD + 1, W_G = W_S + 1, W_SCH = W_G + NGW, NWARPS = W_SCH + 1;
constexpr int NTHREADS = 32 + NWARPS * 32;

constexpr int MAINP  = 16;
constexpr int PF0    = 3;
constexpr int GSH    = 2;
__host__ __device__ constexpr int semi_size(uint32_t h) { return (0x88ccu >> (h / 64 * 4)) & 15; }
__host__ __device__ constexpr int fin_size(uint32_t h) { return (0x248cu >> (h / 64 * 4)) & 15; }
__host__ __device__ constexpr uint32_t cut_group(uint32_t h) { return (2 - h / 4) % 4; }
constexpr int NM     = TPH / MAINP;
static_assert(NM >> GSH == 4, "four interleave groups per head");
constexpr int C_S    = NHEAD * NM, C_F = C_S + NHEAD, NCLAIM = C_F + NHEAD;

constexpr int KBYTES = TR * D * 4;
constexpr int CBYTES = TR * D * 2;
constexpr int QBYTES = D * 2;
constexpr int T_C = KBYTES, T_S = T_C + CBYTES, KSLOT = T_S + CBYTES;
constexpr int SCB = SEGT * TR * 2 << GSH;
static_assert(MAINP <= SEGT && semi_size(0) <= SEGT && fin_size(0) <= SEGT && GSH >= 1, "a piece fills one segment slot");
constexpr int S_Q    = 0;
constexpr int S_SC   = S_Q + QBYTES;
constexpr int S_DESC = S_SC + 4 * SCB;
constexpr int S_BD   = S_DESC + 16;
constexpr int S_LG   = S_BD + SEGT * 8;
constexpr int S_PV   = S_LG + SEGT * TR * 16;
constexpr int S_G    = S_PV + SEGT * TR * 4;
constexpr int S_CF   = S_G + (D + 4) * 4;
constexpr int SEG_BYTES = (S_CF + 16 + 127) / 128 * 128;
constexpr int OFF_V = NK * KSLOT, OFF_SEG = OFF_V + NV * KBYTES, OFF_QT = OFF_SEG + NSEG * SEG_BYTES,
              OFF_TAG = OFF_QT + 2 * QBYTES, OFF_BAR = OFF_TAG + 16;
constexpr int B_FK = 0, B_DS = 64, B_PR = 128, B_HDR = 256, B_GD = 320, B_FC = 384, B_FV = 448, B_GO = 504,
              B_LG = 512, B_SE = 640, B_EV = 768, B_EK = 896;
constexpr int SMEM_BYTES = OFF_BAR + 1024;
static_assert(NK <= 8 && NV <= 7 && W_PROD >= 8 && NSEG == 8 && NBAT == 16, "barrier layout");
static_assert(SMEM_BYTES <= 232448 && SMEM_BYTES > 232448 / 2, "one CTA per SM");
static_assert(NSEG % NGW == 0 && NK % (NKW / 2) == 0 && NVW * 32 == D && LEAD >= 1, "cfg");
static_assert(WIN < NV && LEAD + NV >= 4 && LEAD + NV < NBAT && LEAD < NSEG, "no ring can be lapped or starved");

__device__ unsigned int g_queue;
constexpr int REC = 200, GB = 4;
__device__ unsigned int g_epoch;
__device__ __align__(32) uint32_t g_mail[NHEAD * NM * REC];

__device__ __forceinline__ uint32_t smem_u32(const void* p) { return (uint32_t)__cvta_generic_to_shared(p); }
__device__ __forceinline__ uint32_t pin(uint32_t x) {
    return __shfl_sync(0xffffffffu, x, threadIdx.x & 31);
}
template <class T> __device__ __forceinline__ T* pin(T* p) {
    return (T*)__shfl_sync(0xffffffffu, (unsigned long long)p, threadIdx.x & 31);
}
__device__ __forceinline__ bool elect_one() {
    uint32_t pred;
    asm volatile("{\n.reg .pred p;\nelect.sync _|p, 0xffffffff;\nselp.u32 %0, 1, 0, p;\n}" : "=r"(pred));
    return pred;
}
__device__ __forceinline__ void mbar_init(uint32_t bar, uint32_t cnt) {
    asm volatile("mbarrier.init.shared::cta.b64 [%0], %1;" ::"r"(bar), "r"(cnt) : "memory");
}
__device__ __forceinline__ void mbar_expect(uint32_t bar, uint32_t bytes) {
    asm volatile("mbarrier.arrive.expect_tx.shared::cta.b64 _, [%0], %1;" ::"r"(bar), "r"(bytes) : "memory");
}
__device__ __forceinline__ void mbar_arrive(uint32_t bar) {
    asm volatile("mbarrier.arrive.shared::cta.b64 _, [%0];" ::"r"(bar) : "memory");
}
__device__ __forceinline__ void mbar_arrive(uint32_t bar, uint32_t cnt) {
    asm volatile("mbarrier.arrive.shared::cta.b64 _, [%0], %1;" ::"r"(bar), "r"(cnt) : "memory");
}
__device__ __forceinline__ bool mbar_test(uint32_t bar, uint32_t parity) {
    uint32_t ok;
    asm volatile("{\n.reg .pred p;\nmbarrier.test_wait.parity.shared::cta.b64 p, [%1], %2;\nselp.u32 %0, 1, 0, p;\n}"
                 : "=r"(ok) : "r"(bar), "r"(parity) : "memory");
    return ok;
}
__device__ __forceinline__ void mbar_wait(uint32_t bar, uint32_t parity) {
    asm volatile("{\n.reg .pred p;\n.reg .u32 n;\n"
                 "mbarrier.try_wait.parity.shared::cta.b64 p, [%0], %1;\n"
                 "@p bra DONE;\n"
                 "mov.u32 n, 0;\n"
                 "LOOP:\n"
                 "mbarrier.try_wait.parity.shared::cta.b64 p, [%0], %1;\n"
                 "@p bra DONE;\n"
                 "add.u32 n, n, 1;\n"
                 "setp.lt.u32 p, n, 0x400000;\n"
                 "@p bra LOOP;\n"
                 "trap;\n"
                 "DONE:\n}" ::"r"(bar), "r"(parity) : "memory");
}
__device__ __forceinline__ void bulk_stream(uint32_t dst, const void* src, uint32_t bytes, uint32_t bar, uint64_t pol) {
    asm volatile("cp.async.bulk.shared::cluster.global.mbarrier::complete_tx::bytes.L2::cache_hint [%0], [%1], %2, [%3], %4;"
                 ::"r"(dst), "l"(src), "r"(bytes), "r"(bar), "l"(pol) : "memory");
}
__device__ __forceinline__ void bulk_plain(uint32_t dst, const void* src, uint32_t bytes, uint32_t bar) {
    asm volatile("cp.async.bulk.shared::cluster.global.mbarrier::complete_tx::bytes [%0], [%1], %2, [%3];"
                 ::"r"(dst), "l"(src), "r"(bytes), "r"(bar) : "memory");
}
__device__ __forceinline__ void l2_prefetch(const void* src, uint32_t bytes, uint64_t pol) {
    asm volatile("cp.async.bulk.prefetch.L2.global.L2::cache_hint [%0], %1, %2;" ::"l"(src), "r"(bytes), "l"(pol) : "memory");
}
__device__ __forceinline__ void l2_prefetch(const void* src, uint32_t bytes) {
    asm volatile("cp.async.bulk.prefetch.L2.global [%0], %1;" ::"l"(src), "r"(bytes) : "memory");
}
__device__ __forceinline__ int4 lds128(uint32_t a) {
    int4 v;
    asm volatile("ld.shared.v4.s32 {%0,%1,%2,%3}, [%4];" : "=r"(v.x), "=r"(v.y), "=r"(v.z), "=r"(v.w) : "r"(a));
    return v;
}
__device__ __forceinline__ uint2 lds64(uint32_t a) {
    uint2 v;
    asm volatile("ld.shared.v2.u32 {%0,%1}, [%2];" : "=r"(v.x), "=r"(v.y) : "r"(a));
    return v;
}
__device__ __forceinline__ uint32_t lds32(uint32_t a) {
    uint32_t v;
    asm volatile("ld.shared.u32 %0, [%1];" : "=r"(v) : "r"(a));
    return v;
}
__device__ __forceinline__ uint32_t lds16(uint32_t a) {
    uint16_t v;
    asm volatile("ld.shared.u16 %0, [%1];" : "=h"(v) : "r"(a));
    return v;
}
__device__ __forceinline__ void sts32(uint32_t a, float x) {
    asm volatile("st.shared.f32 [%0], %1;" ::"r"(a), "f"(x) : "memory");
}
__device__ __forceinline__ void sts128(uint32_t a, uint32_t x, uint32_t y, uint32_t z, uint32_t w) {
    asm volatile("st.shared.v4.u32 [%0], {%1,%2,%3,%4};" ::"r"(a), "r"(x), "r"(y), "r"(z), "r"(w) : "memory");
}
__device__ __forceinline__ void sts64(uint32_t a, float x, float y) {
    asm volatile("st.shared.v2.f32 [%0], {%1,%2};" ::"r"(a), "f"(x), "f"(y) : "memory");
}
__device__ __forceinline__ float bf_lo(uint32_t v) { return __uint_as_float(v << 16); }
__device__ __forceinline__ float rbf(float x) {
    uint32_t d; asm("cvt.rn.bf16x2.f32 %0, %1, %2;" : "=r"(d) : "f"(x), "f"(0.f)); return __uint_as_float(d);
}
__device__ __forceinline__ float rcp(float x) {
    float y;
    asm("rcp.approx.ftz.f32 %0, %1;" : "=f"(y) : "f"(x));
    return y;
}
__device__ __forceinline__ float lg2(float x) {
    float y;
    asm("lg2.approx.ftz.f32 %0, %1;" : "=f"(y) : "f"(x));
    return y;
}
__device__ __forceinline__ float ex2(float x) {
    float y;
    asm("ex2.approx.ftz.f32 %0, %1;" : "=f"(y) : "f"(x));
    return y;
}
__device__ __forceinline__ uint32_t bmul(uint32_t a, uint32_t b) {
    uint32_t d; asm("mul.rn.bf16x2 %0, %1, %2;" : "=r"(d) : "r"(a), "r"(b)); return d;
}
__device__ __forceinline__ uint32_t bsub(uint32_t a, uint32_t b) {
    uint32_t d; asm("sub.rn.bf16x2 %0, %1, %2;" : "=r"(d) : "r"(a), "r"(b)); return d;
}
__device__ __forceinline__ uint32_t bfma(uint32_t a, uint32_t b, uint32_t c) {
    uint32_t d; asm("fma.rn.bf16x2 %0, %1, %2, %3;" : "=r"(d) : "r"(a), "r"(b), "r"(c)); return d;
}
__device__ __forceinline__ uint32_t i2bf2(int lo, int hi) {
    uint32_t d; asm("cvt.rn.bf16x2.f32 %0, %1, %2;" : "=r"(d) : "f"((float)hi), "f"((float)lo)); return d;
}
__device__ __forceinline__ uint32_t rope2(uint32_t x, uint32_t c, uint32_t y, uint32_t s, uint32_t sg) {
    return bfma(bmul(y, s), sg, bmul(x, c));
}
__device__ __forceinline__ void mma_bf16(float (&c)[4], uint32_t a0, uint32_t a1, uint32_t a2, uint32_t a3,
                                         uint32_t b0, uint32_t b1) {
    asm("mma.sync.aligned.m16n8k16.row.col.f32.bf16.bf16.f32 {%0,%1,%2,%3}, {%4,%5,%6,%7}, {%8,%9}, {%0,%1,%2,%3};"
        : "+f"(c[0]), "+f"(c[1]), "+f"(c[2]), "+f"(c[3])
        : "r"(a0), "r"(a1), "r"(a2), "r"(a3), "r"(b0), "r"(b1));
}
__device__ __forceinline__ void mail_put(uint32_t* p, float x, uint32_t tag) {
    asm volatile("st.relaxed.gpu.global.u32 [%0], %1;" ::"l"(p), "r"((__float_as_uint(x) & ~3u) | tag) : "memory");
}

struct Claim { uint32_t head, tile0, piece, sh, off; int ntiles; };

__device__ __forceinline__ Claim decode_claim(uint32_t c) {
    Claim cl;
    cl.sh = cl.off = 0;
    if (c < C_S) {
        cl.head = c / NM; cl.piece = c % NM; cl.sh = GSH; cl.off = c % (1 << GSH); cl.tile0 = (c - cl.off) * MAINP;
        cl.ntiles = MAINP;
        if (cl.piece >> GSH == cut_group(cl.head))
            cl.ntiles -= (semi_size(cl.head) + fin_size(cl.head) + cl.off) >> GSH;
    } else {
        cl.head = (c - C_S) % NHEAD; cl.piece = 0;
        cl.ntiles = fin_size(cl.head); cl.tile0 = cl.head * TPH + (cut_group(cl.head) + 1) * (TPH / 4) - cl.ntiles;
        if (c < C_F) { cl.ntiles = semi_size(cl.head); cl.tile0 -= cl.ntiles; }
    }
    return cl;
}

struct Params {
    const int* qk; const __nv_bfloat16* kcos; const __nv_bfloat16* ksin; const int* qv;
    const __nv_bfloat16* ks; const __nv_bfloat16* kz; const __nv_bfloat16* vs; const __nv_bfloat16* vz;
    const __nv_bfloat16* q; const __nv_bfloat16* qcos; const __nv_bfloat16* qsin;
    __nv_bfloat16* out;
};

constexpr float NEG = -3.0e38f;
constexpr float LOG2E = 1.4426950408889634f;
constexpr int F_NT = 31, F_LAST = 64, F_SEMI = 128, F_FIN = 256, F_END = 512;
static_assert(NHEAD * NM * REC < (1 << 20), "batch descriptor");

__global__ void __launch_bounds__(NTHREADS, 1)
kv_rope_decode_kernel(const Params p) {
    extern __shared__ __align__(128) unsigned char smem[];
    if (threadIdx.x < 32 && elect_one()) {
        l2_prefetch(p.kcos + (blockIdx.x % (TPH / 2)) * (2 * TR * D), 2 * CBYTES);
        l2_prefetch(p.ksin + (blockIdx.x % (TPH / 2)) * (2 * TR * D), 2 * CBYTES);
        uint64_t pol;
        asm volatile("createpolicy.fractional.L2::evict_first.b64 %0, 1.0;" : "=l"(pol));
        const uint32_t off = blockIdx.x % (1 << GSH);
        l2_prefetch(p.qk + (size_t)((blockIdx.x - off) * MAINP + off * PF0) * (TR * D), PF0 * KBYTES, pol);
    }
    const int w = __shfl_sync(0xffffffffu, (threadIdx.x >> 5) - 1, 0), lane = threadIdx.x & 31;
    if (w < 0) return;
    const uint32_t sb = __shfl_sync(0xffffffffu, smem_u32(smem), 0);
    const uint32_t bar = sb + OFF_BAR;

    if (w < 8 && elect_one()) {
        const uint32_t cnt = w == 4 ? 8 : w == 5 ? NKW + NVW : w == 6 ? NVW : w == 7 ? 2 : 1;
#pragma unroll
        for (int i = 0; i < 16; i++) mbar_init(bar + w * 128 + i * 8, cnt);
        asm volatile("fence.mbarrier_init.release.cluster;" ::: "memory");
    }
    asm volatile("bar.sync 0, %0;" ::"n"(NWARPS * 32) : "memory");

    if ((unsigned)(w - W_V) < NVW) {
        const int v = w - W_V, g = lane >> 3, l = lane & 7;
        const uint32_t up = pin(lane & 16), up2 = pin(lane & 8);
        const uint32_t oV = pin(sb + OFF_V + g * (2 * D * 4) + v * 128 + l * 16), oP = pin(S_PV + g * 8);
        const uint32_t col = pin(v * 32 + l * 4 + (up ? 2 : 0) + (up2 ? 1 : 0));
        const uint32_t oG = pin(S_G + col * 4);
        __nv_bfloat16* const outp = pin(p.out + col);
        uint32_t* const mailp = pin(g_mail + col);
        float a0 = 0.f, a1 = 0.f, a2 = 0.f, a3 = 0.f;
        uint32_t vb = bar, vt = oV, vph = 0, seg = 0;
        uint32_t s = sb + OFF_SEG, t0 = 0;
        mbar_wait(bar + B_PR, 0);
        uint2 bd = lds64(s + S_BD);
        uint2 pv = lds64(s + oP);
        bool ready = false;
        int4 x0, x1;
        auto load_tile = [&]() {
            if (!ready) mbar_wait(vb + B_FV, vph);
            x0 = lds128(vt);
            x1 = lds128(vt + D * 4);
            __syncwarp();
            if (lane == 0) mbar_arrive(vb + B_EV);
            vb += 8; vt += KBYTES;
            if (vb == bar + NV * 8) { vb = bar; vt = oV; vph ^= 1; }
            ready = mbar_test(vb + B_FV, vph);
        };
        auto fma_tile = [&]() {
            const float pv0 = __uint_as_float(pv.x), pv1 = __uint_as_float(pv.y);
            a0 = fmaf(pv1, (float)x1.x, fmaf(pv0, (float)x0.x, a0));
            a1 = fmaf(pv1, (float)x1.y, fmaf(pv0, (float)x0.y, a1));
            a2 = fmaf(pv1, (float)x1.z, fmaf(pv0, (float)x0.z, a2));
            a3 = fmaf(pv1, (float)x1.w, fmaf(pv0, (float)x0.w, a3));
        };
        for (uint32_t batch = 1; !(bd.y & F_END); batch++) {
            const uint32_t n = bd.y & F_NT, sbar = bar + (seg % NSEG) * 8, sph = (seg / NSEG) & 1;
            const bool last = bd.y & F_LAST;
            const uint32_t seg2 = seg + last, t2 = last ? 0 : t0 + n;
            const uint32_t s2 = sb + OFF_SEG + (seg2 % NSEG) * SEG_BYTES;
            const uint32_t prb = bar + B_PR + (batch % NBAT) * 8, prp = (batch / NBAT) & 1;
            const float alpha = __uint_as_float(bd.x);
            a0 *= alpha; a1 *= alpha; a2 *= alpha; a3 *= alpha;
#pragma unroll 1
            for (uint32_t i = 1; i < n; i++) {
                load_tile();
                const uint2 pn = lds64(s + oP + (t0 + i) * (TR * 4));
                fma_tile();
                pv = pn;
            }
            load_tile();
            const bool early = mbar_test(sbar + B_FC, sph);
            const bool next = mbar_test(prb, prp);
            fma_tile();
            if (last) {
                const float u0 = (up ? a2 : a0) + __shfl_xor_sync(0xffffffffu, up ? a0 : a2, 16);
                const float u1 = (up ? a3 : a1) + __shfl_xor_sync(0xffffffffu, up ? a1 : a3, 16);
                if (!early) mbar_wait(sbar + B_FC, sph);
                const int4 cf = lds128(s + S_CF);
                const uint32_t gv = lds32(s + oG);
                const float u = (up2 ? u1 : u0) + __shfl_xor_sync(0xffffffffu, up2 ? u0 : u1, 8);
                const float gj = (bd.y & (F_SEMI | F_FIN)) ? __uint_as_float(gv) : 0.f;
                const float o = fmaf(u, __int_as_float(cf.x), fmaf(gj, __int_as_float(cf.y), __int_as_float(cf.z)));
                if (bd.y & F_FIN) {
                    const __nv_bfloat16 r = __float2bfloat16_rn(o);
                    asm volatile("st.global.b16 [%0], %1;" ::"l"(outp + (bd.y >> 12)), "h"(*(const uint16_t*)&r) : "memory");
                    if (cf.w & 2) return;
                } else {
                    mail_put(mailp + (bd.y >> 12), o, cf.w & 3);
                    if (col < REC - D) mail_put(mailp + (bd.y >> 12) + D, __int_as_float(cf.w), cf.w & 3);
                }
                a0 = a1 = a2 = a3 = 0.f;
                __syncwarp();
                if (lane == 0) mbar_arrive(sbar + B_SE);
            }
            if (!next) mbar_wait(prb, prp);
            bd = lds64(s2 + S_BD + t2 * 8);
            pv = lds64(s2 + oP + t2 * (TR * 4));
            s = s2; t0 = t2; seg = seg2;
        }
    } else if (w == W_S) {
        uint32_t batch = 0;
        for (uint32_t seg = 0;; seg++) {
            const uint32_t s = sb + OFF_SEG + (seg % NSEG) * SEG_BYTES, sbar = bar + (seg % NSEG) * 8;
            const uint32_t sph = (seg / NSEG) & 1;
            mbar_wait(sbar + B_HDR, sph);
            const int4 desc = lds128(s + S_DESC);
            if (desc.y & F_END) {
                if (lane == 0) {
                    sts64(s + S_BD, 0.f, __uint_as_float(F_END));
                    mbar_arrive(bar + B_PR + (batch % NBAT) * 8);
                }
                break;
            }
            float m = NEG, L = 0.f, C = 0.f;
            const uint32_t head = (uint32_t)desc.x / TPH, index = (desc.y & F_FIN) ? head * D : (head * NM + desc.z) * REC;
            const int nt = desc.y & F_NT;
#pragma unroll 1
            for (int t0 = 0; t0 < nt; t0 += 4, batch++) {
                const int n = min(4, nt - t0);
                const bool valid = lane < n * TR;
                const uint32_t tl = t0 + (valid ? lane >> 3 : 0), row = tl * TR + (lane & 7);
                const uint32_t sc = s + S_SC + (((tl << (desc.w & 255)) + (desc.w >> 8)) * TR + (lane & 7)) * 2;
                const float vs = bf_lo(lds16(sc + 2 * SCB)), vz = bf_lo(lds16(sc + 3 * SCB));
                mbar_wait(bar + B_LG + (batch % NBAT) * 8, (batch / NBAT) & 1);
                const int4 part = lds128(s + S_LG + row * 16);
                const float dot = (__int_as_float(part.x) + __int_as_float(part.y)) + (__int_as_float(part.z) + __int_as_float(part.w));
                const float sv = rbf(rbf(dot) * 0.07216878364870322f) * LOG2E;
                int key = __float_as_int(fmaxf(m, sv));
                key ^= (key >> 31) & 0x7fffffff;
                key = __reduce_max_sync(0xffffffffu, key);
                const float mn = __int_as_float(key ^ ((key >> 31) & 0x7fffffff));
                const float alpha = ex2(m - mn), pr = ex2(sv - mn), pv = pr * vs;
                m = mn;
                sts32(s + S_PV + row * 4, pv);
                if (lane == 0)
                    sts64(s + S_BD + t0 * 8, alpha,
                          __uint_as_float(n | (t0 + n < nt ? 0 : index << 12 | F_LAST | (desc.y & (F_SEMI | F_FIN)))));
                __syncwarp();
                if (lane == 0) mbar_arrive(bar + B_PR + (batch % NBAT) * 8);
                L = fmaf(L, alpha, valid ? pr : 0.f);
                C = fmaf(C, alpha, valid ? pv * vz : 0.f);
            }
#pragma unroll
            for (int o = 16; o > 0; o >>= 1) {
                L += __shfl_xor_sync(0xffffffffu, L, o);
                C += __shfl_xor_sync(0xffffffffu, C, o);
            }
            mbar_wait(sbar + B_GD, sph);
            uint32_t tag = lds32(sb + OFF_TAG) | ((desc.y & F_SEMI) ? 2 : 0);
            if ((desc.y & F_FIN) && mbar_test(bar + B_HDR + ((seg + 1) % NSEG) * 8, ((seg + 1) / NSEG) & 1))
                tag |= lds32(sb + OFF_SEG + ((seg + 1) % NSEG) * SEG_BYTES + S_DESC + 4) / (F_END / 2);
            const float gl = (desc.y & (F_SEMI | F_FIN)) ? __uint_as_float(lds32(s + S_G + D * 4)) : -3.4e38f;
            const float M = fmaxf(m, gl), e = ex2(m - M), a = ex2(gl - M);
            const float W = fmaf(L, e, a), inv = rcp(W);
            if (lane == 0)
                sts128(s + S_CF, __float_as_uint(e * inv), __float_as_uint(a * inv), __float_as_uint(-C * e * inv),
                       (__float_as_uint(M + lg2(W)) & ~3u) | tag);
            __syncwarp();
            if (lane == 0) mbar_arrive(sbar + B_FC);
        }
    } else if ((unsigned)(w - W_G) < NGW) {
        if (w == W_G) {
            if (lane == 0) sts32(sb + OFF_TAG, __uint_as_float(~*(volatile unsigned int*)&g_epoch & 1));
        } else {
            mbar_wait(bar + B_GD, 0);
        }
        for (uint32_t seg = w - W_G;; seg += NGW) {
            const uint32_t s = sb + OFF_SEG + (seg % NSEG) * SEG_BYTES, sbar = bar + (seg % NSEG) * 8;
            mbar_wait(sbar + B_HDR, (seg / NSEG) & 1);
            const int4 desc = lds128(s + S_DESC);
            if (desc.y & F_END) break;
            if (desc.y & (F_SEMI | F_FIN)) {
                const uint32_t tag = lds32(sb + OFF_TAG) | ((desc.y & F_FIN) ? 2 : 0);
                const int cnt = (desc.y & F_FIN) ? 1 : NM;
                const uint32_t* mail = g_mail + (uint32_t)desc.x / TPH * (NM * REC);
                float M = NEG, W = 0.f, O[6] = {0.f, 0.f, 0.f, 0.f, 0.f, 0.f};
#pragma unroll 1
                for (int i0 = 0; i0 < cnt; i0 += GB, mail += GB * REC) {
                    uint2 pk[3 * GB];
                    uint32_t ls[GB], stale;
                    int it = 0;
                    do {
                        stale = 0;
#pragma unroll
                        for (int i = 0; i < GB; i++) {
                            ls[i] = 0xff7ffffcu | tag;
                            pk[3 * i] = pk[3 * i + 1] = pk[3 * i + 2] = make_uint2(tag, tag);
                            if (i0 + i < cnt) {
                                asm volatile("ld.relaxed.gpu.global.u32 %0, [%1];" : "=r"(ls[i]) : "l"(mail + i * REC + D) : "memory");
#pragma unroll
                                for (int k = 0; k < 3; k++)
                                    asm volatile("ld.relaxed.gpu.global.v2.u32 {%0,%1}, [%2];"
                                                 : "=r"(pk[3 * i + k].x), "=r"(pk[3 * i + k].y)
                                                 : "l"(mail + i * REC + k * 64 + lane * 2) : "memory");
                            }
                        }
#pragma unroll
                        for (int i = 0; i < GB; i++) stale |= ls[i] ^= tag;
#pragma unroll
                        for (int i = 0; i < 3 * GB; i++) stale |= (pk[i].x ^= tag) | (pk[i].y ^= tag);
                        if (++it > (1 << 22)) __trap();
                    } while (stale & 3);
                    float Mn = M;
#pragma unroll
                    for (int i = 0; i < GB; i++) Mn = fmaxf(Mn, __uint_as_float(ls[i]));
                    const float a = ex2(M - Mn);
                    M = Mn; W *= a;
#pragma unroll
                    for (int i = 0; i < 6; i++) O[i] *= a;
#pragma unroll
                    for (int i = 0; i < GB; i++) {
                        const float e = ex2(__uint_as_float(ls[i]) - M);
                        W += e;
#pragma unroll
                        for (int k = 0; k < 3; k++) {
                            O[2 * k] = fmaf(e, __uint_as_float(pk[3 * i + k].x), O[2 * k]);
                            O[2 * k + 1] = fmaf(e, __uint_as_float(pk[3 * i + k].y), O[2 * k + 1]);
                        }
                    }
                }
                const float inv = rcp(W);
#pragma unroll
                for (int k = 0; k < 3; k++) sts64(s + S_G + k * 256 + lane * 8, O[2 * k] * inv, O[2 * k + 1] * inv);
                if (lane == 0) sts32(s + S_G + D * 4, M + lg2(W));
            }
            __syncwarp();
            if (lane == 0) mbar_arrive(sbar + B_GD);
        }
    } else if (w / NKW == 0) {
        const int g = lane >> 3, l = lane & 7, godd = g & 1, row = 2 * g + (w & 1);
        const uint32_t sgA = pin(godd ? 0x3f803f80u : 0xbf80bf80u), sgB = pin(godd ? 0xbf80bf80u : 0x3f803f80u);
        const uint32_t oKA = pin(sb + row * (D * 4) + l * 16 + godd * 384), oKB = pin(oKA - godd * 768 + 384);
        const uint32_t oCA = pin(sb + T_C + row * (D * 2) + l * 8 + godd * 192), oCB = pin(oCA - godd * 384 + 192);
        const uint32_t oL = pin(S_LG + row * 16 + (l >> 2) * 8 + (l & 1) * 4), oS = pin(S_SC + row * 2);
        const bool own = (l & 3) == g, hi = l & 4, keep = ((l ^ g) & 2) == 0;
        uint32_t kslot = w >> 1, j = kslot, batch0 = 0, kph = 0;
        for (uint32_t seg = 0;; seg++) {
            const uint32_t s = sb + OFF_SEG + (seg % NSEG) * SEG_BYTES, sbar = bar + (seg % NSEG) * 8;
            mbar_wait(sbar + B_HDR, (seg / NSEG) & 1);
            const int4 desc = lds128(s + S_DESC);
            if (desc.y & F_END) break;
            const uint32_t nt = desc.y & F_NT;
            uint2 qr[3];
#pragma unroll
            for (int i = 0; i < 3; i++) {
                const uint32_t oa = l * 8 + godd * 192 + i * 64, ob = oa + 192 - godd * 384;
                const uint2 a = lds64(s + S_Q + oa), b = lds64(s + S_Q + ob);
                const uint2 ca = lds64(sb + OFF_QT + oa), sa = lds64(sb + OFF_QT + QBYTES + oa);
                qr[i].x = rope2(a.x, ca.x, b.x, sa.x, sgA);
                qr[i].y = rope2(a.y, ca.y, b.y, sa.y, sgA);
            }
            for (; j < nt; j += NKW / 2) {
                const uint32_t t = kslot * KSLOT;
                const uint32_t sc = s + oS + ((j << (desc.w & 255)) + (desc.w >> 8)) * (TR * 2);
                const uint32_t ks2 = lds16(sc) * 0x10001u, kz2 = lds16(sc + SCB) * 0x10001u;
                const uint32_t lgb = bar + B_LG + ((batch0 + (j >> 2)) % NBAT) * 8;
                const uint32_t lgc = j == nt - 1 ? 4 - (j & 3) : 1;
                mbar_wait(bar + B_FK + kslot * 8, kph);
                float c[4] = {0.f, 0.f, 0.f, 0.f};
#pragma unroll
                for (int jj = 0; jj < 3; jj++) {
                    const int4 xa = lds128(t + oKA + jj * 128), xb = lds128(t + oKB + jj * 128);
                    const uint2 ca = lds64(t + oCA + jj * 64), cb = lds64(t + oCB + jj * 64);
                    const uint2 sa = lds64(t + oCA + CBYTES + jj * 64), sbv = lds64(t + oCB + CBYTES + jj * 64);
                    const uint32_t a0 = bmul(bsub(i2bf2(xa.x, xa.y), kz2), ks2);
                    const uint32_t a1 = bmul(bsub(i2bf2(xa.z, xa.w), kz2), ks2);
                    const uint32_t b0 = bmul(bsub(i2bf2(xb.x, xb.y), kz2), ks2);
                    const uint32_t b1 = bmul(bsub(i2bf2(xb.z, xb.w), kz2), ks2);
                    mma_bf16(c, rope2(a0, ca.x, b0, sa.x, sgA), rope2(b0, cb.x, a0, sbv.x, sgB),
                             rope2(a1, ca.y, b1, sa.y, sgA), rope2(b1, cb.y, a1, sbv.y, sgB), qr[jj].x, qr[jj].y);
                }
                __syncwarp();
                if (lane == 0) mbar_arrive(bar + B_EK + kslot * 8);
                const float part = own ? (hi ? c[1] : c[0]) : (hi ? c[3] : c[2]);
                if (keep) sts32(s + oL + j * (TR * 16), part);
                __syncwarp();
                if (lane == 0) mbar_arrive(lgb, lgc);
                kslot += NKW / 2;
                if (kslot >= NK) { kslot -= NK; kph ^= 1; }
            }
            j -= nt;
            batch0 += (nt + 3) >> 2;
            __syncwarp();
            if (lane == 0) mbar_arrive(sbar + B_SE);
        }
    } else if (w == W_SCH) {
        if (elect_one()) {
            asm volatile("mbarrier.expect_tx.shared::cta.b64 [%0], %1;" ::"r"(bar + B_HDR), "r"(2 * QBYTES) : "memory");
            uint32_t seg = 0, c = blockIdx.x;
            while (c < NCLAIM) {
                const Claim cl = decode_claim(c);
                const uint32_t s = sb + OFF_SEG + (seg % NSEG) * SEG_BYTES, b = bar + (seg % NSEG) * 8;
                mbar_wait(b + B_SE, ((seg / NSEG) & 1) ^ 1);
                sts128(s + S_DESC, cl.tile0 + cl.off, cl.ntiles | (c >= C_F ? F_FIN : c >= C_S ? F_SEMI : 0), cl.piece,
                       cl.sh | cl.off << 8);
                if (seg) mbar_arrive(bar + B_DS + ((seg - 1) % NSEG) * 8);
                const uint32_t scb = cl.ntiles * TR * 2 << cl.sh, r = cl.tile0 * TR;
                mbar_expect(b + B_HDR, 4 * scb + QBYTES);
                bulk_plain(s + S_Q, p.q + cl.head * D, QBYTES, b + B_HDR);
                bulk_plain(s + S_SC, p.ks + r, scb, b + B_HDR);
                bulk_plain(s + S_SC + SCB, p.kz + r, scb, b + B_HDR);
                bulk_plain(s + S_SC + 2 * SCB, p.vs + r, scb, b + B_HDR);
                bulk_plain(s + S_SC + 3 * SCB, p.vz + r, scb, b + B_HDR);
                if (seg == 0) {
                    bulk_plain(sb + OFF_QT, p.qcos, QBYTES, bar + B_HDR);
                    bulk_plain(sb + OFF_QT + QBYTES, p.qsin, QBYTES, bar + B_HDR);
                    mbar_wait(bar + B_GD, 0);
                }
                mbar_wait(bar + B_GO, seg & 1);
                seg++;
                const unsigned nx = atomicInc(&g_queue, NCLAIM - 1);
                if (nx == NCLAIM - 1) g_epoch = lds32(sb + OFF_TAG);
                c = gridDim.x + nx;
            }
#pragma unroll 1
            for (int i = 0; i < NGW; i++, seg++) {
                const uint32_t s = sb + OFF_SEG + (seg % NSEG) * SEG_BYTES, b = bar + (seg % NSEG) * 8;
                mbar_wait(b + B_SE, ((seg / NSEG) & 1) ^ 1);
                sts128(s + S_DESC, 0, F_END, 0, 0);
                mbar_arrive(bar + B_DS + ((seg - 1) % NSEG) * 8);
                mbar_arrive(b + B_HDR);
            }
        }
    } else {
        if (elect_one()) {
            uint64_t pol;
            asm volatile("createpolicy.fractional.L2::evict_first.b64 %0, 1.0;" : "=l"(pol));
            uint32_t kslot = 0, vslot = 0, kph = 1, vph = 1;
            int pend[LEAD];
#pragma unroll
            for (int i = 0; i < LEAD; i++) pend[i] = -1;
            auto issue_v = [&]() {
                if (pend[0] >= 0) {
                    const uint32_t b = bar + vslot * 8;
                    mbar_wait(b + B_EV, vph);
                    mbar_wait(b + B_FV + (vslot >= WIN ? 0 : NV * 8) - WIN * 8, vph ^ (vslot >= WIN));
                    mbar_expect(b + B_FV, KBYTES);
                    bulk_stream(sb + OFF_V + vslot * KBYTES, p.qv + (size_t)pend[0] * (TR * D), KBYTES, b + B_FV, pol);
                    if (++vslot == NV) { vslot = 0; vph ^= 1; }
                }
#pragma unroll
                for (int i = 0; i + 1 < LEAD; i++) pend[i] = pend[i + 1];
                pend[LEAD - 1] = -1;
            };
            const Claim c0 = decode_claim(blockIdx.x % C_S);
            int4 desc = make_int4(c0.tile0 + c0.off, c0.ntiles, 0, GSH);
            for (uint32_t seg = 0; !(desc.y & F_END); seg++) {
                uint32_t tile = desc.x;
#pragma unroll 1
                for (int left = desc.y & F_NT; left > 0; left--, tile += 1u << (desc.w & 255)) {
                    if (left == 1) mbar_arrive(bar + B_GO);
                    const uint32_t t = sb + kslot * KSLOT, b = bar + kslot * 8;
                    const uint32_t ro = (tile % TPH) * (TR * D);
                    mbar_wait(b + B_EK, kph);
                    mbar_expect(b + B_FK, KSLOT);
                    bulk_stream(t, p.qk + (size_t)tile * (TR * D), KBYTES, b + B_FK, pol);
                    bulk_plain(t + T_C, p.kcos + ro, CBYTES, b + B_FK);
                    bulk_plain(t + T_S, p.ksin + ro, CBYTES, b + B_FK);
                    if (++kslot == NK) { kslot = 0; kph ^= 1; }
                    pend[LEAD - 1] = tile;
                    issue_v();
                }
                mbar_wait(bar + B_DS + (seg % NSEG) * 8, (seg / NSEG) & 1);
                desc = lds128(sb + OFF_SEG + ((seg + 1) % NSEG) * SEG_BYTES + S_DESC);
            }
#pragma unroll 1
            for (int i = 1; i < LEAD; i++) issue_v();
        }
    }
}

}

extern "C" void kernel_launch(void* const* d_in, const int* in_sizes, int n_in, void* d_out, int out_size) {
    (void)in_sizes; (void)n_in; (void)out_size;
    static int sms = 0;
    if (sms == 0) {
        int dev = 0;
        cudaGetDevice(&dev);
        cudaDeviceGetAttribute(&sms, cudaDevAttrMultiProcessorCount, dev);
        cudaFuncSetAttribute(kv_rope_decode_kernel, cudaFuncAttributeMaxDynamicSharedMemorySize, SMEM_BYTES);
    }
    Params p;
    p.q    = (const __nv_bfloat16*)d_in[0];
    p.qk   = (const int*)d_in[1];
    p.ks   = (const __nv_bfloat16*)d_in[2];
    p.kz   = (const __nv_bfloat16*)d_in[3];
    p.qv   = (const int*)d_in[4];
    p.vs   = (const __nv_bfloat16*)d_in[5];
    p.vz   = (const __nv_bfloat16*)d_in[6];
    p.qcos = (const __nv_bfloat16*)d_in[7];
    p.qsin = (const __nv_bfloat16*)d_in[8];
    p.kcos = (const __nv_bfloat16*)d_in[9];
    p.ksin = (const __nv_bfloat16*)d_in[10];
    p.out  = (__nv_bfloat16*)d_out;
    kv_rope_decode_kernel<<<sms, NTHREADS, SMEM_BYTES>>>(p);
}
```

```cpp
#include <cuda_runtime.h>
#include <cuda_bf16.h>
#include <stdint.h>

namespace {

constexpr int D      = 192;
constexpr int SKV    = 2048;
constexpr int NHEAD  = 256;
constexpr int TR     = 16;
constexpr int TPH    = SKV / TR;
constexpr int NKW    = 4;
constexpr int NVW    = 6;
constexpr int NGW    = 2;
constexpr int NK     = 4;
constexpr int NV     = 3;
constexpr int WIN    = 2;
constexpr int LEAD   = 3;
constexpr int NSEG   = 8;
constexpr int SEGT   = 8;
constexpr int NBAT   = 16;
constexpr int W_V = NKW, W_PROD = W_V + NVW, W_S = W_PROD + 1, W_G = W_S + 1, W_SCH = W_G + NGW, NWARPS = W_SCH + 1;
constexpr int NTHREADS = 32 + NWARPS * 32;

constexpr int MAINP  = 8;
constexpr int PF0    = 18432;
constexpr int GSH    = 2;
__host__ __device__ constexpr int semi_size(uint32_t h) { return (0x44445566u >> (h / 32 * 4)) & 15; }
__host__ __device__ constexpr int fin_size(uint32_t h) { return (0x12224466u >> (h / 32 * 4)) & 15; }
__host__ __device__ constexpr uint32_t cut_group(uint32_t h) { return (3 + 2 * h - h / 8) % 4; }
constexpr int NM     = TPH / MAINP;
static_assert(NM >> GSH == 4, "four interleave groups per head");
constexpr int C_S    = NHEAD * NM, C_F = C_S + NHEAD, NCLAIM = C_F + NHEAD;

constexpr int KBYTES = TR * D * 4;
constexpr int CBYTES = TR * D * 2;
constexpr int QBYTES = D * 2;
constexpr int T_C = KBYTES, T_S = T_C + CBYTES, KSLOT = T_S + CBYTES;
constexpr int SCB = SEGT * TR * 2 << GSH;
static_assert(MAINP <= SEGT && semi_size(0) <= SEGT && fin_size(0) <= SEGT && GSH >= 1, "a piece fills one segment slot");
constexpr int S_Q    = 0;
constexpr int S_SC   = S_Q + QBYTES;
constexpr int S_DESC = S_SC + 4 * SCB;
constexpr int S_BD   = S_DESC + 16;
constexpr int S_LG   = S_BD + SEGT * 8;
constexpr int S_PV   = S_LG + SEGT * TR * 16;
constexpr int S_G    = S_PV + SEGT * TR * 4;
constexpr int S_CF   = S_G + (D + 4) * 4;
constexpr int SEG_BYTES = (S_CF + 16 + 127) / 128 * 128;
constexpr int OFF_V = NK * KSLOT, OFF_SEG = OFF_V + NV * KBYTES, OFF_QT = OFF_SEG + NSEG * SEG_BYTES,
              OFF_TAG = OFF_QT + 2 * QBYTES, OFF_BAR = OFF_TAG + 16;
constexpr int B_FK = 0, B_DS = 64, B_PR = 128, B_HDR = 256, B_GD = 320, B_FC = 384, B_FV = 448, B_GO = 504,
              B_LG = 512, B_SE = 640, B_EV = 768, B_EK = 896;
constexpr int SMEM_BYTES = OFF_BAR + 1024;
static_assert(NK <= 8 && NV <= 7 && W_PROD >= 8 && NSEG == 8 && NBAT == 16, "barrier layout");
static_assert(SMEM_BYTES <= 232448 && SMEM_BYTES > 232448 / 2, "one CTA per SM");
static_assert(NSEG % NGW == 0 && NVW * 32 == D && LEAD >= 1, "cfg");
static_assert(WIN < NV && LEAD + NV >= 2 && LEAD + NV < NBAT && LEAD < NSEG, "no ring can be lapped or starved");

__device__ unsigned int g_queue;
constexpr int REC = 200, GB = 4;
__device__ unsigned int g_epoch;
__device__ __align__(32) uint32_t g_mail[NHEAD * NM * REC];

__device__ __forceinline__ uint32_t smem_u32(const void* p) { return (uint32_t)__cvta_generic_to_shared(p); }
__device__ __forceinline__ uint32_t pin(uint32_t x) {
    return __shfl_sync(0xffffffffu, x, threadIdx.x & 31);
}
template <class T> __device__ __forceinline__ T* pin(T* p) {
    return (T*)__shfl_sync(0xffffffffu, (unsigned long long)p, threadIdx.x & 31);
}
__device__ __forceinline__ bool elect_one() {
    uint32_t pred;
    asm volatile("{\n.reg .pred p;\nelect.sync _|p, 0xffffffff;\nselp.u32 %0, 1, 0, p;\n}" : "=r"(pred));
    return pred;
}
__device__ __forceinline__ void mbar_init(uint32_t bar, uint32_t cnt) {
    asm volatile("mbarrier.init.shared::cta.b64 [%0], %1;" ::"r"(bar), "r"(cnt) : "memory");
}
__device__ __forceinline__ void mbar_expect(uint32_t bar, uint32_t bytes) {
    asm volatile("mbarrier.arrive.expect_tx.shared::cta.b64 _, [%0], %1;" ::"r"(bar), "r"(bytes) : "memory");
}
__device__ __forceinline__ void mbar_arrive(uint32_t bar) {
    asm volatile("mbarrier.arrive.shared::cta.b64 _, [%0];" ::"r"(bar) : "memory");
}
__device__ __forceinline__ void mbar_arrive(uint32_t bar, uint32_t cnt) {
    asm volatile("mbarrier.arrive.shared::cta.b64 _, [%0], %1;" ::"r"(bar), "r"(cnt) : "memory");
}
__device__ __forceinline__ bool mbar_test(uint32_t bar, uint32_t parity) {
    uint32_t ok;
    asm volatile("{\n.reg .pred p;\nmbarrier.test_wait.parity.shared::cta.b64 p, [%1], %2;\nselp.u32 %0, 1, 0, p;\n}"
                 : "=r"(ok) : "r"(bar), "r"(parity) : "memory");
    return ok;
}
__device__ __forceinline__ void mbar_wait(uint32_t bar, uint32_t parity) {
    asm volatile("{\n.reg .pred p;\n.reg .u32 n;\n"
                 "mbarrier.try_wait.parity.shared::cta.b64 p, [%0], %1;\n"
                 "@p bra DONE;\n"
                 "mov.u32 n, 0;\n"
                 "LOOP:\n"
                 "mbarrier.try_wait.parity.shared::cta.b64 p, [%0], %1;\n"
                 "@p bra DONE;\n"
                 "add.u32 n, n, 1;\n"
                 "setp.lt.u32 p, n, 0x400000;\n"
                 "@p bra LOOP;\n"
                 "trap;\n"
                 "DONE:\n}" ::"r"(bar), "r"(parity) : "memory");
}
__device__ __forceinline__ void bulk_stream(uint32_t dst, const void* src, uint32_t bytes, uint32_t bar, uint64_t pol) {
    asm volatile("cp.async.bulk.shared::cluster.global.mbarrier::complete_tx::bytes.L2::cache_hint [%0], [%1], %2, [%3], %4;"
                 ::"r"(dst), "l"(src), "r"(bytes), "r"(bar), "l"(pol) : "memory");
}
__device__ __forceinline__ void bulk_plain(uint32_t dst, const void* src, uint32_t bytes, uint32_t bar) {
    asm volatile("cp.async.bulk.shared::cluster.global.mbarrier::complete_tx::bytes [%0], [%1], %2, [%3];"
                 ::"r"(dst), "l"(src), "r"(bytes), "r"(bar) : "memory");
}
__device__ __forceinline__ void l2_prefetch(const void* src, uint32_t bytes, uint64_t pol) {
    asm volatile("cp.async.bulk.prefetch.L2.global.L2::cache_hint [%0], %1, %2;" ::"l"(src), "r"(bytes), "l"(pol) : "memory");
}
__device__ __forceinline__ void l2_prefetch(const void* src, uint32_t bytes) {
    asm volatile("cp.async.bulk.prefetch.L2.global [%0], %1;" ::"l"(src), "r"(bytes) : "memory");
}
__device__ __forceinline__ int4 lds128(uint32_t a) {
    int4 v;
    asm volatile("ld.shared.v4.s32 {%0,%1,%2,%3}, [%4];" : "=r"(v.x), "=r"(v.y), "=r"(v.z), "=r"(v.w) : "r"(a));
    return v;
}
__device__ __forceinline__ uint2 lds64(uint32_t a) {
    uint2 v;
    asm volatile("ld.shared.v2.u32 {%0,%1}, [%2];" : "=r"(v.x), "=r"(v.y) : "r"(a));
    return v;
}
__device__ __forceinline__ uint32_t lds32(uint32_t a) {
    uint32_t v;
    asm volatile("ld.shared.u32 %0, [%1];" : "=r"(v) : "r"(a));
    return v;
}
__device__ __forceinline__ uint32_t lds16(uint32_t a) {
    uint16_t v;
    asm volatile("ld.shared.u16 %0, [%1];" : "=h"(v) : "r"(a));
    return v;
}
__device__ __forceinline__ void sts32(uint32_t a, float x) {
    asm volatile("st.shared.f32 [%0], %1;" ::"r"(a), "f"(x) : "memory");
}
__device__ __forceinline__ void sts128(uint32_t a, uint32_t x, uint32_t y, uint32_t z, uint32_t w) {
    asm volatile("st.shared.v4.u32 [%0], {%1,%2,%3,%4};" ::"r"(a), "r"(x), "r"(y), "r"(z), "r"(w) : "memory");
}
__device__ __forceinline__ void sts64(uint32_t a, float x, float y) {
    asm volatile("st.shared.v2.f32 [%0], {%1,%2};" ::"r"(a), "f"(x), "f"(y) : "memory");
}
__device__ __forceinline__ float bf_lo(uint32_t v) { return __uint_as_float(v << 16); }
__device__ __forceinline__ float rbf(float x) {
    uint32_t d; asm("cvt.rn.bf16x2.f32 %0, %1, %2;" : "=r"(d) : "f"(x), "f"(0.f)); return __uint_as_float(d);
}
__device__ __forceinline__ float rcp(float x) {
    float y;
    asm("rcp.approx.ftz.f32 %0, %1;" : "=f"(y) : "f"(x));
    return y;
}
__device__ __forceinline__ float lg2(float x) {
    float y;
    asm("lg2.approx.ftz.f32 %0, %1;" : "=f"(y) : "f"(x));
    return y;
}
__device__ __forceinline__ float ex2(float x) {
    float y;
    asm("ex2.approx.ftz.f32 %0, %1;" : "=f"(y) : "f"(x));
    return y;
}
__device__ __forceinline__ uint32_t bmul(uint32_t a, uint32_t b) {
    uint32_t d; asm("mul.rn.bf16x2 %0, %1, %2;" : "=r"(d) : "r"(a), "r"(b)); return d;
}
__device__ __forceinline__ uint32_t bsub(uint32_t a, uint32_t b) {
    uint32_t d; asm("sub.rn.bf16x2 %0, %1, %2;" : "=r"(d) : "r"(a), "r"(b)); return d;
}
__device__ __forceinline__ uint32_t bfma(uint32_t a, uint32_t b, uint32_t c) {
    uint32_t d; asm("fma.rn.bf16x2 %0, %1, %2, %3;" : "=r"(d) : "r"(a), "r"(b), "r"(c)); return d;
}
__device__ __forceinline__ uint32_t i2bf2(int lo, int hi) {
    uint32_t d; asm("cvt.rn.bf16x2.f32 %0, %1, %2;" : "=r"(d) : "f"((float)hi), "f"((float)lo)); return d;
}
__device__ __forceinline__ uint32_t rope2(uint32_t x, uint32_t c, uint32_t y, uint32_t s, uint32_t sg) {
    return bfma(bmul(y, s), sg, bmul(x, c));
}
__device__ __forceinline__ void mma_bf16(float (&c)[4], uint32_t a0, uint32_t a1, uint32_t a2, uint32_t a3,
                                         uint32_t b0, uint32_t b1) {
    asm("mma.sync.aligned.m16n8k16.row.col.f32.bf16.bf16.f32 {%0,%1,%2,%3}, {%4,%5,%6,%7}, {%8,%9}, {%0,%1,%2,%3};"
        : "+f"(c[0]), "+f"(c[1]), "+f"(c[2]), "+f"(c[3])
        : "r"(a0), "r"(a1), "r"(a2), "r"(a3), "r"(b0), "r"(b1));
}
__device__ __forceinline__ void mail_put(uint32_t* p, float x, uint32_t tag) {
    asm volatile("st.relaxed.gpu.global.u32 [%0], %1;" ::"l"(p), "r"((__float_as_uint(x) & ~3u) | tag) : "memory");
}

struct Claim { uint32_t head, tile0, piece, sh, off; int ntiles; };

__device__ __forceinline__ Claim decode_claim(uint32_t c) {
    Claim cl;
    cl.sh = cl.off = 0;
    if (c < C_S) {
        cl.head = c / NM; cl.piece = c % NM; cl.sh = GSH; cl.off = c % (1 << GSH); cl.tile0 = (c - cl.off) * MAINP;
        cl.ntiles = MAINP;
        if (cl.piece >> GSH == cut_group(cl.head))
            cl.ntiles -= (semi_size(cl.head) + fin_size(cl.head) + cl.off) >> GSH;
    } else {
        cl.head = (c - C_S) % NHEAD; cl.piece = 0;
        cl.ntiles = fin_size(cl.head); cl.tile0 = cl.head * TPH + (cut_group(cl.head) + 1) * (TPH / 4) - cl.ntiles;
        if (c < C_F) { cl.ntiles = semi_size(cl.head); cl.tile0 -= cl.ntiles; }
    }
    return cl;
}

struct Params {
    const int* qk; const __nv_bfloat16* kcos; const __nv_bfloat16* ksin; const int* qv;
    const __nv_bfloat16* ks; const __nv_bfloat16* kz; const __nv_bfloat16* vs; const __nv_bfloat16* vz;
    const __nv_bfloat16* q; const __nv_bfloat16* qcos; const __nv_bfloat16* qsin;
    __nv_bfloat16* out;
};

constexpr float NEG = -3.0e38f;
constexpr float LOG2E = 1.4426950408889634f;
constexpr int F_NT = 31, F_LAST = 64, F_SEMI = 128, F_FIN = 256, F_END = 512;
static_assert(NHEAD * NM * REC < (1 << 20), "batch descriptor");

__global__ void __launch_bounds__(NTHREADS, 1)
kv_rope_decode_kernel(const Params p) {
    extern __shared__ __align__(128) unsigned char smem[];
    if (threadIdx.x < 32 && elect_one()) {
        l2_prefetch(p.kcos + (blockIdx.x % TPH) * (TR * D), CBYTES);
        l2_prefetch(p.ksin + (blockIdx.x % TPH) * (TR * D), CBYTES);
        uint64_t pol;
        asm volatile("createpolicy.fractional.L2::evict_first.b64 %0, 1.0;" : "=l"(pol));
        const uint32_t off = blockIdx.x % (1 << GSH);
        l2_prefetch(p.qk + ((blockIdx.x - off) * (MAINP * TR * D) + off * (PF0 / 4)), PF0, pol);
    }
    const int w = __shfl_sync(0xffffffffu, (threadIdx.x >> 5) - 1, 0), lane = threadIdx.x & 31;
    if (w < 0) return;
    const uint32_t sb = __shfl_sync(0xffffffffu, smem_u32(smem), 0);
    const uint32_t bar = sb + OFF_BAR;

    if (w < 8 && elect_one()) {
        const uint32_t cnt = w == 4 ? 8 : w == 5 ? NKW + NVW : w == 6 ? NVW : w == 7 ? NKW : 1;
#pragma unroll
        for (int i = 0; i < 16; i++) mbar_init(bar + w * 128 + i * 8, cnt);
        asm volatile("fence.mbarrier_init.release.cluster;" ::: "memory");
    }
    asm volatile("bar.sync 0, %0;" ::"n"(NWARPS * 32) : "memory");

    if ((unsigned)(w - W_V) < NVW) {
        const int v = w - W_V, g = lane >> 3, l = lane & 7;
        const uint32_t up = pin(lane & 16), up2 = pin(lane & 8);
        const uint32_t oV = pin(sb + OFF_V + g * (4 * D * 4) + v * 128 + l * 16), oP = pin(S_PV + g * 16);
        const uint32_t col = pin(v * 32 + l * 4 + (up ? 2 : 0) + (up2 ? 1 : 0));
        const uint32_t oG = pin(S_G + col * 4);
        __nv_bfloat16* const outp = pin(p.out + col);
        uint32_t* const mailp = pin(g_mail + col);
        float a0 = 0.f, a1 = 0.f, a2 = 0.f, a3 = 0.f;
        uint32_t vb = bar, vt = oV, vph = 0, seg = 0;
        uint32_t s = sb + OFF_SEG, t0 = 0;
        mbar_wait(bar + B_PR, 0);
        uint2 bd = lds64(s + S_BD);
        int4 pv = lds128(s + oP);
        bool ready = false;
        int4 x0, x1, x2, x3;
        auto load_tile = [&]() {
            if (!ready) mbar_wait(vb + B_FV, vph);
            x0 = lds128(vt);
            x1 = lds128(vt + D * 4);
            x2 = lds128(vt + D * 8);
            x3 = lds128(vt + D * 12);
            __syncwarp();
            if (lane == 0) mbar_arrive(vb + B_EV);
            vb += 8; vt += KBYTES;
            if (vb == bar + NV * 8) { vb = bar; vt = oV; vph ^= 1; }
            ready = mbar_test(vb + B_FV, vph);
        };
        auto fma_tile = [&]() {
            const float p0 = __int_as_float(pv.x), p1 = __int_as_float(pv.y), p2 = __int_as_float(pv.z), p3 = __int_as_float(pv.w);
            a0 = fmaf(p3, (float)x3.x, fmaf(p2, (float)x2.x, fmaf(p1, (float)x1.x, fmaf(p0, (float)x0.x, a0))));
            a1 = fmaf(p3, (float)x3.y, fmaf(p2, (float)x2.y, fmaf(p1, (float)x1.y, fmaf(p0, (float)x0.y, a1))));
            a2 = fmaf(p3, (float)x3.z, fmaf(p2, (float)x2.z, fmaf(p1, (float)x1.z, fmaf(p0, (float)x0.z, a2))));
            a3 = fmaf(p3, (float)x3.w, fmaf(p2, (float)x2.w, fmaf(p1, (float)x1.w, fmaf(p0, (float)x0.w, a3))));
        };
        for (uint32_t batch = 1; !(bd.y & F_END); batch++) {
            const uint32_t n = bd.y & F_NT, sbar = bar + (seg % NSEG) * 8, sph = (seg / NSEG) & 1;
            const bool last = bd.y & F_LAST;
            const uint32_t seg2 = seg + last, t2 = last ? 0 : t0 + n;
            const uint32_t s2 = sb + OFF_SEG + (seg2 % NSEG) * SEG_BYTES;
            const uint32_t prb = bar + B_PR + (batch % NBAT) * 8, prp = (batch / NBAT) & 1;
            const float alpha = __uint_as_float(bd.x);
            a0 *= alpha; a1 *= alpha; a2 *= alpha; a3 *= alpha;
            if (n == 2) {
                load_tile();
                const int4 pn = lds128(s + oP + (t0 + 1) * (TR * 4));
                fma_tile();
                pv = pn;
            }
            load_tile();
            const bool early = mbar_test(sbar + B_FC, sph);
            const bool next = mbar_test(prb, prp);
            fma_tile();
            if (last) {
                const float u0 = (up ? a2 : a0) + __shfl_xor_sync(0xffffffffu, up ? a0 : a2, 16);
                const float u1 = (up ? a3 : a1) + __shfl_xor_sync(0xffffffffu, up ? a1 : a3, 16);
                if (!early) mbar_wait(sbar + B_FC, sph);
                const int4 cf = lds128(s + S_CF);
                const uint32_t gv = lds32(s + oG);
                const float u = (up2 ? u1 : u0) + __shfl_xor_sync(0xffffffffu, up2 ? u0 : u1, 8);
                const float gj = (bd.y & (F_SEMI | F_FIN)) ? __uint_as_float(gv) : 0.f;
                const float o = fmaf(u, __int_as_float(cf.x), fmaf(gj, __int_as_float(cf.y), __int_as_float(cf.z)));
                if (bd.y & F_FIN) {
                    const __nv_bfloat16 r = __float2bfloat16_rn(o);
                    asm volatile("st.global.b16 [%0], %1;" ::"l"(outp + (bd.y >> 12)), "h"(*(const uint16_t*)&r) : "memory");
                    if (cf.w & 2) return;
                } else {
                    mail_put(mailp + (bd.y >> 12), o, cf.w & 3);
                    if (col < REC - D) mail_put(mailp + (bd.y >> 12) + D, __int_as_float(cf.w), cf.w & 3);
                }
                a0 = a1 = a2 = a3 = 0.f;
                __syncwarp();
                if (lane == 0) mbar_arrive(sbar + B_SE);
            }
            if (!next) mbar_wait(prb, prp);
            bd = lds64(s2 + S_BD + t2 * 8);
            pv = lds128(s2 + oP + t2 * (TR * 4));
            s = s2; t0 = t2; seg = seg2;
        }
    } else if (w == W_S) {
        uint32_t batch = 0;
        for (uint32_t seg = 0;; seg++) {
            const uint32_t s = sb + OFF_SEG + (seg % NSEG) * SEG_BYTES, sbar = bar + (seg % NSEG) * 8;
            const uint32_t sph = (seg / NSEG) & 1;
            mbar_wait(sbar + B_HDR, sph);
            const int4 desc = lds128(s + S_DESC);
            if (desc.y & F_END) {
                if (lane == 0) {
                    sts64(s + S_BD, 0.f, __uint_as_float(F_END));
                    mbar_arrive(bar + B_PR + (batch % NBAT) * 8);
                }
                break;
            }
            float m = NEG, L = 0.f, C = 0.f;
            const uint32_t head = (uint32_t)desc.x / TPH, index = (desc.y & F_FIN) ? head * D : (head * NM + desc.z) * REC;
            const int nt = desc.y & F_NT;
#pragma unroll 1
            for (int t0 = 0; t0 < nt; t0 += 2, batch++) {
                const int n = min(2, nt - t0);
                const bool valid = lane < n * TR;
                const uint32_t tl = t0 + (valid ? lane >> 4 : 0), row = tl * TR + (lane & 15);
                const uint32_t sc = s + S_SC + (((tl << (desc.w & 255)) + (desc.w >> 8)) * TR + (lane & 15)) * 2;
                const float vs = bf_lo(lds16(sc + 2 * SCB)), vz = bf_lo(lds16(sc + 3 * SCB));
                mbar_wait(bar + B_LG + (batch % NBAT) * 8, (batch / NBAT) & 1);
                const int4 part = lds128(s + S_LG + row * 16);
                const float dot = (__int_as_float(part.x) + __int_as_float(part.y)) + (__int_as_float(part.z) + __int_as_float(part.w));
                const float sv = rbf(rbf(dot) * 0.07216878364870322f) * LOG2E;
                int key = __float_as_int(fmaxf(m, sv));
                key ^= (key >> 31) & 0x7fffffff;
                key = __reduce_max_sync(0xffffffffu, key);
                const float mn = __int_as_float(key ^ ((key >> 31) & 0x7fffffff));
                const float alpha = ex2(m - mn), pr = ex2(sv - mn), pv = pr * vs;
                m = mn;
                sts32(s + S_PV + row * 4, pv);
                if (lane == 0)
                    sts64(s + S_BD + t0 * 8, alpha,
                          __uint_as_float(n | (t0 + n < nt ? 0 : index << 12 | F_LAST | (desc.y & (F_SEMI | F_FIN)))));
                __syncwarp();
                if (lane == 0) mbar_arrive(bar + B_PR + (batch % NBAT) * 8);
                L = fmaf(L, alpha, valid ? pr : 0.f);
                C = fmaf(C, alpha, valid ? pv * vz : 0.f);
            }
#pragma unroll
            for (int o = 16; o > 0; o >>= 1) {
                L += __shfl_xor_sync(0xffffffffu, L, o);
                C += __shfl_xor_sync(0xffffffffu, C, o);
            }
            mbar_wait(sbar + B_GD, sph);
            uint32_t tag = lds32(sb + OFF_TAG) | ((desc.y & F_SEMI) ? 2 : 0);
            if ((desc.y & F_FIN) && mbar_test(bar + B_HDR + ((seg + 1) % NSEG) * 8, ((seg + 1) / NSEG) & 1))
                tag |= lds32(sb + OFF_SEG + ((seg + 1) % NSEG) * SEG_BYTES + S_DESC + 4) / (F_END / 2);
            const float gl = (desc.y & (F_SEMI | F_FIN)) ? __uint_as_float(lds32(s + S_G + D * 4)) : -3.4e38f;
            const float M = fmaxf(m, gl), e = ex2(m - M), a = ex2(gl - M);
            const float W = fmaf(L, e, a), inv = rcp(W);
            if (lane == 0)
                sts128(s + S_CF, __float_as_uint(e * inv), __float_as_uint(a * inv), __float_as_uint(-C * e * inv),
                       (__float_as_uint(M + lg2(W)) & ~3u) | tag);
            __syncwarp();
            if (lane == 0) mbar_arrive(sbar + B_FC);
        }
    } else if ((unsigned)(w - W_G) < NGW) {
        if (w == W_G) {
            if (lane == 0) sts32(sb + OFF_TAG, __uint_as_float(~*(volatile unsigned int*)&g_epoch & 1));
        } else {
            mbar_wait(bar + B_GD, 0);
        }
        for (uint32_t seg = w - W_G;; seg += NGW) {
            const uint32_t s = sb + OFF_SEG + (seg % NSEG) * SEG_BYTES, sbar = bar + (seg % NSEG) * 8;
            mbar_wait(sbar + B_HDR, (seg / NSEG) & 1);
            const int4 desc = lds128(s + S_DESC);
            if (desc.y & F_END) break;
            if (desc.y & (F_SEMI | F_FIN)) {
                const uint32_t tag = lds32(sb + OFF_TAG) | ((desc.y & F_FIN) ? 2 : 0);
                const int cnt = (desc.y & F_FIN) ? 1 : NM;
                const uint32_t* mail = g_mail + (uint32_t)desc.x / TPH * (NM * REC);
                float M = NEG, W = 0.f, O[6] = {0.f, 0.f, 0.f, 0.f, 0.f, 0.f};
#pragma unroll 1
                for (int i0 = 0; i0 < cnt; i0 += GB, mail += GB * REC) {
                    uint2 pk[3 * GB];
                    uint32_t ls[GB], stale;
                    int it = 0;
                    do {
                        stale = 0;
#pragma unroll
                        for (int i = 0; i < GB; i++) {
                            ls[i] = 0xff7ffffcu | tag;
                            pk[3 * i] = pk[3 * i + 1] = pk[3 * i + 2] = make_uint2(tag, tag);
                            if (i0 + i < cnt) {
                                asm volatile("ld.relaxed.gpu.global.u32 %0, [%1];" : "=r"(ls[i]) : "l"(mail + i * REC + D) : "memory");
#pragma unroll
                                for (int k = 0; k < 3; k++)
                                    asm volatile("ld.relaxed.gpu.global.v2.u32 {%0,%1}, [%2];"
                                                 : "=r"(pk[3 * i + k].x), "=r"(pk[3 * i + k].y)
                                                 : "l"(mail + i * REC + k * 64 + lane * 2) : "memory");
                            }
                        }
#pragma unroll
                        for (int i = 0; i < GB; i++) stale |= ls[i] ^= tag;
#pragma unroll
                        for (int i = 0; i < 3 * GB; i++) stale |= (pk[i].x ^= tag) | (pk[i].y ^= tag);
                        if (++it > (1 << 22)) __trap();
                    } while (stale & 3);
                    float Mn = M;
#pragma unroll
                    for (int i = 0; i < GB; i++) Mn = fmaxf(Mn, __uint_as_float(ls[i]));
                    const float a = ex2(M - Mn);
                    M = Mn; W *= a;
#pragma unroll
                    for (int i = 0; i < 6; i++) O[i] *= a;
#pragma unroll
                    for (int i = 0; i < GB; i++) {
                        const float e = ex2(__uint_as_float(ls[i]) - M);
                        W += e;
#pragma unroll
                        for (int k = 0; k < 3; k++) {
                            O[2 * k] = fmaf(e, __uint_as_float(pk[3 * i + k].x), O[2 * k]);
                            O[2 * k + 1] = fmaf(e, __uint_as_float(pk[3 * i + k].y), O[2 * k + 1]);
                        }
                    }
                }
                const float inv = rcp(W);
#pragma unroll
                for (int k = 0; k < 3; k++) sts64(s + S_G + k * 256 + lane * 8, O[2 * k] * inv, O[2 * k + 1] * inv);
                if (lane == 0) sts32(s + S_G + D * 4, M + lg2(W));
            }
            __syncwarp();
            if (lane == 0) mbar_arrive(sbar + B_GD);
        }
    } else if (w / NKW == 0) {
        const int g = lane >> 3, l = lane & 7, godd = g & 1, row = 4 * w + g;
        const uint32_t sgA = pin(godd ? 0x3f803f80u : 0xbf80bf80u), sgB = pin(godd ? 0xbf80bf80u : 0x3f803f80u);
        const uint32_t oKA = pin(sb + row * (D * 4) + l * 16 + godd * 384), oKB = pin(oKA - godd * 768 + 384);
        const uint32_t oCA = pin(sb + T_C + row * (D * 2) + l * 8 + godd * 192), oCB = pin(oCA - godd * 384 + 192);
        const uint32_t oL = pin(S_LG + row * 16 + (l >> 2) * 8 + (l & 1) * 4), oS = pin(S_SC + row * 2);
        const bool own = (l & 3) == g, hi = l & 4, keep = ((l ^ g) & 2) == 0;
        uint32_t kslot = 0, batch0 = 0, kph = 0;
        for (uint32_t seg = 0;; seg++) {
            const uint32_t s = sb + OFF_SEG + (seg % NSEG) * SEG_BYTES, sbar = bar + (seg % NSEG) * 8;
            mbar_wait(sbar + B_HDR, (seg / NSEG) & 1);
            const int4 desc = lds128(s + S_DESC);
            if (desc.y & F_END) break;
            const uint32_t nt = desc.y & F_NT;
            uint2 qr[3];
#pragma unroll
            for (int i = 0; i < 3; i++) {
                const uint32_t oa = l * 8 + godd * 192 + i * 64, ob = oa + 192 - godd * 384;
                const uint2 a = lds64(s + S_Q + oa), b = lds64(s + S_Q + ob);
                const uint2 ca = lds64(sb + OFF_QT + oa), sa = lds64(sb + OFF_QT + QBYTES + oa);
                qr[i].x = rope2(a.x, ca.x, b.x, sa.x, sgA);
                qr[i].y = rope2(a.y, ca.y, b.y, sa.y, sgA);
            }
#pragma unroll 1
            for (uint32_t j = 0; j < nt; j++) {
                const uint32_t t = kslot * KSLOT;
                const uint32_t sc = s + oS + ((j << (desc.w & 255)) + (desc.w >> 8)) * (TR * 2);
                const uint32_t ks2 = lds16(sc) * 0x10001u, kz2 = lds16(sc + SCB) * 0x10001u;
                const uint32_t lgb = bar + B_LG + ((batch0 + (j >> 1)) % NBAT) * 8;
                const uint32_t lgc = j == nt - 1 ? 2 - (j & 1) : 1;
                mbar_wait(bar + B_FK + kslot * 8, kph);
                float c[4] = {0.f, 0.f, 0.f, 0.f};
#pragma unroll
                for (int jj = 0; jj < 3; jj++) {
                    const int4 xa = lds128(t + oKA + jj * 128), xb = lds128(t + oKB + jj * 128);
                    const uint2 ca = lds64(t + oCA + jj * 64), cb = lds64(t + oCB + jj * 64);
                    const uint2 sa = lds64(t + oCA + CBYTES + jj * 64), sbv = lds64(t + oCB + CBYTES + jj * 64);
                    const uint32_t a0 = bmul(bsub(i2bf2(xa.x, xa.y), kz2), ks2);
                    const uint32_t a1 = bmul(bsub(i2bf2(xa.z, xa.w), kz2), ks2);
                    const uint32_t b0 = bmul(bsub(i2bf2(xb.x, xb.y), kz2), ks2);
                    const uint32_t b1 = bmul(bsub(i2bf2(xb.z, xb.w), kz2), ks2);
                    mma_bf16(c, rope2(a0, ca.x, b0, sa.x, sgA), rope2(b0, cb.x, a0, sbv.x, sgB),
                             rope2(a1, ca.y, b1, sa.y, sgA), rope2(b1, cb.y, a1, sbv.y, sgB), qr[jj].x, qr[jj].y);
                }
                __syncwarp();
                if (lane == 0) mbar_arrive(bar + B_EK + kslot * 8);
                const float part = own ? (hi ? c[1] : c[0]) : (hi ? c[3] : c[2]);
                if (keep) sts32(s + oL + j * (TR * 16), part);
                __syncwarp();
                if (lane == 0) mbar_arrive(lgb, lgc);
                if (++kslot == NK) { kslot = 0; kph ^= 1; }
            }
            batch0 += (nt + 1) >> 1;
            __syncwarp();
            if (lane == 0) mbar_arrive(sbar + B_SE);
        }
    } else if (w == W_SCH) {
        if (elect_one()) {
            asm volatile("mbarrier.expect_tx.shared::cta.b64 [%0], %1;" ::"r"(bar + B_HDR), "r"(2 * QBYTES) : "memory");
            uint32_t seg = 0, c = blockIdx.x;
            while (c < NCLAIM) {
                const Claim cl = decode_claim(c);
                const uint32_t s = sb + OFF_SEG + (seg % NSEG) * SEG_BYTES, b = bar + (seg % NSEG) * 8;
                mbar_wait(b + B_SE, ((seg / NSEG) & 1) ^ 1);
                sts128(s + S_DESC, cl.tile0 + cl.off, cl.ntiles | (c >= C_F ? F_FIN : c >= C_S ? F_SEMI : 0), cl.piece,
                       cl.sh | cl.off << 8);
                if (seg) mbar_arrive(bar + B_DS + ((seg - 1) % NSEG) * 8);
                const uint32_t scb = cl.ntiles * TR * 2 << cl.sh, r = cl.tile0 * TR;
                mbar_expect(b + B_HDR, 4 * scb + QBYTES);
                bulk_plain(s + S_Q, p.q + cl.head * D, QBYTES, b + B_HDR);
                bulk_plain(s + S_SC, p.ks + r, scb, b + B_HDR);
                bulk_plain(s + S_SC + SCB, p.kz + r, scb, b + B_HDR);
                bulk_plain(s + S_SC + 2 * SCB, p.vs + r, scb, b + B_HDR);
                bulk_plain(s + S_SC + 3 * SCB, p.vz + r, scb, b + B_HDR);
                if (seg == 0) {
                    bulk_plain(sb + OFF_QT, p.qcos, QBYTES, bar + B_HDR);
                    bulk_plain(sb + OFF_QT + QBYTES, p.qsin, QBYTES, bar + B_HDR);
                    mbar_wait(bar + B_GD, 0);
                }
                mbar_wait(bar + B_GO, seg & 1);
                seg++;
                const unsigned nx = atomicInc(&g_queue, NCLAIM - 1);
                if (nx == NCLAIM - 1) g_epoch = lds32(sb + OFF_TAG);
                c = gridDim.x + nx;
            }
#pragma unroll 1
            for (int i = 0; i < NGW; i++, seg++) {
                const uint32_t s = sb + OFF_SEG + (seg % NSEG) * SEG_BYTES, b = bar + (seg % NSEG) * 8;
                mbar_wait(b + B_SE, ((seg / NSEG) & 1) ^ 1);
                sts128(s + S_DESC, 0, F_END, 0, 0);
                mbar_arrive(bar + B_DS + ((seg - 1) % NSEG) * 8);
                mbar_arrive(b + B_HDR);
            }
        }
    } else {
        if (elect_one()) {
            uint64_t pol;
            asm volatile("createpolicy.fractional.L2::evict_first.b64 %0, 1.0;" : "=l"(pol));
            uint32_t kslot = 0, vslot = 0, kph = 1, vph = 1;
            int pend[LEAD];
#pragma unroll
            for (int i = 0; i < LEAD; i++) pend[i] = -1;
            auto issue_v = [&]() {
                if (pend[0] >= 0) {
                    const uint32_t b = bar + vslot * 8;
                    mbar_wait(b + B_EV, vph);
                    mbar_wait(b + B_FV + (vslot >= WIN ? 0 : NV * 8) - WIN * 8, vph ^ (vslot >= WIN));
                    mbar_expect(b + B_FV, KBYTES);
                    bulk_stream(sb + OFF_V + vslot * KBYTES, p.qv + (size_t)pend[0] * (TR * D), KBYTES, b + B_FV, pol);
                    if (++vslot == NV) { vslot = 0; vph ^= 1; }
                }
#pragma unroll
                for (int i = 0; i + 1 < LEAD; i++) pend[i] = pend[i + 1];
                pend[LEAD - 1] = -1;
            };
            const Claim c0 = decode_claim(blockIdx.x % C_S);
            int4 desc = make_int4(c0.tile0 + c0.off, c0.ntiles, 0, GSH);
            for (uint32_t seg = 0; !(desc.y & F_END); seg++) {
                uint32_t tile = desc.x;
#pragma unroll 1
                for (int left = desc.y & F_NT; left > 0; left--, tile += 1u << (desc.w & 255)) {
                    const uint32_t t = sb + kslot * KSLOT, b = bar + kslot * 8;
                    const uint32_t ro = (tile % TPH) * (TR * D);
                    mbar_wait(b + B_EK, kph);
                    mbar_expect(b + B_FK, KSLOT);
                    bulk_stream(t, p.qk + (size_t)tile * (TR * D), KBYTES, b + B_FK, pol);
                    bulk_plain(t + T_C, p.kcos + ro, CBYTES, b + B_FK);
                    bulk_plain(t + T_S, p.ksin + ro, CBYTES, b + B_FK);
                    if (++kslot == NK) { kslot = 0; kph ^= 1; }
                    pend[LEAD - 1] = tile;
                    issue_v();
                }
                mbar_arrive(bar + B_GO);
                mbar_wait(bar + B_DS + (seg % NSEG) * 8, (seg / NSEG) & 1);
                desc = lds128(sb + OFF_SEG + ((seg + 1) % NSEG) * SEG_BYTES + S_DESC);
            }
#pragma unroll 1
            for (int i = 1; i < LEAD; i++) issue_v();
        }
    }
}

}

extern "C" void kernel_launch(void* const* d_in, const int* in_sizes, int n_in, void* d_out, int out_size) {
    (void)in_sizes; (void)n_in; (void)out_size;
    static int sms = 0;
    if (sms == 0) {
        int dev = 0;
        cudaGetDevice(&dev);
        cudaDeviceGetAttribute(&sms, cudaDevAttrMultiProcessorCount, dev);
        cudaFuncSetAttribute(kv_rope_decode_kernel, cudaFuncAttributeMaxDynamicSharedMemorySize, SMEM_BYTES);
    }
    Params p;
    p.q    = (const __nv_bfloat16*)d_in[0];
    p.qk   = (const int*)d_in[1];
    p.ks   = (const __nv_bfloat16*)d_in[2];
    p.kz   = (const __nv_bfloat16*)d_in[3];
    p.qv   = (const int*)d_in[4];
    p.vs   = (const __nv_bfloat16*)d_in[5];
    p.vz   = (const __nv_bfloat16*)d_in[6];
    p.qcos = (const __nv_bfloat16*)d_in[7];
    p.qsin = (const __nv_bfloat16*)d_in[8];
    p.kcos = (const __nv_bfloat16*)d_in[9];
    p.ksin = (const __nv_bfloat16*)d_in[10];
    p.out  = (__nv_bfloat16*)d_out;
    kv_rope_decode_kernel<<<sms, NTHREADS, SMEM_BYTES>>>(p);
}
```
